```python
import torch

def _softmax(x, axis=-1):
    return torch.softmax(x, dim=axis)

def _gelu(x):
    return torch.nn.functional.gelu(x, approximate='tanh')

def _silu(x):
    return torch.nn.functional.silu(x)

def _sigmoid(x):
    return torch.sigmoid(x)

def _layernorm(x, axis=-1, eps=1e-05):
    m = x.mean(dim=axis, keepdim=True)
    v = x.var(dim=axis, keepdim=True, unbiased=False)
    return (x - m) / torch.sqrt(v + eps)

def _scatter_add(tgt, idx, src, axis=0):
    return tgt.clone().index_add_(axis, idx, src)

def _segment_sum(src, seg, n):
    out = torch.zeros((n,) + src.shape[1:], dtype=src.dtype)
    return out.index_add_(0, seg, src)

def _pad(x, pw):
    flat = tuple((v for pair in reversed(pw) for v in pair))
    return torch.nn.functional.pad(x, flat)
kernel_name = 'gather_scatter__tensor_product_equiv_tfn__graph'

def setup_inputs():

    _w = lambda a: (lambda t: t.to(torch.bfloat16) if t.is_floating_point() else t)(torch.as_tensor(a))
    N, deg, C, L, DE = (10000, 32, 128, 1, 4)
    E = N * deg
    M = (L + 1) ** 2
    src = (lambda lo, hi, *s: torch.randint(lo, hi, s))(0, N, E).to(torch.int64)
    dst = (lambda lo, hi, *s: torch.randint(lo, hi, s))(0, N, E).to(torch.int64)
    r = (lambda *s: torch.randn(*s, dtype=torch.bfloat16) * 0.05)(E, 3)
    r = r / (torch.linalg.norm(r, dim=-1, keepdim=True) + 1e-09)
    rx, ry, rz = (r[:, 0].clone(), r[:, 1].clone(), r[:, 2].clone())
    Ys = [torch.ones((E, 1), dtype=float)]
    if L >= 1:
        Ys.append(r.to(float))
    if L >= 2:
        Ys.append(torch.stack([2 * rx * ry, 2 * ry * rz, (3 * rz * rz - 1.0) / (lambda _x: torch.sqrt(torch.as_tensor(_x)))(3.0), 2 * rx * rz, rx * rx - ry * ry], dim=-1).to(float))
    for _l in range(3, L + 1):
        Ys.append(((lambda *s: torch.randn(*s, dtype=torch.bfloat16) * 0.05)(E, 2 * _l + 1) * 0.3).to(float))
    Y = torch.cat(Ys, dim=-1)
    cg = torch.zeros((M, M, M), dtype=float)
    off = [_l * _l for _l in range(L + 2)]
    for l1 in range(L + 1):
        for l2 in range(L + 1):
            for l3 in range(abs(l1 - l2), min(L, l1 + l2) + 1):
                d1, d2, d3 = (2 * l1 + 1, 2 * l2 + 1, 2 * l3 + 1)
                cg[off[l1]:off[l1 + 1], off[l2]:off[l2 + 1], off[l3]:off[l3 + 1]] = (lambda *s: torch.randn(*s, dtype=torch.bfloat16) * 0.05)(d1, d2, d3) / (lambda _x: torch.sqrt(torch.as_tensor(_x)))(float(d1 * d2))
    return {'x': _w((lambda *s: torch.randn(*s, dtype=torch.bfloat16) * 0.05)(N, C, M) * 0.2), 'src': _w(src), 'dst': _w(dst), 'Y': _w(Y), 'edge_feat': _w((lambda *s: torch.randn(*s, dtype=torch.bfloat16) * 0.05)(E, DE)), 'w_rad': _w((lambda *s: torch.randn(*s, dtype=torch.bfloat16) * 0.05)(DE, C) * (1.0 / max(1.0, DE) ** 0.5)), 'cg': _w(cg), 'w_mix': _w((lambda *s: torch.randn(*s, dtype=torch.bfloat16) * 0.05)(C, C) * (1.0 / max(1.0, C) ** 0.5))}

def reference(x, src, dst, Y, edge_feat, w_rad, cg, w_mix):
    N, C, M = (x.shape[0], x.shape[1], x.shape[2])
    R = _silu(edge_feat @ w_rad)
    xs = x[src]
    tp = torch.einsum('eci,ef,ifo->eco', xs, Y, cg)
    msg = R[:, :, None] * tp
    agg = _segment_sum(msg.reshape(-1, C * M), dst, N).reshape(N, C, M)
    return torch.einsum('ncm,cd->ndm', agg, w_mix)
```

```cpp
#include <cuda.h>
#include <cuda_runtime.h>
#include <cuda_bf16.h>
#include <stdint.h>

namespace {

constexpr int NCTA   = 132;
constexpr int NW     = 8;
constexpr int NT     = 2 * NW * 32;
constexpr int RA     = 5;
constexpr int SLICE  = RA * NT;
constexpr int MBE    = 39;
constexpr int MB1    = NCTA * 32;
constexpr int MBW    = NCTA * 40;
constexpr int ASTR   = 44;
constexpr int NH     = NW * 32;
constexpr int RL     = 17;
constexpr int NG     = 24;
constexpr int KCAP   = 684;
constexpr int RCAP   = 2688;
constexpr int GK     = 48;
constexpr int NBIN   = 128;
constexpr int S      = 5;
constexpr int LCAP   = KCAP + NW + 4;
constexpr uint32_t EMPTY = NG << 25;

constexpr int SM_RING = 0;
constexpr int RSTR    = NW * S * 1024 + 256;
constexpr int SM_REC  = SM_RING + 4 * RSTR;
constexpr int SM_ZERO = SM_REC + RCAP * 16;
constexpr int SM_LIST = SM_ZERO + 128;
constexpr int SM_MISC = SM_LIST + LCAP * 16;
constexpr int SM_BAR  = SM_MISC + 256;
constexpr int SM_SRC  = SM_BAR + NW * S * 8 + 64;
constexpr int SM_SEG  = SM_SRC + LCAP * 16;
constexpr int SM_TOTAL = SM_SEG + NCTA * 4;
constexpr int SM_AREC = SM_RING;
constexpr int SM_AP   = SM_AREC + SLICE * 16;
constexpr int SM_AMB  = SM_AP + NH * 12;
constexpr int SM_AOFF = SM_AMB + (NCTA + 1) * ASTR * 4;
constexpr int SM_HIST = SM_AOFF + 576;
constexpr int SM_KEY  = SM_HIST + 576;
constexpr int SM_BIN  = SM_KEY + 128;
constexpr int SM_DUM  = SM_BIN + NG * NBIN * 4;
constexpr int SM_T2   = SM_DUM + NBIN * 4;
constexpr int SM_KSG  = SM_T2 + NG * NBIN * 4;
constexpr int SM_DOFF = SM_KSG + NG * GK * 16;
constexpr int SM_RAWY = SM_REC;
constexpr int SM_RAWF = SM_RAWY + SLICE * 8;
static_assert(SM_DOFF + 576 <= SM_REC && SM_RAWF + SLICE * 8 <= SM_ZERO, "temporaries must fit");
static_assert(SM_TOTAL <= 232448, "smem");
static_assert(SM_LIST % 128 == 0 && SM_BAR % 128 == 0 && SM_HIST % 16 == 0 && SM_BIN % 16 == 0 && SM_MISC % 16 == 0 && SM_KSG % 16 == 0, "align");
static_assert(NCTA <= RL * NW && RCAP < 4096 && NBIN == 128 && SM_SRC % 16 == 0 && SM_ZERO % 128 == 0 && S == 5, "layout");

struct Scratch {
    uint4    rec[NCTA * SLICE];
    uint32_t mb[NCTA * MBW];
    uint32_t ss[NCTA * SLICE];
    uint2    exc[NCTA * MBW];
    uint32_t epoch;
    uint32_t sent[2];
    uint32_t gap[61];
    uint32_t sent2[2];
};
__device__ __align__(128) Scratch g_scr;

#define STAMP(i)
#define STAMPT(i, th)
#define ANCHOR(i)

__device__ __forceinline__ uint32_t pack_bf16(float lo, float hi) {
    __nv_bfloat162 v = __floats2bfloat162_rn(lo, hi);
    return *reinterpret_cast<uint32_t*>(&v);
}
__device__ __forceinline__ void mma_k8_zero(float (&d)[4], uint32_t a0, uint32_t a1, uint32_t b0) {
    asm("mma.sync.aligned.m16n8k8.row.col.f32.bf16.bf16.f32 {%0,%1,%2,%3}, {%4,%5}, {%6}, {%7,%7,%7,%7};"
        : "=f"(d[0]), "=f"(d[1]), "=f"(d[2]), "=f"(d[3])
        : "r"(a0), "r"(a1), "r"(b0), "f"(0.f));
}
__device__ __forceinline__ float silu_half(float h) {
    float t;
    asm("tanh.approx.f32 %0, %1;" : "=f"(t) : "f"(h));
    return fmaf(h, t, h);
}
__device__ __forceinline__ uint32_t hmul2_lo(uint32_t x, uint32_t r) {
    __nv_bfloat162 a = *reinterpret_cast<__nv_bfloat162*>(&x), b = *reinterpret_cast<__nv_bfloat162*>(&r);
    __nv_bfloat162 c = __hmul2(a, __low2bfloat162(b));
    return *reinterpret_cast<uint32_t*>(&c);
}
__device__ __forceinline__ uint32_t hmul2_hi(uint32_t x, uint32_t r) {
    __nv_bfloat162 a = *reinterpret_cast<__nv_bfloat162*>(&x), b = *reinterpret_cast<__nv_bfloat162*>(&r);
    __nv_bfloat162 c = __hmul2(a, __high2bfloat162(b));
    return *reinterpret_cast<uint32_t*>(&c);
}
__device__ __forceinline__ uint4 lds128(uint32_t addr) {
    uint4 v;
    asm volatile("ld.shared.v4.u32 {%0,%1,%2,%3}, [%4];" : "=r"(v.x), "=r"(v.y), "=r"(v.z), "=r"(v.w) : "r"(addr) : "memory");
    return v;
}
__device__ __forceinline__ uint32_t movm(uint32_t v) {
    uint32_t r;
    asm("movmatrix.sync.aligned.m8n8.trans.b16 %0, %1;" : "=r"(r) : "r"(v));
    return r;
}
__device__ __forceinline__ uint4 ldg128_relaxed(const uint4* p) {
    uint4 v;
    asm volatile("ld.relaxed.gpu.global.v4.u32 {%0,%1,%2,%3}, [%4];" : "=r"(v.x), "=r"(v.y), "=r"(v.z), "=r"(v.w) : "l"(p) : "memory");
    return v;
}
__device__ __forceinline__ uint32_t atoms_inc(uint32_t addr) {
    uint32_t v;
    asm volatile("atom.shared.add.u32 %0, [%1], 1;" : "=r"(v) : "r"(addr) : "memory");
    return v;
}
__device__ __forceinline__ uint32_t lds32(uint32_t addr) {
    uint32_t v;
    asm volatile("ld.shared.u32 %0, [%1];" : "=r"(v) : "r"(addr) : "memory");
    return v;
}
__device__ __forceinline__ void sts32_if(bool p, uint32_t addr, uint32_t v) {
    asm volatile("{\n\t.reg .pred p;\n\tsetp.ne.u32 p, %2, 0;\n\t@p st.shared.u32 [%0], %1;\n\t}"
                 ::"r"(addr), "r"(v), "r"((uint32_t)p) : "memory");
}
__device__ __forceinline__ uint32_t lds32v(uint32_t addr) {
    uint32_t v;
    asm volatile("ld.volatile.shared.u32 %0, [%1];" : "=r"(v) : "r"(addr) : "memory");
    return v;
}
__device__ __forceinline__ uint32_t clock32() {
    uint32_t c;
    asm volatile("mov.u32 %0, %clock;" : "=r"(c));
    return c;
}
__device__ __forceinline__ uint32_t timer32() {
    uint32_t c;
    asm volatile("mov.u32 %0, %globaltimer_lo;" : "=r"(c));
    return c;
}
__device__ __forceinline__ uint32_t opaque(uint32_t v) {
    asm volatile("" : "+r"(v));
    return v;
}
#define HINT ""
__device__ __forceinline__ bool mbar_try(uint32_t bar, uint32_t parity) {
    uint32_t ok;
    asm volatile("{\n\t.reg .pred p;\n\t"
                 "mbarrier.try_wait.parity.shared::cta.b64 p, [%1], %2" HINT ";\n\t"
                 "selp.u32 %0, 1, 0, p;\n\t}"
                 : "=r"(ok) : "r"(bar), "r"(parity) : "memory");
    return ok;
}
__device__ __forceinline__ void mbar_wait(uint32_t bar, uint32_t parity) {
    int guard = 0;
    while (!mbar_try(bar, parity) && ++guard < (1 << 20)) {}
}
__device__ __forceinline__ void mbar_init(uint32_t bar, uint32_t count) {
    asm volatile("mbarrier.init.shared::cta.b64 [%0], %1;" ::"r"(bar), "r"(count) : "memory");
}
__device__ __forceinline__ uint32_t atoms_add(uint32_t addr, uint32_t x) {
    uint32_t v;
    asm volatile("atom.shared.add.u32 %0, [%1], %2;" : "=r"(v) : "r"(addr), "r"(x) : "memory");
    return v;
}
__device__ __forceinline__ uint2 lds64(uint32_t addr) {
    uint2 v;
    asm volatile("ld.shared.v2.u32 {%0,%1}, [%2];" : "=r"(v.x), "=r"(v.y) : "r"(addr) : "memory");
    return v;
}
__device__ __forceinline__ void sts128_if(bool p, uint32_t addr, uint4 v) {
    asm volatile("{\n\t.reg .pred p;\n\tsetp.ne.u32 p, %5, 0;\n\t@p st.shared.v4.u32 [%0], {%1,%2,%3,%4};\n\t}"
                 ::"r"(addr), "r"(v.x), "r"(v.y), "r"(v.z), "r"(v.w), "r"((uint32_t)p) : "memory");
}
__device__ __forceinline__ int warp_incl_scan(int v, int lane) {
#pragma unroll
    for (int o = 1; o < 32; o <<= 1) {
        const int u = __shfl_up_sync(0xffffffffu, v, o);
        if (lane >= o) v += u;
    }
    return v;
}

__device__ __forceinline__ void edge_terms(uint32_t efw, uint32_t yw, const uint32_t (&wz)[4][2], const uint32_t (&wt)[2],
                                           uint32_t (&R)[8], uint32_t& b0, uint32_t& b1) {
    float tt[4];
    mma_k8_zero(tt, wt[0], wt[1], yw);
    b0 = pack_bf16(tt[0], tt[2]);
    b1 = pack_bf16(tt[1], tt[3]);
#pragma unroll
    for (int j = 0; j < 4; j++) {
        float z[4];
        mma_k8_zero(z, wz[j][0], wz[j][1], efw);
        R[2 * j]     = pack_bf16(silu_half(z[0]), silu_half(z[2]));
        R[2 * j + 1] = pack_bf16(silu_half(z[1]), silu_half(z[3]));
    }
}
__device__ __forceinline__ void mma_k16v(float (&d)[4], uint32_t a0, uint32_t a1, uint32_t a2, uint32_t a3,
                                         uint32_t b0, uint32_t b1) {
    asm volatile("mma.sync.aligned.m16n8k16.row.col.f32.bf16.bf16.f32 {%0,%1,%2,%3}, {%4,%5,%6,%7}, {%8,%9}, {%0,%1,%2,%3};"
        : "+f"(d[0]), "+f"(d[1]), "+f"(d[2]), "+f"(d[3])
        : "r"(a0), "r"(a1), "r"(a2), "r"(a3), "r"(b0), "r"(b1));
}
__device__ __forceinline__ void load_row(uint32_t dst, const CUtensorMap* tm, uint32_t col, uint32_t row, uint32_t bar) {
    asm volatile("cp.async.bulk.tensor.2d.shared::cluster.global.tile.mbarrier::complete_tx::bytes [%0], [%1, {%2, %3}], [%4];"
                 ::"r"(dst), "l"(tm), "r"(col), "r"(row), "r"(bar) : "memory");
}
__device__ __forceinline__ void load_rows(uint32_t dst, const CUtensorMap* tm, uint4 cols, uint4 rows, uint32_t bar) {
    load_row(dst, tm, cols.x, rows.x, bar);
    load_row(dst + RSTR, tm, cols.y, rows.y, bar);
    load_row(dst + 2 * RSTR, tm, cols.z, rows.z, bar);
    load_row(dst + 3 * RSTR, tm, cols.w, rows.w, bar);
}
__device__ __forceinline__ bool elect_one() {
    uint32_t ok;
    asm volatile("{\n\t.reg .pred p;\n\telect.sync _|p, 0xffffffff;\n\tselp.u32 %0, 1, 0, p;\n\t}" : "=r"(ok));
    return ok;
}
__host__ __device__ constexpr int chunk_of(int m, int g) {
    return ((m & 1) + (g & 2) + 2 * (m & 2)) * 8 + ((g ^ m) & 1) + ((m >> 2) & 1) * 2 + 4 * (((g >> 2) ^ (m >> 1)) & 1);
}
__device__ __forceinline__ uint4 lds128v(uint32_t addr) {
    uint4 v;
    asm volatile("ld.volatile.shared.v4.u32 {%0,%1,%2,%3}, [%4];" : "=r"(v.x), "=r"(v.y), "=r"(v.z), "=r"(v.w) : "r"(addr) : "memory");
    return v;
}
#define MAIN_LOOP_PTX \
    "{\n" \
    ".reg .b32 v<16>, a<4>, u<4>, b<2>, c<2>, w<4>, ca0, ca1, na0, na1, ef, rx, ry, ex, ey, e0, e1, e3, gx, gy, cnt;\n" \
    ".reg .f32 z<8>, t<4>, y<4>, fz;\n" \
    ".reg .b16 h<2>;\n" \
    ".reg .pred pr, p<2>, q<3>;\n" \
    "mov.f32 fz, 0f00000000;\n" \
    "ld.shared.v4.u32 {e0,e1,ex,e3}, [%160];\n" \
    "prmt.b32 ey, e0, e1, %177;\n" \
    "lop3.b32 u2, ey, %176, %175, 0xea; add.u32 u2, u2, %178; ld.shared.v2.u32 {rx,ry}, [u2+%180];\n" \
    "shr.u32 u2, ex, 16; add.u32 na0, %171, u2; add.u32 na1, %172, u2;\n" \
    "mma.sync.aligned.m16n8k8.row.col.f32.bf16.bf16.f32 {y0,y1,y2,y3}, {%169,%170}, {ry}, {fz,fz,fz,fz};\n" \
    "and.b32 u2, ey, %173; setp.ne.u32 p0, u2, 0; and.b32 u2, ey, %174; setp.ne.u32 p1, u2, 0;\n" \
    "cvt.rn.bf16x2.f32 b0, y2, y0; cvt.rn.bf16x2.f32 b1, y3, y1;\n" \
    "selp.b32 a0, b0, 0, p0; selp.b32 a1, b0, 0, p1; selp.b32 a2, b1, 0, p0; selp.b32 a3, b1, 0, p1;\n" \
    "mma.sync.aligned.m16n8k8.row.col.f32.bf16.bf16.f32 {z0,z1,z2,z3}, {%161,%162}, {rx}, {fz,fz,fz,fz};\n" \
    "tanh.approx.f32 t0, z0; tanh.approx.f32 t1, z2;\n" \
    "ld.shared.v4.u32 {e0,e1,ex,e3}, [%160+16];\n" \
    "bra.uni SLOW;\n" \
    "S2:\n" \
    "add.u32 %160, %160, 16;\n" \
    "or.b32 c0, a0, a1; or.b32 c1, a2, a3;\n" \
    "mov.b32 ca0, na0; mov.b32 ca1, na1; mov.b32 ef, rx;\n" \
    "ld.shared.v4.u32 {v12,v13,v14,v15}, [ca0+640];\n" \
    "tanh.approx.f32 t2, z1; fma.rn.f32 z0, z0, t0, z0;\n" \
    "mov.b32 {h0,h1}, z0; mov.b32 u1, {h1,h1}; mul.bf16x2 w0, v0, u1;\n" \
    "mov.b32 {h0,h1}, z0; mov.b32 u1, {h1,h1}; mul.bf16x2 w1, v1, u1;\n" \
    "tanh.approx.f32 t3, z3; fma.rn.f32 z2, z2, t1, z2;\n" \
    "mov.b32 {h0,h1}, z2; mov.b32 u1, {h1,h1}; mul.bf16x2 w2, v2, u1;\n" \
    "mov.b32 {h0,h1}, z2; mov.b32 u1, {h1,h1}; mul.bf16x2 w3, v3, u1;\n" \
    "mma.sync.aligned.m16n8k16.row.col.f32.bf16.bf16.f32 {%128,%129,%130,%131}, {w0,w2,w1,w3}, {c0,c1}, {%128,%129,%130,%131};\n" \
    "mma.sync.aligned.m16n8k8.row.col.f32.bf16.bf16.f32 {z4,z5,z6,z7}, {%163,%164}, {ef}, {fz,fz,fz,fz};\n" \
    "ld.shared.v4.u32 {v0,v1,v2,v3}, [ca1+0];\n" \
    "tanh.approx.f32 t0, z4; fma.rn.f32 z1, z1, t2, z1;\n" \
    "mov.b32 {h0,h1}, z1; mov.b32 u1, {h1,h1}; mul.bf16x2 w0, v4, u1;\n" \
    "mov.b32 {h0,h1}, z1; mov.b32 u1, {h1,h1}; mul.bf16x2 w1, v5, u1;\n" \
    "tanh.approx.f32 t1, z6; fma.rn.f32 z3, z3, t3, z3;\n" \
    "mov.b32 {h0,h1}, z3; mov.b32 u1, {h1,h1}; mul.bf16x2 w2, v6, u1;\n" \
    "mov.b32 {h0,h1}, z3; mov.b32 u1, {h1,h1}; mul.bf16x2 w3, v7, u1;\n" \
    "mma.sync.aligned.m16n8k16.row.col.f32.bf16.bf16.f32 {%132,%133,%134,%135}, {w0,w2,w1,w3}, {c0,c1}, {%132,%133,%134,%135};\n" \
    "ld.shared.v4.u32 {v4,v5,v6,v7}, [ca1+128];\n" \
    "tanh.approx.f32 t2, z5; fma.rn.f32 z4, z4, t0, z4;\n" \
    "mov.b32 {h0,h1}, z4; mov.b32 u1, {h1,h1}; mul.bf16x2 w0, v8, u1;\n" \
    "mov.b32 {h0,h1}, z4; mov.b32 u1, {h1,h1}; mul.bf16x2 w1, v9, u1;\n" \
    "tanh.approx.f32 t3, z7; fma.rn.f32 z6, z6, t1, z6;\n" \
    "mov.b32 {h0,h1}, z6; mov.b32 u1, {h1,h1}; mul.bf16x2 w2, v10, u1;\n" \
    "mov.b32 {h0,h1}, z6; mov.b32 u1, {h1,h1}; mul.bf16x2 w3, v11, u1;\n" \
    "mma.sync.aligned.m16n8k16.row.col.f32.bf16.bf16.f32 {%136,%137,%138,%139}, {w0,w2,w1,w3}, {c0,c1}, {%136,%137,%138,%139};\n" \
    "mma.sync.aligned.m16n8k8.row.col.f32.bf16.bf16.f32 {z0,z1,z2,z3}, {%165,%166}, {ef}, {fz,fz,fz,fz};\n" \
    "prmt.b32 ey, e0, e1, %177;\n" \
    "lop3.b32 u2, ey, %176, %175, 0xea; add.u32 u2, u2, %178; ld.shared.v2.u32 {rx,ry}, [u2+%180];\n" \
    "ld.shared.v4.u32 {v8,v9,v10,v11}, [ca1+512];\n" \
    "tanh.approx.f32 t0, z0; fma.rn.f32 z5, z5, t2, z5;\n" \
    "mov.b32 {h0,h1}, z5; mov.b32 u1, {h1,h1}; mul.bf16x2 w0, v12, u1;\n" \
    "mov.b32 {h0,h1}, z5; mov.b32 u1, {h1,h1}; mul.bf16x2 w1, v13, u1;\n" \
    "tanh.approx.f32 t1, z2; fma.rn.f32 z7, z7, t3, z7;\n" \
    "mov.b32 {h0,h1}, z7; mov.b32 u1, {h1,h1}; mul.bf16x2 w2, v14, u1;\n" \
    "mov.b32 {h0,h1}, z7; mov.b32 u1, {h1,h1}; mul.bf16x2 w3, v15, u1;\n" \
    "mma.sync.aligned.m16n8k16.row.col.f32.bf16.bf16.f32 {%140,%141,%142,%143}, {w0,w2,w1,w3}, {c0,c1}, {%140,%141,%142,%143};\n" \
    "and.b32 u2, ex, 1; mbarrier.test_wait.parity.shared::cta.b64 pr, [e3], u2;\n" \
    "shr.u32 u2, ex, 16; add.u32 na0, %171, u2; add.u32 na1, %172, u2;\n" \
    "ld.shared.v4.u32 {v12,v13,v14,v15}, [ca1+640];\n" \
    "tanh.approx.f32 t2, z1; fma.rn.f32 z0, z0, t0, z0;\n" \
    "mov.b32 {h0,h1}, z0; mov.b32 u1, {h1,h1}; mul.bf16x2 w0, v0, u1;\n" \
    "mov.b32 {h0,h1}, z0; mov.b32 u1, {h1,h1}; mul.bf16x2 w1, v1, u1;\n" \
    "tanh.approx.f32 t3, z3; fma.rn.f32 z2, z2, t1, z2;\n" \
    "mov.b32 {h0,h1}, z2; mov.b32 u1, {h1,h1}; mul.bf16x2 w2, v2, u1;\n" \
    "mov.b32 {h0,h1}, z2; mov.b32 u1, {h1,h1}; mul.bf16x2 w3, v3, u1;\n" \
    "mma.sync.aligned.m16n8k16.row.col.f32.bf16.bf16.f32 {%144,%145,%146,%147}, {w0,w2,w1,w3}, {c0,c1}, {%144,%145,%146,%147};\n" \
    "mma.sync.aligned.m16n8k8.row.col.f32.bf16.bf16.f32 {z4,z5,z6,z7}, {%167,%168}, {ef}, {fz,fz,fz,fz};\n" \
    "st.volatile.shared.u32 [%179], %160;\n" \
    "@pr ld.shared.v4.u32 {v0,v1,v2,v3}, [na0+0];\n" \
    "tanh.approx.f32 t0, z4; fma.rn.f32 z1, z1, t2, z1;\n" \
    "mov.b32 {h0,h1}, z1; mov.b32 u1, {h1,h1}; mul.bf16x2 w0, v4, u1;\n" \
    "mov.b32 {h0,h1}, z1; mov.b32 u1, {h1,h1}; mul.bf16x2 w1, v5, u1;\n" \
    "tanh.approx.f32 t1, z6; fma.rn.f32 z3, z3, t3, z3;\n" \
    "mov.b32 {h0,h1}, z3; mov.b32 u1, {h1,h1}; mul.bf16x2 w2, v6, u1;\n" \
    "mov.b32 {h0,h1}, z3; mov.b32 u1, {h1,h1}; mul.bf16x2 w3, v7, u1;\n" \
    "mma.sync.aligned.m16n8k16.row.col.f32.bf16.bf16.f32 {%148,%149,%150,%151}, {w0,w2,w1,w3}, {c0,c1}, {%148,%149,%150,%151};\n" \
    "@pr ld.shared.v4.u32 {v4,v5,v6,v7}, [na0+128];\n" \
    "tanh.approx.f32 t2, z5; fma.rn.f32 z4, z4, t0, z4;\n" \
    "mov.b32 {h0,h1}, z4; mov.b32 u1, {h1,h1}; mul.bf16x2 w0, v8, u1;\n" \
    "mov.b32 {h0,h1}, z4; mov.b32 u1, {h1,h1}; mul.bf16x2 w1, v9, u1;\n" \
    "tanh.approx.f32 t3, z7; fma.rn.f32 z6, z6, t1, z6;\n" \
    "mov.b32 {h0,h1}, z6; mov.b32 u1, {h1,h1}; mul.bf16x2 w2, v10, u1;\n" \
    "mov.b32 {h0,h1}, z6; mov.b32 u1, {h1,h1}; mul.bf16x2 w3, v11, u1;\n" \
    "mma.sync.aligned.m16n8k16.row.col.f32.bf16.bf16.f32 {%152,%153,%154,%155}, {w0,w2,w1,w3}, {c0,c1}, {%152,%153,%154,%155};\n" \
    "mma.sync.aligned.m16n8k8.row.col.f32.bf16.bf16.f32 {z0,z1,z2,z3}, {%161,%162}, {rx}, {fz,fz,fz,fz};\n" \
    "mma.sync.aligned.m16n8k8.row.col.f32.bf16.bf16.f32 {y0,y1,y2,y3}, {%169,%170}, {ry}, {fz,fz,fz,fz};\n" \
    "and.b32 u2, ey, %173; setp.ne.u32 p0, u2, 0; and.b32 u2, ey, %174; setp.ne.u32 p1, u2, 0;\n" \
    "and.b32 u2, ex, 6;\n" \
    "setp.eq.and.u32 q0, u2, 4, pr;\n" \
    "setp.eq.and.u32 q1, u2, 6, pr;\n" \
    "setp.eq.and.u32 q2, u2, 2, pr;\n" \
    "ld.shared.v4.u32 {e0,e1,ex,e3}, [%160+16];\n" \
    "@pr ld.shared.v4.u32 {v8,v9,v10,v11}, [na0+512];\n" \
    "tanh.approx.f32 t0, z0; fma.rn.f32 z5, z5, t2, z5;\n" \
    "mov.b32 {h0,h1}, z5; mov.b32 u1, {h1,h1}; mul.bf16x2 w0, v12, u1;\n" \
    "mov.b32 {h0,h1}, z5; mov.b32 u1, {h1,h1}; mul.bf16x2 w1, v13, u1;\n" \
    "tanh.approx.f32 t1, z2; fma.rn.f32 z7, z7, t3, z7;\n" \
    "mov.b32 {h0,h1}, z7; mov.b32 u1, {h1,h1}; mul.bf16x2 w2, v14, u1;\n" \
    "mov.b32 {h0,h1}, z7; mov.b32 u1, {h1,h1}; mul.bf16x2 w3, v15, u1;\n" \
    "mma.sync.aligned.m16n8k16.row.col.f32.bf16.bf16.f32 {%156,%157,%158,%159}, {w0,w2,w1,w3}, {c0,c1}, {%156,%157,%158,%159};\n" \
    "cvt.rn.bf16x2.f32 b0, y2, y0; cvt.rn.bf16x2.f32 b1, y3, y1;\n" \
    "selp.b32 a0, b0, 0, p0; selp.b32 a1, b0, 0, p1; selp.b32 a2, b1, 0, p0; selp.b32 a3, b1, 0, p1;\n" \
    "@q0 bra.uni S1;\n" \
    "@q1 bra.uni S2;\n" \
    "@!q2 bra.uni SLOW;\n" \
    "S0:\n" \
    "add.u32 %160, %160, 16;\n" \
    "mov.b32 ca0, na0; mov.b32 ca1, na1; mov.b32 ef, rx;\n" \
    "ld.shared.v4.u32 {v12,v13,v14,v15}, [ca0+640];\n" \
    "tanh.approx.f32 t2, z1; fma.rn.f32 z0, z0, t0, z0;\n" \
    "mov.b32 {h0,h1}, z0; mov.b32 u1, {h1,h1}; mul.bf16x2 v0, v0, u1;\n" \
    "mov.b32 {h0,h1}, z0; mov.b32 u1, {h1,h1}; mul.bf16x2 v1, v1, u1;\n" \
    "mma.sync.aligned.m16n8k16.row.col.f32.bf16.bf16.f32 {%0,%1,%2,%3}, {a0,a1,a2,a3}, {v0,v1}, {%0,%1,%2,%3};\n" \
    "tanh.approx.f32 t3, z3; fma.rn.f32 z2, z2, t1, z2;\n" \
    "mov.b32 {h0,h1}, z2; mov.b32 u1, {h1,h1}; mul.bf16x2 v2, v2, u1;\n" \
    "mov.b32 {h0,h1}, z2; mov.b32 u1, {h1,h1}; mul.bf16x2 v3, v3, u1;\n" \
    "mma.sync.aligned.m16n8k16.row.col.f32.bf16.bf16.f32 {%4,%5,%6,%7}, {a0,a1,a2,a3}, {v2,v3}, {%4,%5,%6,%7};\n" \
    "mma.sync.aligned.m16n8k8.row.col.f32.bf16.bf16.f32 {z4,z5,z6,z7}, {%163,%164}, {ef}, {fz,fz,fz,fz};\n" \
    "ld.shared.v4.u32 {v0,v1,v2,v3}, [ca1+0];\n" \
    "tanh.approx.f32 t0, z4; fma.rn.f32 z1, z1, t2, z1;\n" \
    "mov.b32 {h0,h1}, z1; mov.b32 u1, {h1,h1}; mul.bf16x2 v4, v4, u1;\n" \
    "mov.b32 {h0,h1}, z1; mov.b32 u1, {h1,h1}; mul.bf16x2 v5, v5, u1;\n" \
    "mma.sync.aligned.m16n8k16.row.col.f32.bf16.bf16.f32 {%8,%9,%10,%11}, {a0,a1,a2,a3}, {v4,v5}, {%8,%9,%10,%11};\n" \
    "tanh.approx.f32 t1, z6; fma.rn.f32 z3, z3, t3, z3;\n" \
    "mov.b32 {h0,h1}, z3; mov.b32 u1, {h1,h1}; mul.bf16x2 v6, v6, u1;\n" \
    "mov.b32 {h0,h1}, z3; mov.b32 u1, {h1,h1}; mul.bf16x2 v7, v7, u1;\n" \
    "mma.sync.aligned.m16n8k16.row.col.f32.bf16.bf16.f32 {%12,%13,%14,%15}, {a0,a1,a2,a3}, {v6,v7}, {%12,%13,%14,%15};\n" \
    "ld.shared.v4.u32 {v4,v5,v6,v7}, [ca1+128];\n" \
    "tanh.approx.f32 t2, z5; fma.rn.f32 z4, z4, t0, z4;\n" \
    "mov.b32 {h0,h1}, z4; mov.b32 u1, {h1,h1}; mul.bf16x2 v8, v8, u1;\n" \
    "mov.b32 {h0,h1}, z4; mov.b32 u1, {h1,h1}; mul.bf16x2 v9, v9, u1;\n" \
    "mma.sync.aligned.m16n8k16.row.col.f32.bf16.bf16.f32 {%16,%17,%18,%19}, {a0,a1,a2,a3}, {v8,v9}, {%16,%17,%18,%19};\n" \
    "tanh.approx.f32 t3, z7; fma.rn.f32 z6, z6, t1, z6;\n" \
    "mov.b32 {h0,h1}, z6; mov.b32 u1, {h1,h1}; mul.bf16x2 v10, v10, u1;\n" \
    "mov.b32 {h0,h1}, z6; mov.b32 u1, {h1,h1}; mul.bf16x2 v11, v11, u1;\n" \
    "mma.sync.aligned.m16n8k16.row.col.f32.bf16.bf16.f32 {%20,%21,%22,%23}, {a0,a1,a2,a3}, {v10,v11}, {%20,%21,%22,%23};\n" \
    "mma.sync.aligned.m16n8k8.row.col.f32.bf16.bf16.f32 {z0,z1,z2,z3}, {%165,%166}, {ef}, {fz,fz,fz,fz};\n" \
    "prmt.b32 ey, e0, e1, %177;\n" \
    "lop3.b32 u2, ey, %176, %175, 0xea; add.u32 u2, u2, %178; ld.shared.v2.u32 {rx,ry}, [u2+%180];\n" \
    "ld.shared.v4.u32 {v8,v9,v10,v11}, [ca1+512];\n" \
    "tanh.approx.f32 t0, z0; fma.rn.f32 z5, z5, t2, z5;\n" \
    "mov.b32 {h0,h1}, z5; mov.b32 u1, {h1,h1}; mul.bf16x2 v12, v12, u1;\n" \
    "mov.b32 {h0,h1}, z5; mov.b32 u1, {h1,h1}; mul.bf16x2 v13, v13, u1;\n" \
    "mma.sync.aligned.m16n8k16.row.col.f32.bf16.bf16.f32 {%24,%25,%26,%27}, {a0,a1,a2,a3}, {v12,v13}, {%24,%25,%26,%27};\n" \
    "tanh.approx.f32 t1, z2; fma.rn.f32 z7, z7, t3, z7;\n" \
    "mov.b32 {h0,h1}, z7; mov.b32 u1, {h1,h1}; mul.bf16x2 v14, v14, u1;\n" \
    "mov.b32 {h0,h1}, z7; mov.b32 u1, {h1,h1}; mul.bf16x2 v15, v15, u1;\n" \
    "mma.sync.aligned.m16n8k16.row.col.f32.bf16.bf16.f32 {%28,%29,%30,%31}, {a0,a1,a2,a3}, {v14,v15}, {%28,%29,%30,%31};\n" \
    "and.b32 u2, ex, 1; mbarrier.test_wait.parity.shared::cta.b64 pr, [e3], u2;\n" \
    "shr.u32 u2, ex, 16; add.u32 na0, %171, u2; add.u32 na1, %172, u2;\n" \
    "ld.shared.v4.u32 {v12,v13,v14,v15}, [ca1+640];\n" \
    "tanh.approx.f32 t2, z1; fma.rn.f32 z0, z0, t0, z0;\n" \
    "mov.b32 {h0,h1}, z0; mov.b32 u1, {h1,h1}; mul.bf16x2 v0, v0, u1;\n" \
    "mov.b32 {h0,h1}, z0; mov.b32 u1, {h1,h1}; mul.bf16x2 v1, v1, u1;\n" \
    "mma.sync.aligned.m16n8k16.row.col.f32.bf16.bf16.f32 {%32,%33,%34,%35}, {a0,a1,a2,a3}, {v0,v1}, {%32,%33,%34,%35};\n" \
    "tanh.approx.f32 t3, z3; fma.rn.f32 z2, z2, t1, z2;\n" \
    "mov.b32 {h0,h1}, z2; mov.b32 u1, {h1,h1}; mul.bf16x2 v2, v2, u1;\n" \
    "mov.b32 {h0,h1}, z2; mov.b32 u1, {h1,h1}; mul.bf16x2 v3, v3, u1;\n" \
    "mma.sync.aligned.m16n8k16.row.col.f32.bf16.bf16.f32 {%36,%37,%38,%39}, {a0,a1,a2,a3}, {v2,v3}, {%36,%37,%38,%39};\n" \
    "mma.sync.aligned.m16n8k8.row.col.f32.bf16.bf16.f32 {z4,z5,z6,z7}, {%167,%168}, {ef}, {fz,fz,fz,fz};\n" \
    "st.volatile.shared.u32 [%179], %160;\n" \
    "@pr ld.shared.v4.u32 {v0,v1,v2,v3}, [na0+0];\n" \
    "tanh.approx.f32 t0, z4; fma.rn.f32 z1, z1, t2, z1;\n" \
    "mov.b32 {h0,h1}, z1; mov.b32 u1, {h1,h1}; mul.bf16x2 v4, v4, u1;\n" \
    "mov.b32 {h0,h1}, z1; mov.b32 u1, {h1,h1}; mul.bf16x2 v5, v5, u1;\n" \
    "mma.sync.aligned.m16n8k16.row.col.f32.bf16.bf16.f32 {%40,%41,%42,%43}, {a0,a1,a2,a3}, {v4,v5}, {%40,%41,%42,%43};\n" \
    "tanh.approx.f32 t1, z6; fma.rn.f32 z3, z3, t3, z3;\n" \
    "mov.b32 {h0,h1}, z3; mov.b32 u1, {h1,h1}; mul.bf16x2 v6, v6, u1;\n" \
    "mov.b32 {h0,h1}, z3; mov.b32 u1, {h1,h1}; mul.bf16x2 v7, v7, u1;\n" \
    "mma.sync.aligned.m16n8k16.row.col.f32.bf16.bf16.f32 {%44,%45,%46,%47}, {a0,a1,a2,a3}, {v6,v7}, {%44,%45,%46,%47};\n" \
    "@pr ld.shared.v4.u32 {v4,v5,v6,v7}, [na0+128];\n" \
    "tanh.approx.f32 t2, z5; fma.rn.f32 z4, z4, t0, z4;\n" \
    "mov.b32 {h0,h1}, z4; mov.b32 u1, {h1,h1}; mul.bf16x2 v8, v8, u1;\n" \
    "mov.b32 {h0,h1}, z4; mov.b32 u1, {h1,h1}; mul.bf16x2 v9, v9, u1;\n" \
    "mma.sync.aligned.m16n8k16.row.col.f32.bf16.bf16.f32 {%48,%49,%50,%51}, {a0,a1,a2,a3}, {v8,v9}, {%48,%49,%50,%51};\n" \
    "tanh.approx.f32 t3, z7; fma.rn.f32 z6, z6, t1, z6;\n" \
    "mov.b32 {h0,h1}, z6; mov.b32 u1, {h1,h1}; mul.bf16x2 v10, v10, u1;\n" \
    "mov.b32 {h0,h1}, z6; mov.b32 u1, {h1,h1}; mul.bf16x2 v11, v11, u1;\n" \
    "mma.sync.aligned.m16n8k16.row.col.f32.bf16.bf16.f32 {%52,%53,%54,%55}, {a0,a1,a2,a3}, {v10,v11}, {%52,%53,%54,%55};\n" \
    "mma.sync.aligned.m16n8k8.row.col.f32.bf16.bf16.f32 {z0,z1,z2,z3}, {%161,%162}, {rx}, {fz,fz,fz,fz};\n" \
    "mma.sync.aligned.m16n8k8.row.col.f32.bf16.bf16.f32 {y0,y1,y2,y3}, {%169,%170}, {ry}, {fz,fz,fz,fz};\n" \
    "and.b32 u2, ey, %173; setp.ne.u32 p0, u2, 0; and.b32 u2, ey, %174; setp.ne.u32 p1, u2, 0;\n" \
    "and.b32 u2, ex, 6;\n" \
    "setp.eq.and.u32 q0, u2, 2, pr;\n" \
    "setp.eq.and.u32 q1, u2, 6, pr;\n" \
    "setp.eq.and.u32 q2, u2, 4, pr;\n" \
    "ld.shared.v4.u32 {e0,e1,ex,e3}, [%160+16];\n" \
    "@pr ld.shared.v4.u32 {v8,v9,v10,v11}, [na0+512];\n" \
    "tanh.approx.f32 t0, z0; fma.rn.f32 z5, z5, t2, z5;\n" \
    "mov.b32 {h0,h1}, z5; mov.b32 u1, {h1,h1}; mul.bf16x2 v12, v12, u1;\n" \
    "mov.b32 {h0,h1}, z5; mov.b32 u1, {h1,h1}; mul.bf16x2 v13, v13, u1;\n" \
    "mma.sync.aligned.m16n8k16.row.col.f32.bf16.bf16.f32 {%56,%57,%58,%59}, {a0,a1,a2,a3}, {v12,v13}, {%56,%57,%58,%59};\n" \
    "tanh.approx.f32 t1, z2; fma.rn.f32 z7, z7, t3, z7;\n" \
    "mov.b32 {h0,h1}, z7; mov.b32 u1, {h1,h1}; mul.bf16x2 v14, v14, u1;\n" \
    "mov.b32 {h0,h1}, z7; mov.b32 u1, {h1,h1}; mul.bf16x2 v15, v15, u1;\n" \
    "mma.sync.aligned.m16n8k16.row.col.f32.bf16.bf16.f32 {%60,%61,%62,%63}, {a0,a1,a2,a3}, {v14,v15}, {%60,%61,%62,%63};\n" \
    "cvt.rn.bf16x2.f32 b0, y2, y0; cvt.rn.bf16x2.f32 b1, y3, y1;\n" \
    "selp.b32 a0, b0, 0, p0; selp.b32 a1, b0, 0, p1; selp.b32 a2, b1, 0, p0; selp.b32 a3, b1, 0, p1;\n" \
    "@q0 bra.uni S0;\n" \
    "@q1 bra.uni S2;\n" \
    "@!q2 bra.uni SLOW;\n" \
    "S1:\n" \
    "add.u32 %160, %160, 16;\n" \
    "mov.b32 ca0, na0; mov.b32 ca1, na1; mov.b32 ef, rx;\n" \
    "ld.shared.v4.u32 {v12,v13,v14,v15}, [ca0+640];\n" \
    "tanh.approx.f32 t2, z1; fma.rn.f32 z0, z0, t0, z0;\n" \
    "mov.b32 {h0,h1}, z0; mov.b32 u1, {h1,h1}; mul.bf16x2 v0, v0, u1;\n" \
    "mov.b32 {h0,h1}, z0; mov.b32 u1, {h1,h1}; mul.bf16x2 v1, v1, u1;\n" \
    "mma.sync.aligned.m16n8k16.row.col.f32.bf16.bf16.f32 {%64,%65,%66,%67}, {a0,a1,a2,a3}, {v0,v1}, {%64,%65,%66,%67};\n" \
    "tanh.approx.f32 t3, z3; fma.rn.f32 z2, z2, t1, z2;\n" \
    "mov.b32 {h0,h1}, z2; mov.b32 u1, {h1,h1}; mul.bf16x2 v2, v2, u1;\n" \
    "mov.b32 {h0,h1}, z2; mov.b32 u1, {h1,h1}; mul.bf16x2 v3, v3, u1;\n" \
    "mma.sync.aligned.m16n8k16.row.col.f32.bf16.bf16.f32 {%68,%69,%70,%71}, {a0,a1,a2,a3}, {v2,v3}, {%68,%69,%70,%71};\n" \
    "mma.sync.aligned.m16n8k8.row.col.f32.bf16.bf16.f32 {z4,z5,z6,z7}, {%163,%164}, {ef}, {fz,fz,fz,fz};\n" \
    "ld.shared.v4.u32 {v0,v1,v2,v3}, [ca1+0];\n" \
    "tanh.approx.f32 t0, z4; fma.rn.f32 z1, z1, t2, z1;\n" \
    "mov.b32 {h0,h1}, z1; mov.b32 u1, {h1,h1}; mul.bf16x2 v4, v4, u1;\n" \
    "mov.b32 {h0,h1}, z1; mov.b32 u1, {h1,h1}; mul.bf16x2 v5, v5, u1;\n" \
    "mma.sync.aligned.m16n8k16.row.col.f32.bf16.bf16.f32 {%72,%73,%74,%75}, {a0,a1,a2,a3}, {v4,v5}, {%72,%73,%74,%75};\n" \
    "tanh.approx.f32 t1, z6; fma.rn.f32 z3, z3, t3, z3;\n" \
    "mov.b32 {h0,h1}, z3; mov.b32 u1, {h1,h1}; mul.bf16x2 v6, v6, u1;\n" \
    "mov.b32 {h0,h1}, z3; mov.b32 u1, {h1,h1}; mul.bf16x2 v7, v7, u1;\n" \
    "mma.sync.aligned.m16n8k16.row.col.f32.bf16.bf16.f32 {%76,%77,%78,%79}, {a0,a1,a2,a3}, {v6,v7}, {%76,%77,%78,%79};\n" \
    "ld.shared.v4.u32 {v4,v5,v6,v7}, [ca1+128];\n" \
    "tanh.approx.f32 t2, z5; fma.rn.f32 z4, z4, t0, z4;\n" \
    "mov.b32 {h0,h1}, z4; mov.b32 u1, {h1,h1}; mul.bf16x2 v8, v8, u1;\n" \
    "mov.b32 {h0,h1}, z4; mov.b32 u1, {h1,h1}; mul.bf16x2 v9, v9, u1;\n" \
    "mma.sync.aligned.m16n8k16.row.col.f32.bf16.bf16.f32 {%80,%81,%82,%83}, {a0,a1,a2,a3}, {v8,v9}, {%80,%81,%82,%83};\n" \
    "tanh.approx.f32 t3, z7; fma.rn.f32 z6, z6, t1, z6;\n" \
    "mov.b32 {h0,h1}, z6; mov.b32 u1, {h1,h1}; mul.bf16x2 v10, v10, u1;\n" \
    "mov.b32 {h0,h1}, z6; mov.b32 u1, {h1,h1}; mul.bf16x2 v11, v11, u1;\n" \
    "mma.sync.aligned.m16n8k16.row.col.f32.bf16.bf16.f32 {%84,%85,%86,%87}, {a0,a1,a2,a3}, {v10,v11}, {%84,%85,%86,%87};\n" \
    "mma.sync.aligned.m16n8k8.row.col.f32.bf16.bf16.f32 {z0,z1,z2,z3}, {%165,%166}, {ef}, {fz,fz,fz,fz};\n" \
    "prmt.b32 ey, e0, e1, %177;\n" \
    "lop3.b32 u2, ey, %176, %175, 0xea; add.u32 u2, u2, %178; ld.shared.v2.u32 {rx,ry}, [u2+%180];\n" \
    "ld.shared.v4.u32 {v8,v9,v10,v11}, [ca1+512];\n" \
    "tanh.approx.f32 t0, z0; fma.rn.f32 z5, z5, t2, z5;\n" \
    "mov.b32 {h0,h1}, z5; mov.b32 u1, {h1,h1}; mul.bf16x2 v12, v12, u1;\n" \
    "mov.b32 {h0,h1}, z5; mov.b32 u1, {h1,h1}; mul.bf16x2 v13, v13, u1;\n" \
    "mma.sync.aligned.m16n8k16.row.col.f32.bf16.bf16.f32 {%88,%89,%90,%91}, {a0,a1,a2,a3}, {v12,v13}, {%88,%89,%90,%91};\n" \
    "tanh.approx.f32 t1, z2; fma.rn.f32 z7, z7, t3, z7;\n" \
    "mov.b32 {h0,h1}, z7; mov.b32 u1, {h1,h1}; mul.bf16x2 v14, v14, u1;\n" \
    "mov.b32 {h0,h1}, z7; mov.b32 u1, {h1,h1}; mul.bf16x2 v15, v15, u1;\n" \
    "mma.sync.aligned.m16n8k16.row.col.f32.bf16.bf16.f32 {%92,%93,%94,%95}, {a0,a1,a2,a3}, {v14,v15}, {%92,%93,%94,%95};\n" \
    "and.b32 u2, ex, 1; mbarrier.test_wait.parity.shared::cta.b64 pr, [e3], u2;\n" \
    "shr.u32 u2, ex, 16; add.u32 na0, %171, u2; add.u32 na1, %172, u2;\n" \
    "ld.shared.v4.u32 {v12,v13,v14,v15}, [ca1+640];\n" \
    "tanh.approx.f32 t2, z1; fma.rn.f32 z0, z0, t0, z0;\n" \
    "mov.b32 {h0,h1}, z0; mov.b32 u1, {h1,h1}; mul.bf16x2 v0, v0, u1;\n" \
    "mov.b32 {h0,h1}, z0; mov.b32 u1, {h1,h1}; mul.bf16x2 v1, v1, u1;\n" \
    "mma.sync.aligned.m16n8k16.row.col.f32.bf16.bf16.f32 {%96,%97,%98,%99}, {a0,a1,a2,a3}, {v0,v1}, {%96,%97,%98,%99};\n" \
    "tanh.approx.f32 t3, z3; fma.rn.f32 z2, z2, t1, z2;\n" \
    "mov.b32 {h0,h1}, z2; mov.b32 u1, {h1,h1}; mul.bf16x2 v2, v2, u1;\n" \
    "mov.b32 {h0,h1}, z2; mov.b32 u1, {h1,h1}; mul.bf16x2 v3, v3, u1;\n" \
    "mma.sync.aligned.m16n8k16.row.col.f32.bf16.bf16.f32 {%100,%101,%102,%103}, {a0,a1,a2,a3}, {v2,v3}, {%100,%101,%102,%103};\n" \
    "mma.sync.aligned.m16n8k8.row.col.f32.bf16.bf16.f32 {z4,z5,z6,z7}, {%167,%168}, {ef}, {fz,fz,fz,fz};\n" \
    "st.volatile.shared.u32 [%179], %160;\n" \
    "@pr ld.shared.v4.u32 {v0,v1,v2,v3}, [na0+0];\n" \
    "tanh.approx.f32 t0, z4; fma.rn.f32 z1, z1, t2, z1;\n" \
    "mov.b32 {h0,h1}, z1; mov.b32 u1, {h1,h1}; mul.bf16x2 v4, v4, u1;\n" \
    "mov.b32 {h0,h1}, z1; mov.b32 u1, {h1,h1}; mul.bf16x2 v5, v5, u1;\n" \
    "mma.sync.aligned.m16n8k16.row.col.f32.bf16.bf16.f32 {%104,%105,%106,%107}, {a0,a1,a2,a3}, {v4,v5}, {%104,%105,%106,%107};\n" \
    "tanh.approx.f32 t1, z6; fma.rn.f32 z3, z3, t3, z3;\n" \
    "mov.b32 {h0,h1}, z3; mov.b32 u1, {h1,h1}; mul.bf16x2 v6, v6, u1;\n" \
    "mov.b32 {h0,h1}, z3; mov.b32 u1, {h1,h1}; mul.bf16x2 v7, v7, u1;\n" \
    "mma.sync.aligned.m16n8k16.row.col.f32.bf16.bf16.f32 {%108,%109,%110,%111}, {a0,a1,a2,a3}, {v6,v7}, {%108,%109,%110,%111};\n" \
    "@pr ld.shared.v4.u32 {v4,v5,v6,v7}, [na0+128];\n" \
    "tanh.approx.f32 t2, z5; fma.rn.f32 z4, z4, t0, z4;\n" \
    "mov.b32 {h0,h1}, z4; mov.b32 u1, {h1,h1}; mul.bf16x2 v8, v8, u1;\n" \
    "mov.b32 {h0,h1}, z4; mov.b32 u1, {h1,h1}; mul.bf16x2 v9, v9, u1;\n" \
    "mma.sync.aligned.m16n8k16.row.col.f32.bf16.bf16.f32 {%112,%113,%114,%115}, {a0,a1,a2,a3}, {v8,v9}, {%112,%113,%114,%115};\n" \
    "tanh.approx.f32 t3, z7; fma.rn.f32 z6, z6, t1, z6;\n" \
    "mov.b32 {h0,h1}, z6; mov.b32 u1, {h1,h1}; mul.bf16x2 v10, v10, u1;\n" \
    "mov.b32 {h0,h1}, z6; mov.b32 u1, {h1,h1}; mul.bf16x2 v11, v11, u1;\n" \
    "mma.sync.aligned.m16n8k16.row.col.f32.bf16.bf16.f32 {%116,%117,%118,%119}, {a0,a1,a2,a3}, {v10,v11}, {%116,%117,%118,%119};\n" \
    "mma.sync.aligned.m16n8k8.row.col.f32.bf16.bf16.f32 {z0,z1,z2,z3}, {%161,%162}, {rx}, {fz,fz,fz,fz};\n" \
    "mma.sync.aligned.m16n8k8.row.col.f32.bf16.bf16.f32 {y0,y1,y2,y3}, {%169,%170}, {ry}, {fz,fz,fz,fz};\n" \
    "and.b32 u2, ey, %173; setp.ne.u32 p0, u2, 0; and.b32 u2, ey, %174; setp.ne.u32 p1, u2, 0;\n" \
    "and.b32 u2, ex, 6;\n" \
    "setp.eq.and.u32 q0, u2, 2, pr;\n" \
    "setp.eq.and.u32 q1, u2, 4, pr;\n" \
    "setp.eq.and.u32 q2, u2, 6, pr;\n" \
    "ld.shared.v4.u32 {e0,e1,ex,e3}, [%160+16];\n" \
    "@pr ld.shared.v4.u32 {v8,v9,v10,v11}, [na0+512];\n" \
    "tanh.approx.f32 t0, z0; fma.rn.f32 z5, z5, t2, z5;\n" \
    "mov.b32 {h0,h1}, z5; mov.b32 u1, {h1,h1}; mul.bf16x2 v12, v12, u1;\n" \
    "mov.b32 {h0,h1}, z5; mov.b32 u1, {h1,h1}; mul.bf16x2 v13, v13, u1;\n" \
    "mma.sync.aligned.m16n8k16.row.col.f32.bf16.bf16.f32 {%120,%121,%122,%123}, {a0,a1,a2,a3}, {v12,v13}, {%120,%121,%122,%123};\n" \
    "tanh.approx.f32 t1, z2; fma.rn.f32 z7, z7, t3, z7;\n" \
    "mov.b32 {h0,h1}, z7; mov.b32 u1, {h1,h1}; mul.bf16x2 v14, v14, u1;\n" \
    "mov.b32 {h0,h1}, z7; mov.b32 u1, {h1,h1}; mul.bf16x2 v15, v15, u1;\n" \
    "mma.sync.aligned.m16n8k16.row.col.f32.bf16.bf16.f32 {%124,%125,%126,%127}, {a0,a1,a2,a3}, {v14,v15}, {%124,%125,%126,%127};\n" \
    "cvt.rn.bf16x2.f32 b0, y2, y0; cvt.rn.bf16x2.f32 b1, y3, y1;\n" \
    "selp.b32 a0, b0, 0, p0; selp.b32 a1, b0, 0, p1; selp.b32 a2, b1, 0, p0; selp.b32 a3, b1, 0, p1;\n" \
    "@q0 bra.uni S0;\n" \
    "@q1 bra.uni S1;\n" \
    "@!q2 bra.uni SLOW;\n" \
    "bra.uni S2;\n" \
    "SLOW:\n" \
    "ld.shared.v2.u32 {gx,gy}, [%160+8];\n" \
    "and.b32 u2, gx, 1; and.b32 gx, gx, 6; setp.eq.u32 q0, gx, 0;\n" \
    "@q0 bra.uni DONE;\n" \
    "mov.b32 cnt, 0;\n" \
    "XW:\n" \
    "mbarrier.try_wait.parity.shared::cta.b64 pr, [gy], u2;\n" \
    "add.u32 cnt, cnt, 1; setp.lt.and.u32 q0, cnt, 1048576, !pr;\n" \
    "@q0 bra.uni XW;\n" \
    "ld.shared.v4.u32 {v0,v1,v2,v3}, [na0+0];\n" \
    "ld.shared.v4.u32 {v4,v5,v6,v7}, [na0+128];\n" \
    "ld.shared.v4.u32 {v8,v9,v10,v11}, [na0+512];\n" \
    "setp.eq.u32 q0, gx, 2; setp.eq.u32 q1, gx, 4;\n" \
    "@q0 bra.uni S0;\n" \
    "@q1 bra.uni S1;\n" \
    "bra.uni S2;\n" \
    "DONE:\n" \
    "}\n" \
    ""
#define MAIN_LOOP_ACC(A) \
    "+f"(A[0][0]), "+f"(A[0][1]), "+f"(A[0][2]), "+f"(A[0][3]), "+f"(A[1][0]), "+f"(A[1][1]), "+f"(A[1][2]), "+f"(A[1][3]), \
    "+f"(A[2][0]), "+f"(A[2][1]), "+f"(A[2][2]), "+f"(A[2][3]), "+f"(A[3][0]), "+f"(A[3][1]), "+f"(A[3][2]), "+f"(A[3][3]), \
    "+f"(A[4][0]), "+f"(A[4][1]), "+f"(A[4][2]), "+f"(A[4][3]), "+f"(A[5][0]), "+f"(A[5][1]), "+f"(A[5][2]), "+f"(A[5][3]), \
    "+f"(A[6][0]), "+f"(A[6][1]), "+f"(A[6][2]), "+f"(A[6][3]), "+f"(A[7][0]), "+f"(A[7][1]), "+f"(A[7][2]), "+f"(A[7][3]), \
    "+f"(A[8][0]), "+f"(A[8][1]), "+f"(A[8][2]), "+f"(A[8][3]), "+f"(A[9][0]), "+f"(A[9][1]), "+f"(A[9][2]), "+f"(A[9][3]), \
    "+f"(A[10][0]), "+f"(A[10][1]), "+f"(A[10][2]), "+f"(A[10][3]), "+f"(A[11][0]), "+f"(A[11][1]), "+f"(A[11][2]), "+f"(A[11][3]), \
    "+f"(A[12][0]), "+f"(A[12][1]), "+f"(A[12][2]), "+f"(A[12][3]), "+f"(A[13][0]), "+f"(A[13][1]), "+f"(A[13][2]), "+f"(A[13][3]), \
    "+f"(A[14][0]), "+f"(A[14][1]), "+f"(A[14][2]), "+f"(A[14][3]), "+f"(A[15][0]), "+f"(A[15][1]), "+f"(A[15][2]), "+f"(A[15][3]), \
    "+f"(A[16][0]), "+f"(A[16][1]), "+f"(A[16][2]), "+f"(A[16][3]), "+f"(A[17][0]), "+f"(A[17][1]), "+f"(A[17][2]), "+f"(A[17][3]), \
    "+f"(A[18][0]), "+f"(A[18][1]), "+f"(A[18][2]), "+f"(A[18][3]), "+f"(A[19][0]), "+f"(A[19][1]), "+f"(A[19][2]), "+f"(A[19][3]), \
    "+f"(A[20][0]), "+f"(A[20][1]), "+f"(A[20][2]), "+f"(A[20][3]), "+f"(A[21][0]), "+f"(A[21][1]), "+f"(A[21][2]), "+f"(A[21][3]), \
    "+f"(A[22][0]), "+f"(A[22][1]), "+f"(A[22][2]), "+f"(A[22][3]), "+f"(A[23][0]), "+f"(A[23][1]), "+f"(A[23][2]), "+f"(A[23][3]), \
    "+f"(A[24][0]), "+f"(A[24][1]), "+f"(A[24][2]), "+f"(A[24][3]), "+f"(A[25][0]), "+f"(A[25][1]), "+f"(A[25][2]), "+f"(A[25][3]), \
    "+f"(A[26][0]), "+f"(A[26][1]), "+f"(A[26][2]), "+f"(A[26][3]), "+f"(A[27][0]), "+f"(A[27][1]), "+f"(A[27][2]), "+f"(A[27][3]), \
    "+f"(A[28][0]), "+f"(A[28][1]), "+f"(A[28][2]), "+f"(A[28][3]), "+f"(A[29][0]), "+f"(A[29][1]), "+f"(A[29][2]), "+f"(A[29][3]), \
    "+f"(A[30][0]), "+f"(A[30][1]), "+f"(A[30][2]), "+f"(A[30][3]), "+f"(A[31][0]), "+f"(A[31][1]), "+f"(A[31][2]), "+f"(A[31][3]), \
    "+f"(A[32][0]), "+f"(A[32][1]), "+f"(A[32][2]), "+f"(A[32][3]), "+f"(A[33][0]), "+f"(A[33][1]), "+f"(A[33][2]), "+f"(A[33][3]), \
    "+f"(A[34][0]), "+f"(A[34][1]), "+f"(A[34][2]), "+f"(A[34][3]), "+f"(A[35][0]), "+f"(A[35][1]), "+f"(A[35][2]), "+f"(A[35][3]), \
    "+f"(A[36][0]), "+f"(A[36][1]), "+f"(A[36][2]), "+f"(A[36][3]), "+f"(A[37][0]), "+f"(A[37][1]), "+f"(A[37][2]), "+f"(A[37][3]), \
    "+f"(A[38][0]), "+f"(A[38][1]), "+f"(A[38][2]), "+f"(A[38][3]), "+f"(A[39][0]), "+f"(A[39][1]), "+f"(A[39][2]), "+f"(A[39][3])
#define PRODUCER_PTX \
    "{\n" \
    ".reg .b32 r<4>, d, b, c, t, w; .reg .pred p;\n" \
    "TOP:\n" \
    "ld.shared.v4.u32 {r0,r1,r2,r3}, [%0+%17];\n" \
    "mul.hi.u32 t, r2, %10;\n" \
    "G0:\n" \
    "mov.u32 c, %%clock; ld.volatile.shared.u32 w, [%9]; sub.s32 c, c, %11; sub.s32 c, c, t;\n" \
    "setp.lt.s32 p, c, 0; setp.lt.or.u32 p, w, %0, p;\n" \
    "@p bra.uni W0;\n" \
    "add.u32 b, %3, 0;\n" \
    "mbarrier.arrive.expect_tx.shared::cta.b64 _, [b], %13;\n" \
    "add.u32 d, %2, 0*%16+1024;\n" \
    "cp.async.bulk.tensor.2d.shared::cluster.global.tile.mbarrier::complete_tx::bytes [d], [%4, {%5, r0}], [b];\n" \
    "add.u32 d, %2, 1*%16+1024;\n" \
    "cp.async.bulk.tensor.2d.shared::cluster.global.tile.mbarrier::complete_tx::bytes [d], [%4, {%6, r1}], [b];\n" \
    "add.u32 d, %2, 2*%16+1024;\n" \
    "cp.async.bulk.tensor.2d.shared::cluster.global.tile.mbarrier::complete_tx::bytes [d], [%4, {%7, r2}], [b];\n" \
    "add.u32 d, %2, 3*%16+1024;\n" \
    "cp.async.bulk.tensor.2d.shared::cluster.global.tile.mbarrier::complete_tx::bytes [d], [%4, {%8, r3}], [b];\n" \
    "add.u32 %0, %0, 16;\n" \
    "ld.shared.v4.u32 {r0,r1,r2,r3}, [%0+%17];\n" \
    "mul.hi.u32 t, r2, %10;\n" \
    "G1:\n" \
    "mov.u32 c, %%clock; ld.volatile.shared.u32 w, [%9]; sub.s32 c, c, %11; sub.s32 c, c, t;\n" \
    "setp.lt.s32 p, c, 0; setp.lt.or.u32 p, w, %0, p;\n" \
    "@p bra.uni W1;\n" \
    "add.u32 b, %3, 8;\n" \
    "mbarrier.arrive.expect_tx.shared::cta.b64 _, [b], %13;\n" \
    "add.u32 d, %2, 0*%16+2048;\n" \
    "cp.async.bulk.tensor.2d.shared::cluster.global.tile.mbarrier::complete_tx::bytes [d], [%4, {%5, r0}], [b];\n" \
    "add.u32 d, %2, 1*%16+2048;\n" \
    "cp.async.bulk.tensor.2d.shared::cluster.global.tile.mbarrier::complete_tx::bytes [d], [%4, {%6, r1}], [b];\n" \
    "add.u32 d, %2, 2*%16+2048;\n" \
    "cp.async.bulk.tensor.2d.shared::cluster.global.tile.mbarrier::complete_tx::bytes [d], [%4, {%7, r2}], [b];\n" \
    "add.u32 d, %2, 3*%16+2048;\n" \
    "cp.async.bulk.tensor.2d.shared::cluster.global.tile.mbarrier::complete_tx::bytes [d], [%4, {%8, r3}], [b];\n" \
    "add.u32 %0, %0, 16;\n" \
    "ld.shared.v4.u32 {r0,r1,r2,r3}, [%0+%17];\n" \
    "mul.hi.u32 t, r2, %10;\n" \
    "G2:\n" \
    "mov.u32 c, %%clock; ld.volatile.shared.u32 w, [%9]; sub.s32 c, c, %11; sub.s32 c, c, t;\n" \
    "setp.lt.s32 p, c, 0; setp.lt.or.u32 p, w, %0, p;\n" \
    "@p bra.uni W2;\n" \
    "add.u32 b, %3, 16;\n" \
    "mbarrier.arrive.expect_tx.shared::cta.b64 _, [b], %13;\n" \
    "add.u32 d, %2, 0*%16+3072;\n" \
    "cp.async.bulk.tensor.2d.shared::cluster.global.tile.mbarrier::complete_tx::bytes [d], [%4, {%5, r0}], [b];\n" \
    "add.u32 d, %2, 1*%16+3072;\n" \
    "cp.async.bulk.tensor.2d.shared::cluster.global.tile.mbarrier::complete_tx::bytes [d], [%4, {%6, r1}], [b];\n" \
    "add.u32 d, %2, 2*%16+3072;\n" \
    "cp.async.bulk.tensor.2d.shared::cluster.global.tile.mbarrier::complete_tx::bytes [d], [%4, {%7, r2}], [b];\n" \
    "add.u32 d, %2, 3*%16+3072;\n" \
    "cp.async.bulk.tensor.2d.shared::cluster.global.tile.mbarrier::complete_tx::bytes [d], [%4, {%8, r3}], [b];\n" \
    "add.u32 %0, %0, 16;\n" \
    "ld.shared.v4.u32 {r0,r1,r2,r3}, [%0+%17];\n" \
    "mul.hi.u32 t, r2, %10;\n" \
    "G3:\n" \
    "mov.u32 c, %%clock; ld.volatile.shared.u32 w, [%9]; sub.s32 c, c, %11; sub.s32 c, c, t;\n" \
    "setp.lt.s32 p, c, 0; setp.lt.or.u32 p, w, %0, p;\n" \
    "@p bra.uni W3;\n" \
    "add.u32 b, %3, 24;\n" \
    "mbarrier.arrive.expect_tx.shared::cta.b64 _, [b], %13;\n" \
    "add.u32 d, %2, 0*%16+4096;\n" \
    "cp.async.bulk.tensor.2d.shared::cluster.global.tile.mbarrier::complete_tx::bytes [d], [%4, {%5, r0}], [b];\n" \
    "add.u32 d, %2, 1*%16+4096;\n" \
    "cp.async.bulk.tensor.2d.shared::cluster.global.tile.mbarrier::complete_tx::bytes [d], [%4, {%6, r1}], [b];\n" \
    "add.u32 d, %2, 2*%16+4096;\n" \
    "cp.async.bulk.tensor.2d.shared::cluster.global.tile.mbarrier::complete_tx::bytes [d], [%4, {%7, r2}], [b];\n" \
    "add.u32 d, %2, 3*%16+4096;\n" \
    "cp.async.bulk.tensor.2d.shared::cluster.global.tile.mbarrier::complete_tx::bytes [d], [%4, {%8, r3}], [b];\n" \
    "add.u32 %0, %0, 16;\n" \
    "ld.shared.v4.u32 {r0,r1,r2,r3}, [%0+%17];\n" \
    "mul.hi.u32 t, r2, %10;\n" \
    "G4:\n" \
    "mov.u32 c, %%clock; ld.volatile.shared.u32 w, [%9]; sub.s32 c, c, %11; sub.s32 c, c, t;\n" \
    "setp.lt.s32 p, c, 0; setp.lt.or.u32 p, w, %0, p;\n" \
    "@p bra.uni W4;\n" \
    "add.u32 b, %3, 32;\n" \
    "mbarrier.arrive.expect_tx.shared::cta.b64 _, [b], %13;\n" \
    "add.u32 d, %2, 0*%16+5120;\n" \
    "cp.async.bulk.tensor.2d.shared::cluster.global.tile.mbarrier::complete_tx::bytes [d], [%4, {%5, r0}], [b];\n" \
    "add.u32 d, %2, 1*%16+5120;\n" \
    "cp.async.bulk.tensor.2d.shared::cluster.global.tile.mbarrier::complete_tx::bytes [d], [%4, {%6, r1}], [b];\n" \
    "add.u32 d, %2, 2*%16+5120;\n" \
    "cp.async.bulk.tensor.2d.shared::cluster.global.tile.mbarrier::complete_tx::bytes [d], [%4, {%7, r2}], [b];\n" \
    "add.u32 d, %2, 3*%16+5120;\n" \
    "cp.async.bulk.tensor.2d.shared::cluster.global.tile.mbarrier::complete_tx::bytes [d], [%4, {%8, r3}], [b];\n" \
    "add.u32 %0, %0, 16;\n" \
    "setp.lt.u32 p, r0, %1;\n" \
    "@p bra.uni TOP;\n" \
    "mov.b32 %1, 0xffffffff; setp.ne.u32 p, %15, 0;\n" \
    "@p cp.async.bulk.prefetch.L2.global [%14], %15;\n" \
    "bra.uni TOP;\n" \
    "W0:\n" \
    "setp.ge.s32 p, c, %12;\n" \
    "nanosleep.u32 64;\n" \
    "@p bra.uni G0;\n" \
    "bra.uni END;\n" \
    "W1:\n" \
    "setp.ge.s32 p, c, %12;\n" \
    "nanosleep.u32 64;\n" \
    "@p bra.uni G1;\n" \
    "bra.uni END;\n" \
    "W2:\n" \
    "setp.ge.s32 p, c, %12;\n" \
    "nanosleep.u32 64;\n" \
    "@p bra.uni G2;\n" \
    "bra.uni END;\n" \
    "W3:\n" \
    "setp.ge.s32 p, c, %12;\n" \
    "nanosleep.u32 64;\n" \
    "@p bra.uni G3;\n" \
    "bra.uni END;\n" \
    "W4:\n" \
    "setp.ge.s32 p, c, %12;\n" \
    "nanosleep.u32 64;\n" \
    "@p bra.uni G4;\n" \
    "bra.uni END;\n" \
    "END:\n" \
    "}\n" \
    ""

__device__ __forceinline__ void wgmma_n128(float (&d)[64], const uint32_t (&a)[4], uint64_t desc, int acc) {
    asm volatile("{\n\t.reg .pred p;\n\tsetp.ne.u32 p, %69, 0;\n\t"
        "wgmma.mma_async.sync.aligned.m64n128k16.f32.bf16.bf16 {%0,%1,%2,%3,%4,%5,%6,%7,%8,%9,%10,%11,%12,%13,%14,%15,"
        "%16,%17,%18,%19,%20,%21,%22,%23,%24,%25,%26,%27,%28,%29,%30,%31,%32,%33,%34,%35,%36,%37,%38,%39,%40,%41,%42,%43,%44,%45,%46,%47,"
        "%48,%49,%50,%51,%52,%53,%54,%55,%56,%57,%58,%59,%60,%61,%62,%63}, {%64,%65,%66,%67}, %68, p, 1, 1, 1;\n\t}"
        : "+f"(d[0]), "+f"(d[1]), "+f"(d[2]), "+f"(d[3]), "+f"(d[4]), "+f"(d[5]), "+f"(d[6]), "+f"(d[7]),
          "+f"(d[8]), "+f"(d[9]), "+f"(d[10]), "+f"(d[11]), "+f"(d[12]), "+f"(d[13]), "+f"(d[14]), "+f"(d[15]),
          "+f"(d[16]), "+f"(d[17]), "+f"(d[18]), "+f"(d[19]), "+f"(d[20]), "+f"(d[21]), "+f"(d[22]), "+f"(d[23]),
          "+f"(d[24]), "+f"(d[25]), "+f"(d[26]), "+f"(d[27]), "+f"(d[28]), "+f"(d[29]), "+f"(d[30]), "+f"(d[31]),
          "+f"(d[32]), "+f"(d[33]), "+f"(d[34]), "+f"(d[35]), "+f"(d[36]), "+f"(d[37]), "+f"(d[38]), "+f"(d[39]),
          "+f"(d[40]), "+f"(d[41]), "+f"(d[42]), "+f"(d[43]), "+f"(d[44]), "+f"(d[45]), "+f"(d[46]), "+f"(d[47]),
          "+f"(d[48]), "+f"(d[49]), "+f"(d[50]), "+f"(d[51]), "+f"(d[52]), "+f"(d[53]), "+f"(d[54]), "+f"(d[55]),
          "+f"(d[56]), "+f"(d[57]), "+f"(d[58]), "+f"(d[59]), "+f"(d[60]), "+f"(d[61]), "+f"(d[62]), "+f"(d[63])
        : "r"(a[0]), "r"(a[1]), "r"(a[2]), "r"(a[3]), "l"(desc), "r"(acc));
}

#define YFP 3
#define PT0 7000
#define PDT 68
#define NSLEEP 64
#define PFA 8000
#define TAIL 0
template <int ID, int COUNT> __device__ __forceinline__ void bar_sync() { asm volatile("bar.sync %0, %1;" ::"n"(ID), "n"(COUNT) : "memory"); }
template <int ID, int COUNT> __device__ __forceinline__ void bar_arrive() { asm volatile("bar.arrive %0, %1;" ::"n"(ID), "n"(COUNT) : "memory"); }
#define REL "relaxed"
__device__ __forceinline__ void await(const uint32_t* p, uint32_t n) {
    uint32_t v;
    int guard = 0;
    do asm volatile("ld.relaxed.gpu.global.u32 %0, [%1];" : "=r"(v) : "l"(p) : "memory");
    while (__any_sync(0xffffffffu, v < n) && ++guard < (1 << 20));
}
template <int BYTES>
__device__ __forceinline__ void fill(uint32_t addr, uint4 v, int tid) {
#pragma unroll
    for (int r = 0; r < (BYTES / 16 + NT - 1) / NT; r++)
        sts128_if((r + 1) * NT <= BYTES / 16 || r * NT + tid < BYTES / 16, addr + (r * NT + tid) * 16, v);
}

template <int MODE>
__global__ void __launch_bounds__(NT, 1)
tfn_kernel(const __grid_constant__ CUtensorMap xmap, const __grid_constant__ CUtensorMap wmap, const __nv_bfloat16* __restrict__ x,
           const int* __restrict__ src, const int* __restrict__ dst,
           const uint2* __restrict__ Y, const uint2* __restrict__ ef, const __nv_bfloat16* __restrict__ w_rad,
           const __nv_bfloat16* __restrict__ cg, const __nv_bfloat16* __restrict__ w_mix,
           __nv_bfloat16* __restrict__ out, Scratch* scr, int N, int E, int slice, int npc, uint32_t npc_magic,
           uint32_t bin_magic, uint32_t pace) {
    extern __shared__ __align__(1024) uint8_t smem[];
    const int tid = threadIdx.x, lane = tid & 31, warp = __shfl_sync(0xffffffffu, tid >> 5, 0);
    const int cta = blockIdx.x;
    const uint32_t sb = (uint32_t)__cvta_generic_to_shared(smem);
    int* s_misc = reinterpret_cast<int*>(smem + SM_MISC);
    const uint32_t bar_w = sb + SM_BAR + NW * S * 8, bar_raw = bar_w + 8, bar_rec = bar_w + 16;
    ANCHOR(0);
    auto prefetch_x = [&](int chunk) {
        const int row = (chunk * NCTA + cta) * 8;
        if (row < N)
            asm volatile("cp.async.bulk.prefetch.L2.global [%0], %1;" ::"l"(x + (size_t)row * 512), "r"(min(8, N - row) * 1024));
    };

    const int e0 = cta * slice, ne = min(E - e0, slice);
    uint32_t a_d[RA], a_s[RA];
    uint32_t tag = 0;
    if (MODE & 1) {
        const int q = min(e0 / 4 + tid, (E - 1) >> 2), e = min(e0 + 4 * NT + tid, E - 1);
        const int4 d4 = __ldcs(reinterpret_cast<const int4*>(dst) + q);
        a_d[4] = __ldcs(dst + e);
        const int4 s4 = __ldcs(reinterpret_cast<const int4*>(src) + q);
        a_s[4] = __ldcs(src + e);
        a_d[0] = d4.x; a_d[1] = d4.y; a_d[2] = d4.z; a_d[3] = d4.w;
        a_s[0] = s4.x; a_s[1] = s4.y; a_s[2] = s4.z; a_s[3] = s4.w;
    }
    if (MODE == 3) asm volatile("ld.relaxed.gpu.global.u32 %0, [%1];" : "=r"(tag) : "l"(&scr->epoch) : "memory");
    auto load_raw = [&]() {
        asm volatile("fence.proxy.async.shared::cta;" ::: "memory");
        const int bytes = max((ne + 1) >> 1, 0) * 16;
        asm volatile("mbarrier.arrive.expect_tx.shared::cta.b64 _, [%0], %1;" ::"r"(bar_raw), "r"(2 * bytes) : "memory");
        if (bytes > 0) {
            asm volatile("cp.async.bulk.shared::cluster.global.mbarrier::complete_tx::bytes [%0], [%1], %2, [%3];"
                         ::"r"(sb + SM_RAWY), "l"(Y + e0), "r"(bytes), "r"(bar_raw) : "memory");
            asm volatile("cp.async.bulk.shared::cluster.global.mbarrier::complete_tx::bytes [%0], [%1], %2, [%3];"
                         ::"r"(sb + SM_RAWF), "l"(ef + e0), "r"(bytes), "r"(bar_raw) : "memory");
        }
    };
    if (elect_one()) {
#pragma unroll
        for (int i = 0; i < S; i++)
            if (warp >= NW) mbar_init(sb + SM_BAR + ((warp - NW) * S + i) * 8, 1);
        if (warp == 0) {
            mbar_init(bar_w, NW);
            mbar_init(bar_raw, 1);
            mbar_init(bar_rec, NW);
            if ((MODE & 1) && YFP == 0) load_raw();
        }
        if (warp == 1 && (MODE & 2)) {
            asm volatile("prefetch.tensormap [%0];" ::"l"(&xmap) : "memory");
            asm volatile("prefetch.tensormap [%0];" ::"l"(&wmap) : "memory");
            asm volatile("cp.async.bulk.prefetch.L2.global [%0], 1024;" ::"l"(w_rad));
            asm volatile("cp.async.bulk.prefetch.L2.global [%0], 128;" ::"l"(cg));
        }
    }
    fill<SM_DUM - SM_HIST>(sb + SM_HIST, make_uint4(0, 0, 0, 0), tid);
    if (MODE & 1) {
        const uint32_t em = EMPTY | lane << 20;
        fill<NCTA * ASTR * 4>(sb + SM_AMB, make_uint4(em, em + (1 << 18), em + (2 << 18), em + (3 << 18)), tid);
    }
    sts32_if(tid < NBIN, sb + SM_DUM + tid * 4, 0x4000);
    if (MODE & 2) {
        const uint32_t pad = RCAP << 18 | N << 4;
        fill<SM_BAR - SM_ZERO>(sb + SM_ZERO, make_uint4(0, 0, 0, 0), tid);
        fill<NG * GK * 16>(sb + SM_KSG, make_uint4(pad, pad, pad, pad), tid);
    }
    __syncthreads();
    STAMP(15);
    if (MODE & 1) {
        if (YFP == 1 && tid == 0) load_raw();
        const uint32_t z = lds32(sb + SM_KEY + lane * 4);
        uint32_t cc[RA], rk[RA];
#pragma unroll
        for (int r = 0; r < RA; r++) {
            cc[r] = (r < 4 ? 4 * tid + r : 4 * NT + tid) < ne ? __umulhi(a_d[r], npc_magic + z) : NCTA;
            rk[r] = atoms_inc(sb + SM_HIST + cc[r] * 4);
        }
        if (YFP == 2 && tid == 0) load_raw();
#pragma unroll
        for (int r = 0; r < RA; r++) {
            const uint32_t l = a_d[r] - cc[r] * npc;
            a_s[r] = (l < 16 ? (l & 7) | 16 : l & 15) << 25 | ((a_s[r] * (bin_magic + z)) & ((NBIN - 1) << 18)) | a_s[r] * (16 + z) |
                     1u << (l < 16 ? l >> 3 : (l >> 4) - 1);
            sts32_if(true, sb + SM_AMB + (cc[r] * ASTR + min(rk[r], MBE)) * 4, a_s[r]);
        }
        tag = (tag & 1) + 1;
        const uint32_t tg = tag << 30;
        STAMP(1);
        __syncthreads();
        auto send = [&](uint32_t* gp, uint4 v) {
            asm volatile("st.relaxed.gpu.global.v4.u32 [%0], {%1,%2,%3,%4};"
                         ::"l"(gp), "r"(v.x | tg), "r"(v.y | tg), "r"(v.z | tg), "r"(v.w | tg) : "memory");
        };
        if (YFP == 3 && tid == NT - 64) load_raw();
        uint32_t h = 0, off = 0;
        if (warp < 5) {
            h = lds32(sb + SM_HIST + min(tid, NCTA + 1) * 4);
            const bool real = tid < NCTA;
            const uint32_t inc = warp_incl_scan(real ? h : 0, lane);
            off = __shfl_sync(0xffffffffu, atoms_add(sb + SM_HIST + 109 * 4 + lane * 4, lane == 31 ? inc : 0), 31) + inc - h;
            sts32_if(tid <= NCTA, sb + SM_AOFF + tid * 4, real ? off : max(ne, 0));
        }
#pragma unroll
        for (int r = 0; r < 3; r++) {
            if (r == 2 && warp != 15) break;
            const uint32_t i = r < 2 ? r * NT + tid : 2 * NT + lane, c = i >> 3;
            send(scr->mb + c * MBW + cta * 32 + (i & 7) * 4, lds128(sb + SM_AMB + c * (ASTR * 4) + (i & 7) * 16));
        }
        if (tid < NCTA) {
            const uint4 v0 = lds128(sb + SM_AMB + tid * (ASTR * 4) + 128);
            uint4 v1 = lds128(sb + SM_AMB + tid * (ASTR * 4) + 144);
            v1.w = h << 12 | off;
            send(scr->mb + tid * MBW + MB1 + cta * 8, v0);
            send(scr->mb + tid * MBW + MB1 + cta * 8 + 4, v1);
        }
        STAMP(2);
        __syncthreads();
        if (MODE == 3 && tid == NT - 1) asm volatile("red.relaxed.gpu.global.add.u32 [%0], 1;" ::"l"(scr->sent + (tag & 1)) : "memory");
        uint32_t ap[2 * RA];
#pragma unroll
        for (int r = 0; r < RA; r++) ap[r] = rk[r] + lds32(sb + SM_AOFF + cc[r] * 4);
        if (max(max(max(rk[0], rk[1]), max(rk[2], rk[3])), rk[4]) >= MBE) {
#pragma unroll
            for (int r = 0; r < RA; r++)
                if (rk[r] >= MBE && cc[r] < NCTA) {
                    __stcg(scr->ss + cta * SLICE + ap[r], a_s[r]);
                    __threadfence();
                }
        }
        if (warp >= NW) {
            asm volatile("st.shared.v2.u32 [%0], {%1, %2};" ::"r"(sb + SM_AP + (tid - NH) * 8), "r"(ap[0] | ap[1] << 16), "r"(ap[2] | ap[3] << 16) : "memory");
            sts32_if(true, sb + SM_AP + NH * 8 + (tid - NH) * 4, ap[4]);
            bar_arrive<1, NT>();
        } else {
            bar_sync<1, NT>();
            const uint2 u = lds64(sb + SM_AP + tid * 8);
            ap[5] = u.x & 0xffff; ap[6] = u.x >> 16; ap[7] = u.y & 0xffff; ap[8] = u.y >> 16;
            ap[9] = lds32(sb + SM_AP + NH * 8 + tid * 4);
            const bool sw = lane & 4;
            mbar_wait(bar_raw, 0);
            STAMP(10);
#pragma unroll
            for (int hh = 0; hh < 2; hh++) {
                const uint32_t a = sb + SM_RAWY + (hh * NH + tid) * 32 + (lane & 4) * 4, b = sb + SM_RAWY + (4 * NT + hh * NH + tid) * 8;
                const uint4 y0 = lds128(a), f0 = lds128(a + SLICE * 8), y1 = lds128(a ^ 16), f1 = lds128((a ^ 16) + SLICE * 8);
                const uint2 y2 = lds64(b), f2 = lds64(b + SLICE * 8);
                const uint32_t* q = ap + hh * RA;
                sts128_if(true, sb + SM_AREC + (sw ? q[2] : q[0]) * 16, make_uint4(f0.x, y0.x, f0.y, y0.y));
                sts128_if(true, sb + SM_AREC + (sw ? q[3] : q[1]) * 16, make_uint4(f0.z, y0.z, f0.w, y0.w));
                sts128_if(true, sb + SM_AREC + (sw ? q[0] : q[2]) * 16, make_uint4(f1.x, y1.x, f1.y, y1.y));
                sts128_if(true, sb + SM_AREC + (sw ? q[1] : q[3]) * 16, make_uint4(f1.z, y1.z, f1.w, y1.w));
                sts128_if(true, sb + SM_AREC + q[4] * 16, make_uint4(f2.x, y2.x, f2.y, y2.y));
            }
            asm volatile("fence.proxy.async.shared::cta;" ::: "memory");
            bar_sync<7, NH>();
            STAMP(25);
            if (warp == 0 && elect_one()) {
                if (ne > 0)
                    asm volatile("cp.async.bulk.global.shared::cta.bulk_group [%0], [%1], %2;"
                                 ::"l"(scr->rec + cta * SLICE), "r"(sb + SM_AREC), "r"(ne * 16) : "memory");
                asm volatile("cp.async.bulk.commit_group;" ::: "memory");
                asm volatile("cp.async.bulk.wait_group 0;" ::: "memory");
                STAMP(26);
                if (MODE == 3) asm volatile("red." REL ".gpu.global.add.u32 [%0], 1;" ::"l"(scr->sent2 + (tag & 1)) : "memory");
            }
            __syncwarp();
            STAMP(3);
        }
    } else {
        tag = 1;
    }
    if (!(MODE & 2)) return;
    const int wl = warp & (NW - 1);
    const uint32_t ring = sb + SM_RING + wl * (S * 1024);
    const uint32_t bars = sb + SM_BAR + wl * (S * 8);
    const uint32_t pos = bar_w + 32 + wl * 4;

    if (warp >= NW) {
        uint32_t ss[RL + 8], rk[RL + 7];
        const uint32_t sl = wl + 8 * lane;
        const uint32_t* mp = scr->mb + cta * MBW + wl * 32 + lane;
        const uint4* mq = reinterpret_cast<const uint4*>(scr->mb + cta * MBW + MB1) + min(sl, NCTA - 1) * 2;
        const uint32_t tg = tag << 30, empty = EMPTY | lane << 18;
        int guard = 0;
        uint32_t bad;
        if (wl == 0) {
            if (MODE == 3) await(scr->sent + (tag & 1), NCTA);
            sts32_if(true, sb + SM_MISC + 4, clock32() + PT0);
        }
        if (MODE == 3) bar_sync<3, NH>();
        STAMPT(11, NH);
        do {
#pragma unroll
            for (int r = 0; r < RL; r++) asm volatile("ld.relaxed.gpu.global.u32 %0, [%1];" : "=r"(ss[r]) : "l"(mp + r * NH) : "memory");
            const uint4 v0 = ldg128_relaxed(mq), v1 = ldg128_relaxed(mq + 1);
            ss[RL] = v0.x; ss[RL + 1] = v0.y; ss[RL + 2] = v0.z; ss[RL + 3] = v0.w;
            ss[RL + 4] = v1.x; ss[RL + 5] = v1.y; ss[RL + 6] = v1.z; ss[RL + 7] = v1.w;
            bad = 0;
#pragma unroll
            for (int r = 0; r < RL + 8; r++) bad |= ss[r] ^ tg;
        } while (__any_sync(0xffffffffu, bad >> 30) && ++guard < (1 << 20));
        STAMPT(4, NH);
        if (wl + 8 * (RL - 1) >= NCTA) ss[RL - 1] = empty;
#pragma unroll
        for (int r = 0; r < RL; r++) rk[r] = atoms_inc(sb + SM_BIN + (ss[r] >> 16 & 0x3ffc));
        const uint32_t cnt = sl < NCTA ? ss[RL + 7] >> 12 & 0xfff : 0;
        const bool late = __any_sync(0xffffffffu, cnt > 32);
        if (late) {
#pragma unroll
            for (int r = RL; r < RL + 7; r++) {
                if (r - RL + 32 >= cnt) ss[r] = empty;
                rk[r] = atoms_inc(sb + SM_BIN + (ss[r] >> 16 & 0x3ffc));
            }
            sts32_if(cnt > MBE, sb + SM_MISC + 8, 1);
        }
        STAMPT(5, NH);
        bar_sync<3, NH>();
        uint32_t dof;
        {
            const uint32_t a = sb + SM_BIN + wl * (NBIN * 12) + lane * 16;
            uint4 u[3];
            uint32_t sum[3];
#pragma unroll
            for (int j = 0; j < 3; j++) {
                u[j] = lds128(a + j * (NBIN * 4));
                sum[j] = u[j].x + u[j].y + u[j].z + u[j].w;
            }
            uint32_t i01 = sum[0] | sum[1] << 16, i2 = sum[2] | min(cnt, MBE) << 16;
#pragma unroll
            for (int o = 1; o < 32; o <<= 1) {
                const uint32_t v01 = __shfl_up_sync(0xffffffffu, i01, o), v2 = __shfl_up_sync(0xffffffffu, i2, o);
                if (lane >= o) { i01 += v01; i2 += v2; }
            }
            dof = atoms_add(sb + SM_MISC - 124 + lane * 4, lane == 31 ? i2 >> 16 : 0);
            const uint32_t inc[3] = {i01 & 0xffff, i01 >> 16, i2 & 0xffff};
#pragma unroll
            for (int j = 0; j < 3; j++) {
                const uint32_t p = (3 * wl + j) * (GK * 4) + inc[j] - sum[j];
                sts128_if(true, a + j * (NBIN * 4), make_uint4(p, p + u[j].x, p + u[j].x + u[j].y, p + u[j].x + u[j].y + u[j].z));
                sts32_if(lane == 31, sb + SM_KEY + (3 * wl + j) * 4, (inc[j] + 3) >> 2 << 5 | (3 * wl + j));
            }
            dof = __shfl_sync(0xffffffffu, dof, 31) + (i2 >> 16) - min(cnt, MBE);
            sts32_if(sl < NCTA, sb + SM_SEG + sl * 4, ss[RL + 7] & 0xffffff);
            sts32_if(sl < NCTA, sb + SM_DOFF + sl * 4, dof);
        }
        STAMPT(12, NH);
        bar_arrive<4, NT>();
        bar_sync<3, NH>();
        const uint32_t key = lds32(sb + SM_KEY + lane * 4), nrec = s_misc[0];
        uint4 ko[4];
#pragma unroll
        for (int j = 0; j < 4; j++) ko[j] = lds128(sb + SM_KEY + (lane & 16) * 4 + j * 16);
#pragma unroll
        for (int r = 0; r < RL; r++) rk[r] += lds32(sb + SM_BIN + (ss[r] >> 16 & 0x3ffc));
        int rank = 0;
#pragma unroll
        for (int j = 0; j < 4; j++) rank += (ko[j].x > key) + (ko[j].y > key) + (ko[j].z > key) + (ko[j].w > key);
        const int to = lane < 16 ? min(rank, 15 - rank) : lane < NG ? (rank < 4 ? rank : 11 - rank) : NW;
        const unsigned mine = __ballot_sync(0xffffffffu, to == wl);
        const uint32_t gq[3] = {(uint32_t)__ffs(mine) - 1, 31u - __clz(mine & 0xffffu), 31u - __clz(mine)};
        const uint32_t cap = __reduce_add_sync(0xffffffffu, min(key >> 5, GK)) > KCAP ? KCAP / NG : GK, nk = min(key >> 5, cap);
        const uint32_t lim = __any_sync(0xffffffffu, (key >> 5) > cap || nrec > RCAP) ? 0 : 0x8000;
        const uint32_t lb = __reduce_add_sync(0xffffffffu, to < wl ? nk : 0u) + wl;
        uint4 pf3[3];
#pragma unroll
        for (int j = 0; j < 3; j++) pf3[j] = lds128(sb + SM_BIN + gq[j] * (NBIN * 4) + lane * 16);
#pragma unroll
        for (int r = 0; r < RL; r++)
            sts32_if(rk[r] < lim, sb + SM_KSG + rk[r] * 4, (__shfl_sync(0xffffffffu, dof, r) + lane) << 18 | (ss[r] & 0x3ffffu));
        uint32_t n[3];
        {
            int c[3][5];
#pragma unroll
            for (int j = 0; j < 3; j++) {
                n[j] = __shfl_sync(0xffffffffu, nk, gq[j]);
                const uint32_t o = 1 - gq[j] * (GK * 4);
                c[j][0] = min((pf3[j].x + o) >> 2, n[j]);
                c[j][1] = min((pf3[j].y + o) >> 2, n[j]);
                c[j][2] = min((pf3[j].z + o) >> 2, n[j]);
                c[j][3] = min((pf3[j].w + o) >> 2, n[j]);
                c[j][4] = __shfl_down_sync(0xffffffffu, c[j][0], 1);
                if (lane == 31) c[j][4] = n[j];
            }
#pragma unroll
            for (int j = 0; j < 3; j++) {
                int d[4];
#pragma unroll
                for (int b = 0; b < 4; b++) d[b] = (j == 0 ? c[1][b] + c[2][b] : j == 1 ? c[0][b + 1] + c[2][b] : c[0][b + 1] + c[1][b + 1]);
                sts128_if(true, sb + SM_T2 + (wl * 3 + j) * (NBIN * 4) + lane * 16, make_uint4(d[0], d[1], d[2], d[3]));
            }
        }
        const uint32_t len = n[0] + n[1] + n[2], le = lb + len;
        sts32_if(lane == 0, sb + SM_LIST + le * 16 + 12, bars);
        sts128_if(lane == 0, sb + SM_SRC + le * 16, make_uint4(0, 0, 0x40000000u, 0));
        sts32_if(lane == 0, pos, sb + SM_LIST + lb * 16);
        sts32_if(lane == 0, sb + SM_MISC + 32 + wl * 4, (wl * S + len - ((len * 13108) >> 16) * S) * 64);
        sts32_if(lane == 0, sb + SM_MISC + 64 + wl * 8, lb | len << 16);
        sts32_if(lane == 0, sb + SM_MISC + 68 + wl * 8, gq[0] | gq[1] << 5 | gq[2] << 10);
        if (late) {
#pragma unroll
            for (int r = RL; r < RL + 7; r++) {
                rk[r] += lds32(sb + SM_BIN + (ss[r] >> 16 & 0x3ffc));
                sts32_if(rk[r] < lim, sb + SM_KSG + rk[r] * 4, (dof + 32 + r - RL) << 18 | (ss[r] & 0x3ffffu));
            }
        }
        if (lim == 0) {
#pragma unroll
            for (int r = 0; r < RL + 7; r++) {
                if (r >= RL && !late) break;
                const uint32_t rnk = r < RL ? lane : 32 + r - RL, from = r < RL ? r : lane;
                const uint32_t ri = __shfl_sync(0xffffffffu, dof, from) + rnk, gi = __shfl_sync(0xffffffffu, ss[RL + 7] & 0xfff, from) + rnk;
                const bool fits = rk[r] - (ss[r] >> 25 & 31) * (GK * 4) < cap * 4;
                if (rk[r] < 0x8000) {
                    sts32_if(fits, sb + SM_KSG + rk[r] * 4, min(ri, RCAP) << 18 | (ss[r] & 0x3ffffu));
                    if (!fits || ri >= RCAP) __stcg(scr->exc + cta * MBW + atomicAdd(s_misc + 3, 1), make_uint2(ss[r], (wl + 8 * from) * SLICE + gi));
                }
            }
        }
        STAMPT(13, NH);
        bar_sync<3, NH>();
#pragma unroll 1
        for (uint32_t i0 = 0; i0 < len; i0 += 96) {
            uint4 w[3];
            uint32_t k[3], ja[3];
#pragma unroll
            for (int j = 0; j < 3; j++) {
                const uint32_t i = min(i0 + j * 32 + lane, len - 1);
                ja[j] = (i >= n[0]) + (i >= n[0] + n[1]);
                k[j] = i - (ja[j] == 0 ? 0 : ja[j] == 1 ? n[0] : n[0] + n[1]);
                w[j] = lds128(sb + SM_KSG + ((ja[j] == 0 ? gq[0] : ja[j] == 1 ? gq[1] : gq[2]) * GK + k[j]) * 16);
            }
#pragma unroll
            for (int j = 0; j < 3; j++)
                k[j] += lds32(sb + SM_T2 + ((wl * 3 + ja[j]) * NBIN + min(((w[j].z >> 4 & 0x3fff) * bin_magic) >> 18, NBIN - 1)) * 4);
#pragma unroll
            for (int j = 0; j < 3; j++) {
                const uint32_t p = k[j], turn = (p * 13108) >> 16, slot = p - turn * S;
                sts128_if(true, sb + SM_SRC + (lb + p) * 16, make_uint4(w[j].x >> 1 & 0x1fff8, w[j].y >> 1 & 0x1fff8, w[j].z >> 1 & 0x1fff8, w[j].w >> 1 & 0x1fff8));
                sts128_if(true, sb + SM_LIST + (lb + p) * 16,
                          make_uint4((w[j].x >> 14 & 0xfff0) | (w[j].x & 15) | (w[j].y << 2 & 0xfff00000u) | (w[j].y & 15) << 16,
                                     (w[j].z >> 14 & 0xfff0) | (w[j].z & 15) | (w[j].w << 2 & 0xfff00000u) | (w[j].w & 15) << 16,

                                     (turn & 1) | (ja[j] + 1) << 1 | slot << 26, bars + slot * 8));
            }
        }
        asm volatile("fence.proxy.async.shared::cta;" ::: "memory");
        bar_arrive<2, NT>();
        bar_sync<5, NT>();
        STAMPT(6, NH);
        asm volatile("setmaxnreg.dec.sync.aligned.u32 24;");
        const uint32_t z = lds32(sb + SM_ZERO + (lane & 3) * 4);
        const uint32_t bytes = opaque(4096 + z), far = opaque(z - (pace << 22)), due0 = opaque(s_misc[1] + z);
        if (elect_one()) {
            const uint4 z0 = lds128v(sb + SM_ZERO);
            uint32_t ka = sb + SM_LIST + lb * 16 - 16 * (S - 1);
            uint32_t pf = max(wl * (NCTA * 64) + PFA - NCTA * 64, 0);
            const int row = ((wl + 2) * NCTA + cta) * 8;
            asm volatile(PRODUCER_PTX : "+r"(ka), "+r"(pf)
                : "r"(ring - 1024 + lds32v(sb + SM_ZERO)), "r"(bars), "l"(reinterpret_cast<uint64_t>(&xmap) + lds32v(sb + SM_ZERO)),
                  "r"(z0.x), "r"(z0.y), "r"(z0.z), "r"(z0.w), "r"(pos + lds32v(sb + SM_ZERO)), "r"((pace << 25) + lds32v(sb + SM_ZERO)), "r"(due0), "r"(far), "r"(bytes),
                  "l"(x + (size_t)row * 512), "r"(min(max(N - row, 0), 8) * 1024), "n"(RSTR), "n"(SM_SRC - SM_LIST + 16 * (S - 1)) : "memory");
            const uint32_t d = ring + (len - ((len * 13108) >> 16) * S) * 1024;
            STAMPT(20, NW * 32);
            for (int guard = 0; lds32v(pos) + 16 * (S - 1) < sb + SM_LIST + le * 16 && guard < (1 << 20); guard++) __nanosleep(NSLEEP);
            asm volatile("mbarrier.arrive.expect_tx.shared::cta.b64 _, [%0], 4096;" ::"r"(bar_w) : "memory");
#pragma unroll
            for (uint32_t r = 0; r < 8; r++)
                asm volatile("cp.async.bulk.tensor.5d.shared::cluster.global.tile.mbarrier::complete_tx::bytes [%0], [%1, {%2, %3, %4, %5, %6}], [%7];"
                             ::"r"(d + (r >> 1) * RSTR + (r & 1) * 512), "l"(&wmap), "r"((r >> 2) * 64), "r"((r >> 1) & 1),
                               "r"((wl >> 1) & 2), "r"(((r ^ (wl >> 1)) & 1) + (wl & 1) * 2), "r"(wl & 2), "r"(bar_w) : "memory");
            STAMPT(21, NW * 32);
        }
        return;
    }

    const int g = lane >> 2, t = lane & 3;
    uint32_t wz[4][2], wt[2];
    {
        bar_sync<4, NT>();
        const uint32_t sl = min(wl + 8 * lane, NCTA - 1);
        const uint32_t dof = lds32(sb + SM_DOFF + sl * 4), loc = lds32(sb + SM_SEG + sl * 4);
        const uint32_t nr = wl + 8 * lane < NCTA ? min(min(loc >> 12, MBE), RCAP - min(dof, RCAP)) : 0;
        asm volatile("fence.proxy.async.shared::cta;" ::: "memory");
        bar_arrive<5, NT>();
        uint32_t cd[RL], cs[RL], cn[RL];
#pragma unroll
        for (int r = 0; r < RL; r++) {
            cd[r] = __shfl_sync(0xffffffffu, nr ? sb + SM_REC + dof * 16 : sb + SM_ZERO + 64, r);
            cs[r] = __shfl_sync(0xffffffffu, (sl * SLICE + (nr ? loc & 0xfff : 0)) * 16, r);
            cn[r] = __shfl_sync(0xffffffffu, max(nr, 1) * 16, r);
        }
        const uint32_t total = __reduce_add_sync(0xffffffffu, lane < RL ? max(nr, 1) * 16 : 0);
        if (lane == 0) asm volatile("mbarrier.arrive.expect_tx.shared::cta.b64 _, [%0], %1;" ::"r"(bar_rec), "r"(total) : "memory");
        if ((warp & 6) == 2 && lane == 0) prefetch_x(warp & 1);
        if (MODE == 3 && cta == 0 && tid == 64) {
            asm volatile("st.relaxed.gpu.global.u32 [%0], %1;" ::"l"(&scr->epoch), "r"(tag) : "memory");
            scr->sent[~tag & 1] = scr->sent2[~tag & 1] = 0;
        }
        STAMP(22);
        {
            const uint32_t* wr = reinterpret_cast<const uint32_t*>(w_rad) + (t & 1) * 128;
            const uint16_t* cp = reinterpret_cast<const uint16_t*>(cg) + (t >> 1) * 32 + (t & 1) * 8 + (g & 3);
            const __nv_bfloat162 half = __floats2bfloat162_rn(0.5f, 0.5f);
#pragma unroll
            for (int j = 0; j < 4; j++) {
                uint32_t u0 = __ldg(wr + chunk_of(2 * j + (t >> 1), g)), u1 = __ldg(wr + chunk_of(2 * j + (t >> 1), g) + 64);
                const __nv_bfloat162 h0 = __hmul2(*reinterpret_cast<__nv_bfloat162*>(&u0), half);
                const __nv_bfloat162 h1 = __hmul2(*reinterpret_cast<__nv_bfloat162*>(&u1), half);
                u0 = *reinterpret_cast<const uint32_t*>(&h0);
                u1 = *reinterpret_cast<const uint32_t*>(&h1);
                wz[j][0] = __byte_perm(u0, u1, 0x5410);
                wz[j][1] = __byte_perm(u0, u1, 0x7632);
            }
            wt[0] = __ldg(cp) | ((uint32_t)__ldg(cp + 4) << 16);
            wt[1] = __ldg(cp + 16) | ((uint32_t)__ldg(cp + 20) << 16);
        }
        if (MODE == 3) {
            if (warp == 0) await(scr->sent2 + (tag & 1), NCTA);
            bar_sync<7, NH>();
        }
        STAMP(24);
        asm volatile("fence.proxy.async.global;" ::: "memory");
        if (elect_one()) {
#pragma unroll
            for (int r = 0; r < RL; r++)
                asm volatile("cp.async.bulk.shared::cluster.global.mbarrier::complete_tx::bytes [%0], [%1], %2, [%3];"
                             ::"r"(cd[r]), "l"(reinterpret_cast<const uint8_t*>(scr->rec) + cs[r]), "r"(cn[r]), "r"(bar_rec) : "memory");
        }
        STAMP(23);
        if (tid == 0 && cta < 128) asm volatile("cp.async.bulk.prefetch.L2.global [%0], 256;" ::"l"(w_mix + cta * 128));
        asm volatile("setmaxnreg.inc.sync.aligned.u32 232;" ::: "memory");
        bar_sync<2, NT>();
        STAMP(14);
    }

    float acc[40][4];
    const uint32_t z = lds32(sb + SM_ZERO + t * 4);
    const float zero = __uint_as_float(z);
#pragma unroll
    for (int j = 0; j < 40; j++) acc[j][0] = acc[j][1] = acc[j][2] = acc[j][3] = zero;
    const bool bact = (g & 1) == (t >> 1);
    mbar_wait(bar_rec, 0);
    STAMP(9);
    {
        auto keep = [&](uint32_t v) { return __shfl_sync(0xffffffffu, v + z, lane); };
        const uint32_t va0 = ring + t * RSTR + (g & 2) * 128 + (g & 1) * 16 + ((((g >> 1) & 2) ^ ((((g >> 1) & 1) + t) & 3)) << 5);
        uint32_t lp = keep(sb + SM_LIST + (lds32(sb + SM_MISC + 64 + wl * 8) & 0xffff) * 16);
        asm volatile(MAIN_LOOP_PTX : MAIN_LOOP_ACC(acc), "+r"(lp)
            : "r"(wz[0][0]), "r"(wz[0][1]), "r"(wz[1][0]), "r"(wz[1][1]), "r"(wz[2][0]), "r"(wz[2][1]), "r"(wz[3][0]), "r"(wz[3][1]),
              "r"(wt[0]), "r"(wt[1]), "r"(keep(va0)), "r"(keep(va0 ^ 32)), "r"(keep(0x10000u << (g >> 2))),
              "r"(keep(0x40000u << (g >> 2))), "r"(keep(bact ? (t & 1) * 8 : SM_ZERO - SM_REC)), "r"(keep(bact ? 0xfff0u : 0u)),
              "r"(keep(0x1010u + (g >> 1) * 0x22 + t * 0x2200)),
              "r"(sb), "r"(keep(pos)), "n"(SM_REC)
            : "memory");
    }
    STAMP(7);
    const uint32_t grp = lds32(sb + SM_MISC + 68 + wl * 8);

    if (s_misc[2] | s_misc[3]) {
        const int* seg = reinterpret_cast<const int*>(smem + SM_SEG);
        __threadfence();
        for (int sgi = 0; sgi <= NCTA; sgi++) {
            sgi += __reduce_min_sync(0xffffffffu, sgi + lane >= NCTA || (seg[min(sgi + lane, NCTA - 1)] >> 12) > MBE ? lane : 31);
            int2 sg = make_int2(0, s_misc[3]);
            if (sgi < NCTA) sg = make_int2(sgi * SLICE + (seg[sgi] & 0xfff), seg[sgi] >> 12);
            for (int i0 = sgi < NCTA ? MBE : 0; i0 < sg.y; i0 += 32) {
                uint32_t w = 0xffffffffu;
                int gi = 0;
                if (i0 + lane < sg.y) {
                    if (sgi < NCTA) {
                        gi = sg.x + i0 + lane;
                        w = __ldcg(scr->ss + gi);
                    } else {
                        const uint2 u = __ldcg(scr->exc + cta * MBW + i0 + lane);
                        w = u.x;
                        gi = u.y;
                    }
                }
                const uint32_t gw = w >> 25 & 31;
                const uint32_t ja = gw == (grp & 31) ? 0 : gw == (grp >> 5 & 31) ? 1 : gw == grp >> 10 ? 2 : 3;
                w = (w >> 4 & 0x3fffu) | (ja * 4 + __ffs(w & 15) - 1) << 14;
                uint4 rc = make_uint4(0, 0, 0, 0);
                if (ja < 3) {
                    rc = ldg128_relaxed(scr->rec + gi);
                }
                unsigned mask = __ballot_sync(0xffffffffu, ja < 3);
                while (mask) {
                    int l_t = -1, l_g = -1;
                    const int first = __ffs(mask) - 1;
#pragma unroll
                    for (int j = 0; j < 4; j++) {
                        const int l = __ffs(mask) - 1;
                        mask &= mask - 1;
                        if (t == j) l_t = l;
                        if ((g >> 1) == j) l_g = l;
                    }
                    const uint32_t w_t = __shfl_sync(0xffffffffu, w, l_t < 0 ? first : l_t);
                    const uint32_t r0 = __shfl_sync(0xffffffffu, rc.x, l_g), r1 = __shfl_sync(0xffffffffu, rc.y, l_g);
                    const uint32_t r2 = __shfl_sync(0xffffffffu, rc.z, l_g), r3 = __shfl_sync(0xffffffffu, rc.w, l_g);
                    uint2 rw = make_uint2(0, 0);
                    if (bact && l_g >= 0) rw = (t & 1) ? make_uint2(r2, r3) : make_uint2(r0, r1);
                    const uint4* xr = reinterpret_cast<const uint4*>(x) + (size_t)(w_t & 0x3fffu) * 64;
                    uint32_t R[8], b0, b1;
                    edge_terms(rw.x, rw.y, wz, wt, R, b0, b1);
                    const int p = (l_t < 0 ? 15 : (int)((w_t >> 14) & 15)) - (g >> 2);
#pragma unroll
                    for (int h = 0; h < 8; h += 4) {
                        uint4 v[4];
#pragma unroll
                        for (int m = 0; m < 4; m++) v[m] = ldg128_relaxed(xr + chunk_of(h + m, g));
#pragma unroll
                        for (int m = 0; m < 4; m++) {
                            const uint32_t x0 = hmul2_lo(v[m].x, R[h + m]), x1 = hmul2_lo(v[m].y, R[h + m]);
                            const uint32_t x2 = hmul2_hi(v[m].z, R[h + m]), x3 = hmul2_hi(v[m].w, R[h + m]);
#pragma unroll
                            for (int j = 0; j < 2; j++) {
                                const uint32_t a0 = p == 4 * j ? b0 : 0u, a1 = p == 4 * j + 2 ? b0 : 0u;
                                const uint32_t a2 = p == 4 * j ? b1 : 0u, a3 = p == 4 * j + 2 ? b1 : 0u;
                                mma_k16v(acc[16 * j + 2 * (h + m)], a0, a1, a2, a3, x0, x1);
                                mma_k16v(acc[16 * j + 2 * (h + m) + 1], a0, a1, a2, a3, x2, x3);
                            }
                            mma_k16v(acc[32 + h + m], x0, x2, x1, x3, p == 8 ? b0 : 0u, p == 8 ? b1 : 0u);
                        }
                    }
                }
            }
        }
    }

    uint32_t aq[3][8][4];
#pragma unroll
    for (int m = 0; m < 8; m++) {
#pragma unroll
        for (int j = 0; j < 2; j++)
#pragma unroll
            for (int q = 0; q < 4; q++) {
                const float* a = acc[16 * j + 2 * m + (q >> 1)] + (q & 1) * 2;
                aq[j][m][q] = pack_bf16(a[m & 1], a[~m & 1]);
            }
        aq[2][m][0] = movm(pack_bf16(acc[32 + m][0], acc[32 + m][1]));
        aq[2][m][2] = movm(pack_bf16(acc[32 + m][2], acc[32 + m][3]));
        if (m & 1) {
            aq[2][m][0] = __byte_perm(aq[2][m][0], 0, 0x1032);
            aq[2][m][2] = __byte_perm(aq[2][m][2], 0, 0x1032);
        }
        aq[2][m][1] = aq[2][m][3] = 0;
    }
    STAMP(16);
    mbar_wait(bar_w, 0);
    STAMP(17);
    const uint4 ws0 = lds128(sb + SM_MISC + 32), ws1 = lds128(sb + SM_MISC + 48);
    const uint32_t ws[8] = {ws0.x, ws0.y, ws0.z, ws0.w, ws1.x, ws1.y, ws1.z, ws1.w};
    const uint64_t wdesc = ((sb + SM_RING) >> 4) | ((uint64_t)(2 * RSTR >> 4) << 16) | ((uint64_t)(RSTR >> 4) << 32) | (1ull << 62);
    const int nloc = min(npc, N - cta * npc);
    uint2* op = reinterpret_cast<uint2*>(out) + (size_t)(cta * npc) * 128 + g + (t & 1) * 8;
    float d[64];
    auto mix = [&](int job) {
        asm volatile("wgmma.fence.sync.aligned;" ::: "memory");
#pragma unroll
        for (int m = 0; m < 8; m++) wgmma_n128(d, aq[job][m], wdesc + ws[m], m);
        asm volatile("wgmma.commit_group.sync.aligned;" ::: "memory");
    };
    mix(0);
#pragma unroll
    for (int job = 0; job < 3; job++) {
        asm volatile("wgmma.wait_group.sync.aligned 0;" ::: "memory");
        if (job == 0) STAMP(18);
        if (job == 2) STAMP(19);
#pragma unroll
        for (int k = 0; k < 64; k++) asm volatile("" : "+f"(d[k]));
        uint32_t pk[32];
#pragma unroll
        for (int k = 0; k < 32; k++) pk[k] = pack_bf16(d[2 * k], d[2 * k + 1]);
        if (job < 2) mix(job + 1);
#pragma unroll
        for (int h = 0; h < (job < 2 ? 2 : 1); h++) {
            const int gj = grp >> (5 * job) & 31;
            const int l = job < 2 ? gj + (1 + 2 * h + (t >> 1)) * 16 : gj - 16 + (t >> 1) * 8;
            const bool ok = l < nloc;
#pragma unroll
            for (int j = 0; j < 16; j += 2) {
                const uint32_t p0 = movm(pk[2 * j + h]), p1 = movm(pk[2 * j + 2 + h]);
                const uint32_t rv = __shfl_xor_sync(0xffffffffu, (t & 1) ? p0 : p1, 1);
                if (ok) op[l * 128 + j * 8] = (t & 1) ? make_uint2(rv, p1) : make_uint2(p0, rv);
            }
        }
    }
    __syncwarp();
    ANCHOR(1);
}

}

extern "C" void kernel_launch(void* const* d_in, const int* in_sizes, int n_in, void* d_out, int out_size) {
    const __nv_bfloat16* x     = (const __nv_bfloat16*)d_in[0];
    const int*           src   = (const int*)d_in[1];
    const int*           dst   = (const int*)d_in[2];
    const uint2*         Y     = (const uint2*)d_in[3];
    const uint2*         ef    = (const uint2*)d_in[4];
    const __nv_bfloat16* w_rad = (const __nv_bfloat16*)d_in[5];
    const __nv_bfloat16* cg    = (const __nv_bfloat16*)d_in[6];
    const __nv_bfloat16* w_mix = (const __nv_bfloat16*)d_in[7];
    __nv_bfloat16*       out   = (__nv_bfloat16*)d_out;
    const int N = in_sizes[0] / 512;
    const int E = in_sizes[1];

    static int n_sm = 0;
    static Scratch* scr = nullptr;
    static decltype(&cuTensorMapEncodeTiled) encode = nullptr;
    if (n_sm == 0) {
        cudaDriverEntryPointQueryResult qr;
        cudaGetDriverEntryPoint("cuTensorMapEncodeTiled", (void**)&encode, cudaEnableDefault, &qr);
        cudaGetSymbolAddress((void**)&scr, g_scr);
        int dev = 0;
        cudaGetDevice(&dev);
        cudaDeviceGetAttribute(&n_sm, cudaDevAttrMultiProcessorCount, dev);
        cudaFuncSetAttribute(tfn_kernel<1>, cudaFuncAttributeMaxDynamicSharedMemorySize, SM_TOTAL);
        cudaFuncSetAttribute(tfn_kernel<2>, cudaFuncAttributeMaxDynamicSharedMemorySize, SM_TOTAL);
        cudaFuncSetAttribute(tfn_kernel<3>, cudaFuncAttributeMaxDynamicSharedMemorySize, SM_TOTAL);
    }
    CUtensorMap xmap;
    {
        const cuuint64_t dims[2] = {64, (cuuint64_t)N * 8}, strides[1] = {128};
        const cuuint32_t box[2] = {64, 8}, es[2] = {1, 1};
        encode(&xmap, CU_TENSOR_MAP_DATA_TYPE_BFLOAT16, 2, (void*)x, dims, strides, box, es, CU_TENSOR_MAP_INTERLEAVE_NONE,
               CU_TENSOR_MAP_SWIZZLE_128B, CU_TENSOR_MAP_L2_PROMOTION_NONE, CU_TENSOR_MAP_FLOAT_OOB_FILL_NONE);
    }
    CUtensorMap wmap;
    {
        const cuuint64_t dims[5] = {128, 2, 4, 4, 4}, strides[4] = {256, 512, 2048, 8192};
        const cuuint32_t box[5] = {64, 1, 2, 1, 2}, es[5] = {1, 1, 1, 1, 1};
        encode(&wmap, CU_TENSOR_MAP_DATA_TYPE_BFLOAT16, 5, (void*)w_mix, dims, strides, box, es, CU_TENSOR_MAP_INTERLEAVE_NONE,
               CU_TENSOR_MAP_SWIZZLE_128B, CU_TENSOR_MAP_L2_PROMOTION_NONE, CU_TENSOR_MAP_FLOAT_OOB_FILL_NONE);
    }
    const int slice = ((E + NCTA - 1) / NCTA + 3) / 4 * 4;
    const int npc   = (N + NCTA - 1) / NCTA;
    const uint32_t npc_magic = (uint32_t)((0x100000000ull + npc - 1) / npc);
    const uint32_t bin_magic = (uint32_t)(((uint64_t)NBIN << 18) / N);
    const uint64_t want = PDT * (uint64_t)E / (32u * N);
    const uint32_t pace = want < 1 ? 1 : want > 127 ? 127 : (uint32_t)want;
    cudaStream_t st = cudaStreamPerThread;
    if (n_sm >= NCTA) {
        tfn_kernel<3><<<NCTA, NT, SM_TOTAL, st>>>(xmap, wmap, x, src, dst, Y, ef, w_rad, cg, w_mix, out, scr, N, E, slice, npc, npc_magic, bin_magic, pace);
    } else {
        tfn_kernel<1><<<NCTA, NT, SM_TOTAL, st>>>(xmap, wmap, x, src, dst, Y, ef, w_rad, cg, w_mix, out, scr, N, E, slice, npc, npc_magic, bin_magic, pace);
        tfn_kernel<2><<<NCTA, NT, SM_TOTAL, st>>>(xmap, wmap, x, src, dst, Y, ef, w_rad, cg, w_mix, out, scr, N, E, slice, npc, npc_magic, bin_magic, pace);
    }
}
```

```cpp
#include <cuda.h>
#include <cuda_runtime.h>
#include <cuda_bf16.h>
#include <stdint.h>

namespace {

constexpr int NCTA   = 132;
constexpr int NW     = 8;
constexpr int NT     = 2 * NW * 32;
constexpr int RA     = 5;
constexpr int SLICE  = RA * NT;
constexpr int MBE    = 39;
constexpr int MB1    = NCTA * 32;
constexpr int MBW    = NCTA * 40;
constexpr int ASTR   = 44;
constexpr int NH     = NW * 32;
constexpr int RL     = 17;
constexpr int NG     = 24;
constexpr int KCAP   = 684;
constexpr int RCAP   = 2688;
constexpr int GK     = 48;
#define NBIN_ 256
constexpr int NBIN   = NBIN_;
constexpr int BSH    = NBIN == 256 ? 17 : 18;
constexpr int LBIN   = 128;
#define S_ 5
constexpr int S      = S_;
constexpr int SMG    = (65535 + S) / S;
constexpr int LCAP   = KCAP + NW + 4;
constexpr uint32_t EMPTY = NG << 25;

constexpr uint32_t sb = 1024;
constexpr int SM_RING = 0;
constexpr int RSTR    = NW * S * 1024 + 256;
constexpr int SM_REC  = SM_RING + 4 * RSTR - (S - 5) * 32768;
constexpr int SM_ZERO = SM_REC + RCAP * 16;
constexpr int SM_LIST = SM_ZERO + 128;
constexpr int SM_MISC = SM_LIST + LCAP * 16;
constexpr int SM_STATE = SM_MISC + 256;
constexpr int SM_BAR  = SM_STATE + 128;
constexpr int SM_SRC  = SM_BAR + NW * S * 8 + 64;
constexpr int SM_SEG  = SM_SRC + LCAP * 16;
constexpr int SM_TOTAL = SM_SEG + NCTA * 4;
constexpr int SM_AREC = SM_RING;
constexpr int SM_AP   = SM_AREC + SLICE * 16;
constexpr int SM_AMB  = SM_AP + NH * 12;
constexpr int SM_AOFF = SM_AMB + (NCTA + 1) * ASTR * 4;
constexpr int SM_HIST = SM_AOFF + 576;
constexpr int SM_KEY  = SM_HIST + 576;
constexpr int SM_LH   = SM_KEY + 128;
constexpr int SM_BIN  = SM_LH + NW * LBIN * 4;
constexpr int SM_DUM  = SM_BIN + NG * NBIN * 4;
constexpr int SM_KSG  = SM_DUM + 128 * 4;
constexpr int SM_CPY  = SM_KSG + NG * GK * 16;
constexpr int SM_DOFF = SM_CPY + NH * 16;
constexpr int SM_LT   = SM_DOFF + NH * 4;
constexpr int SM_RAWY = SM_REC;
constexpr int SM_RAWF = SM_RAWY + SLICE * 8;
static_assert(SM_LT + 144 <= SM_REC && SM_RAWF + SLICE * 8 <= SM_ZERO, "temporaries must fit");
static_assert(SM_TOTAL <= 232448, "smem");
static_assert(SM_AMB % 128 == 0 && SM_LIST % 128 == 0 && SM_BAR % 128 == 0 && SM_HIST % 16 == 0 && SM_BIN % 16 == 0 && SM_MISC % 16 == 0 && SM_KSG % 16 == 0, "align");
static_assert(NCTA <= RL * NW && SM_SRC + NW * 128 - SM_REC < 65536 && LBIN == 128 && SM_SRC % 16 == 0 && SM_ZERO % 128 == 0, "layout");

struct Scratch {
    uint4    rec[NCTA * SLICE];
    uint32_t mb[NCTA * MBW];
    uint32_t ss[NCTA * SLICE];
    uint2    exc[NCTA * MBW];
    uint32_t epoch;
    uint32_t sent[2];
    uint32_t gap[61];
    uint32_t sent2[2];
};
__device__ __align__(128) Scratch g_scr;

#define STAMP(i)
#define STAMPT(i, th)
#define ANCHOR(i)

__device__ __forceinline__ uint32_t pack_bf16(float lo, float hi) {
    __nv_bfloat162 v = __floats2bfloat162_rn(lo, hi);
    return *reinterpret_cast<uint32_t*>(&v);
}
__device__ __forceinline__ uint4 lds128(uint32_t addr) {
    uint4 v;
    asm volatile("ld.shared.v4.u32 {%0,%1,%2,%3}, [%4];" : "=r"(v.x), "=r"(v.y), "=r"(v.z), "=r"(v.w) : "r"(addr) : "memory");
    return v;
}
__device__ __forceinline__ uint32_t movm(uint32_t v) {
    uint32_t r;
    asm("movmatrix.sync.aligned.m8n8.trans.b16 %0, %1;" : "=r"(r) : "r"(v));
    return r;
}
__device__ __forceinline__ uint4 ldg128_relaxed(const uint4* p) {
    uint4 v;
    asm volatile("ld.relaxed.gpu.global.v4.u32 {%0,%1,%2,%3}, [%4];" : "=r"(v.x), "=r"(v.y), "=r"(v.z), "=r"(v.w) : "l"(p) : "memory");
    return v;
}
__device__ __forceinline__ uint32_t atoms_inc(uint32_t addr) {
    uint32_t v;
    asm volatile("atom.shared.add.u32 %0, [%1], 1;" : "=r"(v) : "r"(addr) : "memory");
    return v;
}
__device__ __forceinline__ uint32_t lds32(uint32_t addr) {
    uint32_t v;
    asm volatile("ld.shared.u32 %0, [%1];" : "=r"(v) : "r"(addr) : "memory");
    return v;
}
__device__ __forceinline__ void sts32_if(bool p, uint32_t addr, uint32_t v) {
    asm volatile("{\n\t.reg .pred p;\n\tsetp.ne.u32 p, %2, 0;\n\t@p st.shared.u32 [%0], %1;\n\t}"
                 ::"r"(addr), "r"(v), "r"((uint32_t)p) : "memory");
}
__device__ __forceinline__ uint32_t lds32v(uint32_t addr) {
    uint32_t v;
    asm volatile("ld.volatile.shared.u32 %0, [%1];" : "=r"(v) : "r"(addr) : "memory");
    return v;
}
__device__ __forceinline__ uint32_t clock32() {
    uint32_t c;
    asm volatile("mov.u32 %0, %clock;" : "=r"(c));
    return c;
}
__device__ __forceinline__ uint32_t timer32() {
    uint32_t c;
    asm volatile("mov.u32 %0, %globaltimer_lo;" : "=r"(c));
    return c;
}
__device__ __forceinline__ uint32_t opaque(uint32_t v) {
    asm volatile("" : "+r"(v));
    return v;
}
#define HINT ""
__device__ __forceinline__ bool mbar_try(uint32_t bar, uint32_t parity) {
    uint32_t ok;
    asm volatile("{\n\t.reg .pred p;\n\t"
                 "mbarrier.try_wait.parity.shared::cta.b64 p, [%1], %2" HINT ";\n\t"
                 "selp.u32 %0, 1, 0, p;\n\t}"
                 : "=r"(ok) : "r"(bar), "r"(parity) : "memory");
    return ok;
}
__device__ __forceinline__ void mbar_wait(uint32_t bar, uint32_t parity) {
    int guard = 0;
    while (!mbar_try(bar, parity) && ++guard < (1 << 20)) {}
}
__device__ __forceinline__ void mbar_init(uint32_t bar, uint32_t count) {
    asm volatile("mbarrier.init.shared::cta.b64 [%0], %1;" ::"r"(bar), "r"(count) : "memory");
}
__device__ __forceinline__ uint32_t atoms_add(uint32_t addr, uint32_t x) {
    uint32_t v;
    asm volatile("atom.shared.add.u32 %0, [%1], %2;" : "=r"(v) : "r"(addr), "r"(x) : "memory");
    return v;
}
__device__ __forceinline__ uint2 lds64(uint32_t addr) {
    uint2 v;
    asm volatile("ld.shared.v2.u32 {%0,%1}, [%2];" : "=r"(v.x), "=r"(v.y) : "r"(addr) : "memory");
    return v;
}
__device__ __forceinline__ void sts128_if(bool p, uint32_t addr, uint4 v) {
    asm volatile("{\n\t.reg .pred p;\n\tsetp.ne.u32 p, %5, 0;\n\t@p st.shared.v4.u32 [%0], {%1,%2,%3,%4};\n\t}"
                 ::"r"(addr), "r"(v.x), "r"(v.y), "r"(v.z), "r"(v.w), "r"((uint32_t)p) : "memory");
}
__device__ __forceinline__ int warp_incl_scan(int v, int lane) {
#pragma unroll
    for (int o = 1; o < 32; o <<= 1) {
        const int u = __shfl_up_sync(0xffffffffu, v, o);
        if (lane >= o) v += u;
    }
    return v;
}

__device__ __forceinline__ void mma_k16v(float (&d)[4], uint32_t a0, uint32_t a1, uint32_t a2, uint32_t a3,
                                         uint32_t b0, uint32_t b1) {
    asm volatile("mma.sync.aligned.m16n8k16.row.col.f32.bf16.bf16.f32 {%0,%1,%2,%3}, {%4,%5,%6,%7}, {%8,%9}, {%0,%1,%2,%3};"
        : "+f"(d[0]), "+f"(d[1]), "+f"(d[2]), "+f"(d[3])
        : "r"(a0), "r"(a1), "r"(a2), "r"(a3), "r"(b0), "r"(b1));
}
__device__ __forceinline__ bool elect_one() {
    uint32_t ok;
    asm volatile("{\n\t.reg .pred p;\n\telect.sync _|p, 0xffffffff;\n\tselp.u32 %0, 1, 0, p;\n\t}" : "=r"(ok));
    return ok;
}
__host__ __device__ constexpr int chunk_of(int m, int g) {
    return ((m & 1) + (g & 2) + 2 * (m & 2)) * 8 + ((g ^ m) & 1) + ((m >> 2) & 1) * 2 + 4 * (((g >> 2) ^ (m >> 1)) & 1);
}
__device__ __forceinline__ uint4 lds128v(uint32_t addr) {
    uint4 v;
    asm volatile("ld.volatile.shared.v4.u32 {%0,%1,%2,%3}, [%4];" : "=r"(v.x), "=r"(v.y), "=r"(v.z), "=r"(v.w) : "r"(addr) : "memory");
    return v;
}
#define HM0 0x50000u
#define MAIN_LOOP_PTX \
    "{\n" \
    ".reg .b32 v<16>, a<4>, u<4>, b<2>, c<2>, w<4>, ca0, ca1, na0, na1, ef, rx, ry, ex, ey, e0, e1, e3, gx, gy, cnt;\n" \
    ".reg .f32 z<16>, t<8>, y<4>, fz;\n" \
    ".reg .b16 h<2>;\n" \
    ".reg .pred pa, pr, p<2>, q<3>;\n" \
    "mov.f32 fz, 0f00000000;\n" \
    "setp.ne.u32 pa, %175, 0; mov.b32 rx, 0; mov.b32 ry, 0;\n" \
    "ld.shared.v4.u32 {e0,e1,ex,e3}, [%160];\n" \
    "prmt.b32 ey, e0, e1, %176;\n" \
    "lop3.b32 u2, ey, 0xfff0, %174, 0xea; @pa ld.shared.v2.u32 {rx,ry}, [u2+%178];\n" \
    "and.b32 u2, ey, %172; setp.ge.u32 p1, u2, 0x40000; setp.ne.and.u32 p0, u2, 0, !p1;\n" \
    "shr.u32 u2, ex, 16; add.u32 na0, %171, u2;\n" \
    "mma.sync.aligned.m16n8k8.row.col.f32.bf16.bf16.f32 {y0,y1,y2,y3}, {%169,%170}, {ry}, {fz,fz,fz,fz};\n" \
    "cvt.rn.bf16x2.f32 b0, y2, y0; cvt.rn.bf16x2.f32 b1, y3, y1;\n" \
    "selp.b32 a0, b0, 0, p0; selp.b32 a1, b0, 0, p1; selp.b32 a2, b1, 0, p0; selp.b32 a3, b1, 0, p1;\n" \
    "mma.sync.aligned.m16n8k8.row.col.f32.bf16.bf16.f32 {z0,z1,z2,z3}, {%161,%162}, {rx}, {fz,fz,fz,fz};\n" \
    "tanh.approx.f32 t0, z0; tanh.approx.f32 t1, z2;\n" \
    "ld.shared.v4.u32 {e0,e1,ex,e3}, [%160+16];\n" \
    "bra.uni SLOW;\n" \
    "S2:\n" \
    "or.b32 c0, a0, a1; or.b32 c1, a2, a3;\n" \
    "add.u32 %160, %160, 16;\n" \
    "tanh.approx.f32 t3, z3;\n" \
    "fma.rn.f32 z0, z0, t0, z0;\n" \
    "mov.b32 {h0,h1}, z0; mov.b32 u1, {h1,h1}; mul.bf16x2 w0, v0, u1;\n" \
    "mov.b32 {h0,h1}, z0; mov.b32 u1, {h1,h1}; mul.bf16x2 w1, v1, u1;\n" \
    "tanh.approx.f32 t2, z1;\n" \
    "mov.b32 ca0, na0; xor.b32 ca1, na0, 32; mov.b32 ef, rx;\n" \
    "ld.shared.v4.u32 {v8,v9,v10,v11}, [ca0+512];\n" \
    "fma.rn.f32 z2, z2, t1, z2;\n" \
    "mov.b32 {h0,h1}, z2; mov.b32 u1, {h1,h1}; mul.bf16x2 w2, v2, u1;\n" \
    "mov.b32 {h0,h1}, z2; mov.b32 u1, {h1,h1}; mul.bf16x2 w3, v3, u1;\n" \
    "mma.sync.aligned.m16n8k8.row.col.f32.bf16.bf16.f32 {z4,z5,z6,z7}, {%163,%164}, {ef}, {fz,fz,fz,fz};\n" \
    "ld.shared.v4.u32 {v12,v13,v14,v15}, [ca0+640];\n" \
    "tanh.approx.f32 t4, z4;\n" \
    "mma.sync.aligned.m16n8k16.row.col.f32.bf16.bf16.f32 {%128,%129,%130,%131}, {w0,w2,w1,w3}, {c0,c1}, {%128,%129,%130,%131};\n" \
    "fma.rn.f32 z3, z3, t3, z3;\n" \
    "mov.b32 {h0,h1}, z3; mov.b32 u1, {h1,h1}; mul.bf16x2 w2, v6, u1;\n" \
    "tanh.approx.f32 t5, z6;\n" \
    "fma.rn.f32 z1, z1, t2, z1;\n" \
    "mov.b32 {h0,h1}, z1; mov.b32 u1, {h1,h1}; mul.bf16x2 w1, v5, u1;\n" \
    "mov.b32 {h0,h1}, z1; mov.b32 u1, {h1,h1}; mul.bf16x2 w0, v4, u1;\n" \
    "mov.b32 {h0,h1}, z3; mov.b32 u1, {h1,h1}; mul.bf16x2 w3, v7, u1;\n" \
    "mma.sync.aligned.m16n8k16.row.col.f32.bf16.bf16.f32 {%132,%133,%134,%135}, {w0,w2,w1,w3}, {c0,c1}, {%132,%133,%134,%135};\n" \
    "ld.shared.v4.u32 {v0,v1,v2,v3}, [ca1+0];\n" \
    "tanh.approx.f32 t6, z5;\n" \
    "tanh.approx.f32 t7, z7;\n" \
    "fma.rn.f32 z4, z4, t4, z4;\n" \
    "mov.b32 {h0,h1}, z4; mov.b32 u1, {h1,h1}; mul.bf16x2 w1, v9, u1;\n" \
    "mov.b32 {h0,h1}, z4; mov.b32 u1, {h1,h1}; mul.bf16x2 w0, v8, u1;\n" \
    "fma.rn.f32 z6, z6, t5, z6;\n" \
    "mov.b32 {h0,h1}, z6; mov.b32 u1, {h1,h1}; mul.bf16x2 w2, v10, u1;\n" \
    "mma.sync.aligned.m16n8k8.row.col.f32.bf16.bf16.f32 {z0,z1,z2,z3}, {%165,%166}, {ef}, {fz,fz,fz,fz};\n" \
    "tanh.approx.f32 t0, z0;\n" \
    "mov.b32 {h0,h1}, z6; mov.b32 u1, {h1,h1}; mul.bf16x2 w3, v11, u1;\n" \
    "mma.sync.aligned.m16n8k16.row.col.f32.bf16.bf16.f32 {%136,%137,%138,%139}, {w0,w2,w1,w3}, {c0,c1}, {%136,%137,%138,%139};\n" \
    "fma.rn.f32 z7, z7, t7, z7;\n" \
    "ld.shared.v4.u32 {v4,v5,v6,v7}, [ca1+128];\n" \
    "tanh.approx.f32 t1, z2;\n" \
    "fma.rn.f32 z5, z5, t6, z5;\n" \
    "mov.b32 {h0,h1}, z5; mov.b32 u1, {h1,h1}; mul.bf16x2 w0, v12, u1;\n" \
    "mov.b32 {h0,h1}, z5; mov.b32 u1, {h1,h1}; mul.bf16x2 w1, v13, u1;\n" \
    "mov.b32 {h0,h1}, z7; mov.b32 u1, {h1,h1}; mul.bf16x2 w2, v14, u1;\n" \
    "prmt.b32 ey, e0, e1, %176;\n" \
    "mov.b32 {h0,h1}, z7; mov.b32 u1, {h1,h1}; mul.bf16x2 w3, v15, u1;\n" \
    "mma.sync.aligned.m16n8k16.row.col.f32.bf16.bf16.f32 {%140,%141,%142,%143}, {w0,w2,w1,w3}, {c0,c1}, {%140,%141,%142,%143};\n" \
    "fma.rn.f32 z0, z0, t0, z0;\n" \
    "and.b32 u2, ey, %172; setp.ge.u32 p1, u2, 0x40000; setp.ne.and.u32 p0, u2, 0, !p1;\n" \
    "mov.b32 {h0,h1}, z0; mov.b32 u1, {h1,h1}; mul.bf16x2 w1, v1, u1;\n" \
    "lop3.b32 u2, ey, 0xfff0, %174, 0xea; @pa ld.shared.v2.u32 {rx,ry}, [u2+%178];\n" \
    "tanh.approx.f32 t2, z1;\n" \
    "ld.shared.v4.u32 {v8,v9,v10,v11}, [ca1+512];\n" \
    "mov.b32 {h0,h1}, z0; mov.b32 u1, {h1,h1}; mul.bf16x2 w0, v0, u1;\n" \
    "fma.rn.f32 z2, z2, t1, z2;\n" \
    "mov.b32 {h0,h1}, z2; mov.b32 u1, {h1,h1}; mul.bf16x2 w2, v2, u1;\n" \
    "tanh.approx.f32 t3, z3;\n" \
    "mov.b32 {h0,h1}, z2; mov.b32 u1, {h1,h1}; mul.bf16x2 w3, v3, u1;\n" \
    "mma.sync.aligned.m16n8k16.row.col.f32.bf16.bf16.f32 {%144,%145,%146,%147}, {w0,w2,w1,w3}, {c0,c1}, {%144,%145,%146,%147};\n" \
    "mma.sync.aligned.m16n8k8.row.col.f32.bf16.bf16.f32 {z4,z5,z6,z7}, {%167,%168}, {ef}, {fz,fz,fz,fz};\n" \
    "and.b32 u2, ex, 1; mbarrier.test_wait.parity.shared::cta.b64 pr, [e3], u2;\n" \
    "shr.u32 u2, ex, 16; add.u32 na0, %171, u2;\n" \
    "ld.shared.v4.u32 {v12,v13,v14,v15}, [ca1+640];\n" \
    "fma.rn.f32 z1, z1, t2, z1;\n" \
    "mov.b32 {h0,h1}, z1; mov.b32 u1, {h1,h1}; mul.bf16x2 w1, v5, u1;\n" \
    "tanh.approx.f32 t4, z4;\n" \
    "fma.rn.f32 z3, z3, t3, z3;\n" \
    "mov.b32 {h0,h1}, z3; mov.b32 u1, {h1,h1}; mul.bf16x2 w3, v7, u1;\n" \
    "mov.b32 {h0,h1}, z1; mov.b32 u1, {h1,h1}; mul.bf16x2 w0, v4, u1;\n" \
    "mov.b32 {h0,h1}, z3; mov.b32 u1, {h1,h1}; mul.bf16x2 w2, v6, u1;\n" \
    "tanh.approx.f32 t5, z6;\n" \
    "st.volatile.shared.u32 [%177], %160;\n" \
    "tanh.approx.f32 t6, z5;\n" \
    "fma.rn.f32 z4, z4, t4, z4;\n" \
    "mma.sync.aligned.m16n8k16.row.col.f32.bf16.bf16.f32 {%148,%149,%150,%151}, {w0,w2,w1,w3}, {c0,c1}, {%148,%149,%150,%151};\n" \
    "mov.b32 {h0,h1}, z4; mov.b32 u1, {h1,h1}; mul.bf16x2 w0, v8, u1;\n" \
    "mov.b32 {h0,h1}, z4; mov.b32 u1, {h1,h1}; mul.bf16x2 w1, v9, u1;\n" \
    "@pr ld.shared.v4.u32 {v0,v1,v2,v3}, [na0+0];\n" \
    "fma.rn.f32 z6, z6, t5, z6;\n" \
    "mov.b32 {h0,h1}, z6; mov.b32 u1, {h1,h1}; mul.bf16x2 w2, v10, u1;\n" \
    "tanh.approx.f32 t7, z7;\n" \
    "mov.b32 {h0,h1}, z6; mov.b32 u1, {h1,h1}; mul.bf16x2 w3, v11, u1;\n" \
    "and.b32 u2, ex, 6; setp.eq.and.u32 q0, u2, 4, pr; setp.eq.and.u32 q1, u2, 6, pr; setp.eq.and.u32 q2, u2, 2, pr;\n" \
    "mma.sync.aligned.m16n8k16.row.col.f32.bf16.bf16.f32 {%152,%153,%154,%155}, {w0,w2,w1,w3}, {c0,c1}, {%152,%153,%154,%155};\n" \
    "ld.shared.v4.u32 {e0,e1,ex,e3}, [%160+16];\n" \
    "@pr ld.shared.v4.u32 {v4,v5,v6,v7}, [na0+128];\n" \
    "mma.sync.aligned.m16n8k8.row.col.f32.bf16.bf16.f32 {y0,y1,y2,y3}, {%169,%170}, {ry}, {fz,fz,fz,fz};\n" \
    "mma.sync.aligned.m16n8k8.row.col.f32.bf16.bf16.f32 {z0,z1,z2,z3}, {%161,%162}, {rx}, {fz,fz,fz,fz};\n" \
    "tanh.approx.f32 t0, z0;\n" \
    "fma.rn.f32 z5, z5, t6, z5;\n" \
    "mov.b32 {h0,h1}, z5; mov.b32 u1, {h1,h1}; mul.bf16x2 w0, v12, u1;\n" \
    "tanh.approx.f32 t1, z2;\n" \
    "mov.b32 {h0,h1}, z5; mov.b32 u1, {h1,h1}; mul.bf16x2 w1, v13, u1;\n" \
    "cvt.rn.bf16x2.f32 b0, y2, y0; cvt.rn.bf16x2.f32 b1, y3, y1;\n" \
    "fma.rn.f32 z7, z7, t7, z7;\n" \
    "mov.b32 {h0,h1}, z7; mov.b32 u1, {h1,h1}; mul.bf16x2 w2, v14, u1;\n" \
    "mov.b32 {h0,h1}, z7; mov.b32 u1, {h1,h1}; mul.bf16x2 w3, v15, u1;\n" \
    "mma.sync.aligned.m16n8k16.row.col.f32.bf16.bf16.f32 {%156,%157,%158,%159}, {w0,w2,w1,w3}, {c0,c1}, {%156,%157,%158,%159};\n" \
    "selp.b32 a0, b0, 0, p0; selp.b32 a1, b0, 0, p1; selp.b32 a2, b1, 0, p0; selp.b32 a3, b1, 0, p1;\n" \
    "@q0 bra.uni S1;\n" \
    "@q1 bra.uni S2;\n" \
    "@!q2 bra.uni SLOW;\n" \
    "S0:\n" \
    "mov.b32 ca0, na0; xor.b32 ca1, na0, 32; mov.b32 ef, rx;\n" \
    "add.u32 %160, %160, 16;\n" \
    "tanh.approx.f32 t2, z1;\n" \
    "tanh.approx.f32 t3, z3;\n" \
    "fma.rn.f32 z0, z0, t0, z0;\n" \
    "mov.b32 {h0,h1}, z0; mov.b32 u1, {h1,h1}; mul.bf16x2 v1, v1, u1;\n" \
    "mov.b32 {h0,h1}, z0; mov.b32 u1, {h1,h1}; mul.bf16x2 v0, v0, u1;\n" \
    "mma.sync.aligned.m16n8k16.row.col.f32.bf16.bf16.f32 {%0,%1,%2,%3}, {a0,a1,a2,a3}, {v0,v1}, {%0,%1,%2,%3};\n" \
    "ld.shared.v4.u32 {v8,v9,v10,v11}, [ca0+512];\n" \
    "fma.rn.f32 z2, z2, t1, z2;\n" \
    "mov.b32 {h0,h1}, z2; mov.b32 u1, {h1,h1}; mul.bf16x2 v2, v2, u1;\n" \
    "mov.b32 {h0,h1}, z2; mov.b32 u1, {h1,h1}; mul.bf16x2 v3, v3, u1;\n" \
    "mma.sync.aligned.m16n8k8.row.col.f32.bf16.bf16.f32 {z4,z5,z6,z7}, {%163,%164}, {ef}, {fz,fz,fz,fz};\n" \
    "ld.shared.v4.u32 {v12,v13,v14,v15}, [ca0+640];\n" \
    "tanh.approx.f32 t4, z4;\n" \
    "mma.sync.aligned.m16n8k16.row.col.f32.bf16.bf16.f32 {%4,%5,%6,%7}, {a0,a1,a2,a3}, {v2,v3}, {%4,%5,%6,%7};\n" \
    "fma.rn.f32 z3, z3, t3, z3;\n" \
    "tanh.approx.f32 t5, z6;\n" \
    "fma.rn.f32 z1, z1, t2, z1;\n" \
    "mov.b32 {h0,h1}, z1; mov.b32 u1, {h1,h1}; mul.bf16x2 v5, v5, u1;\n" \
    "mov.b32 {h0,h1}, z1; mov.b32 u1, {h1,h1}; mul.bf16x2 v4, v4, u1;\n" \
    "mma.sync.aligned.m16n8k16.row.col.f32.bf16.bf16.f32 {%8,%9,%10,%11}, {a0,a1,a2,a3}, {v4,v5}, {%8,%9,%10,%11};\n" \
    "mov.b32 {h0,h1}, z3; mov.b32 u1, {h1,h1}; mul.bf16x2 v6, v6, u1;\n" \
    "fma.rn.f32 z4, z4, t4, z4;\n" \
    "mov.b32 {h0,h1}, z4; mov.b32 u1, {h1,h1}; mul.bf16x2 v8, v8, u1;\n" \
    "mov.b32 {h0,h1}, z3; mov.b32 u1, {h1,h1}; mul.bf16x2 v7, v7, u1;\n" \
    "mma.sync.aligned.m16n8k16.row.col.f32.bf16.bf16.f32 {%12,%13,%14,%15}, {a0,a1,a2,a3}, {v6,v7}, {%12,%13,%14,%15};\n" \
    "ld.shared.v4.u32 {v0,v1,v2,v3}, [ca1+0];\n" \
    "mov.b32 {h0,h1}, z4; mov.b32 u1, {h1,h1}; mul.bf16x2 v9, v9, u1;\n" \
    "tanh.approx.f32 t7, z7;\n" \
    "tanh.approx.f32 t6, z5;\n" \
    "mma.sync.aligned.m16n8k16.row.col.f32.bf16.bf16.f32 {%16,%17,%18,%19}, {a0,a1,a2,a3}, {v8,v9}, {%16,%17,%18,%19};\n" \
    "mma.sync.aligned.m16n8k8.row.col.f32.bf16.bf16.f32 {z0,z1,z2,z3}, {%165,%166}, {ef}, {fz,fz,fz,fz};\n" \
    "fma.rn.f32 z6, z6, t5, z6;\n" \
    "mov.b32 {h0,h1}, z6; mov.b32 u1, {h1,h1}; mul.bf16x2 v10, v10, u1;\n" \
    "mov.b32 {h0,h1}, z6; mov.b32 u1, {h1,h1}; mul.bf16x2 v11, v11, u1;\n" \
    "mma.sync.aligned.m16n8k16.row.col.f32.bf16.bf16.f32 {%20,%21,%22,%23}, {a0,a1,a2,a3}, {v10,v11}, {%20,%21,%22,%23};\n" \
    "ld.shared.v4.u32 {v4,v5,v6,v7}, [ca1+128];\n" \
    "tanh.approx.f32 t0, z0;\n" \
    "fma.rn.f32 z5, z5, t6, z5;\n" \
    "mov.b32 {h0,h1}, z5; mov.b32 u1, {h1,h1}; mul.bf16x2 v13, v13, u1;\n" \
    "mov.b32 {h0,h1}, z5; mov.b32 u1, {h1,h1}; mul.bf16x2 v12, v12, u1;\n" \
    "fma.rn.f32 z7, z7, t7, z7;\n" \
    "mma.sync.aligned.m16n8k16.row.col.f32.bf16.bf16.f32 {%24,%25,%26,%27}, {a0,a1,a2,a3}, {v12,v13}, {%24,%25,%26,%27};\n" \
    "mov.b32 {h0,h1}, z7; mov.b32 u1, {h1,h1}; mul.bf16x2 v14, v14, u1;\n" \
    "tanh.approx.f32 t1, z2;\n" \
    "tanh.approx.f32 t2, z1;\n" \
    "mov.b32 {h0,h1}, z7; mov.b32 u1, {h1,h1}; mul.bf16x2 v15, v15, u1;\n" \
    "mma.sync.aligned.m16n8k16.row.col.f32.bf16.bf16.f32 {%28,%29,%30,%31}, {a0,a1,a2,a3}, {v14,v15}, {%28,%29,%30,%31};\n" \
    "prmt.b32 ey, e0, e1, %176;\n" \
    "and.b32 u2, ey, %172; setp.ge.u32 p1, u2, 0x40000; setp.ne.and.u32 p0, u2, 0, !p1;\n" \
    "lop3.b32 u2, ey, 0xfff0, %174, 0xea; @pa ld.shared.v2.u32 {rx,ry}, [u2+%178];\n" \
    "ld.shared.v4.u32 {v8,v9,v10,v11}, [ca1+512];\n" \
    "tanh.approx.f32 t3, z3;\n" \
    "fma.rn.f32 z0, z0, t0, z0;\n" \
    "mov.b32 {h0,h1}, z0; mov.b32 u1, {h1,h1}; mul.bf16x2 v1, v1, u1;\n" \
    "mov.b32 {h0,h1}, z0; mov.b32 u1, {h1,h1}; mul.bf16x2 v0, v0, u1;\n" \
    "mma.sync.aligned.m16n8k16.row.col.f32.bf16.bf16.f32 {%32,%33,%34,%35}, {a0,a1,a2,a3}, {v0,v1}, {%32,%33,%34,%35};\n" \
    "fma.rn.f32 z2, z2, t1, z2;\n" \
    "mov.b32 {h0,h1}, z2; mov.b32 u1, {h1,h1}; mul.bf16x2 v2, v2, u1;\n" \
    "mov.b32 {h0,h1}, z2; mov.b32 u1, {h1,h1}; mul.bf16x2 v3, v3, u1;\n" \
    "mma.sync.aligned.m16n8k16.row.col.f32.bf16.bf16.f32 {%36,%37,%38,%39}, {a0,a1,a2,a3}, {v2,v3}, {%36,%37,%38,%39};\n" \
    "and.b32 u2, ex, 1; mbarrier.test_wait.parity.shared::cta.b64 pr, [e3], u2;\n" \
    "ld.shared.v4.u32 {v12,v13,v14,v15}, [ca1+640];\n" \
    "mma.sync.aligned.m16n8k8.row.col.f32.bf16.bf16.f32 {z4,z5,z6,z7}, {%167,%168}, {ef}, {fz,fz,fz,fz};\n" \
    "fma.rn.f32 z1, z1, t2, z1;\n" \
    "mov.b32 {h0,h1}, z1; mov.b32 u1, {h1,h1}; mul.bf16x2 v5, v5, u1;\n" \
    "shr.u32 u2, ex, 16; add.u32 na0, %171, u2;\n" \
    "mov.b32 {h0,h1}, z1; mov.b32 u1, {h1,h1}; mul.bf16x2 v4, v4, u1;\n" \
    "tanh.approx.f32 t4, z4;\n" \
    "tanh.approx.f32 t5, z6;\n" \
    "mma.sync.aligned.m16n8k16.row.col.f32.bf16.bf16.f32 {%40,%41,%42,%43}, {a0,a1,a2,a3}, {v4,v5}, {%40,%41,%42,%43};\n" \
    "st.volatile.shared.u32 [%177], %160;\n" \
    "fma.rn.f32 z3, z3, t3, z3;\n" \
    "mov.b32 {h0,h1}, z3; mov.b32 u1, {h1,h1}; mul.bf16x2 v6, v6, u1;\n" \
    "mov.b32 {h0,h1}, z3; mov.b32 u1, {h1,h1}; mul.bf16x2 v7, v7, u1;\n" \
    "mma.sync.aligned.m16n8k16.row.col.f32.bf16.bf16.f32 {%44,%45,%46,%47}, {a0,a1,a2,a3}, {v6,v7}, {%44,%45,%46,%47};\n" \
    "fma.rn.f32 z4, z4, t4, z4;\n" \
    "tanh.approx.f32 t6, z5;\n" \
    "@pr ld.shared.v4.u32 {v0,v1,v2,v3}, [na0+0];\n" \
    "mov.b32 {h0,h1}, z4; mov.b32 u1, {h1,h1}; mul.bf16x2 v8, v8, u1;\n" \
    "fma.rn.f32 z6, z6, t5, z6;\n" \
    "mov.b32 {h0,h1}, z4; mov.b32 u1, {h1,h1}; mul.bf16x2 v9, v9, u1;\n" \
    "mov.b32 {h0,h1}, z6; mov.b32 u1, {h1,h1}; mul.bf16x2 v10, v10, u1;\n" \
    "mov.b32 {h0,h1}, z6; mov.b32 u1, {h1,h1}; mul.bf16x2 v11, v11, u1;\n" \
    "tanh.approx.f32 t7, z7;\n" \
    "mma.sync.aligned.m16n8k16.row.col.f32.bf16.bf16.f32 {%52,%53,%54,%55}, {a0,a1,a2,a3}, {v10,v11}, {%52,%53,%54,%55};\n" \
    "mma.sync.aligned.m16n8k16.row.col.f32.bf16.bf16.f32 {%48,%49,%50,%51}, {a0,a1,a2,a3}, {v8,v9}, {%48,%49,%50,%51};\n" \
    "mma.sync.aligned.m16n8k8.row.col.f32.bf16.bf16.f32 {z0,z1,z2,z3}, {%161,%162}, {rx}, {fz,fz,fz,fz};\n" \
    "mma.sync.aligned.m16n8k8.row.col.f32.bf16.bf16.f32 {y0,y1,y2,y3}, {%169,%170}, {ry}, {fz,fz,fz,fz};\n" \
    "and.b32 u2, ex, 6; setp.eq.and.u32 q0, u2, 2, pr; setp.eq.and.u32 q1, u2, 6, pr; setp.eq.and.u32 q2, u2, 4, pr;\n" \
    "ld.shared.v4.u32 {e0,e1,ex,e3}, [%160+16];\n" \
    "tanh.approx.f32 t0, z0;\n" \
    "fma.rn.f32 z5, z5, t6, z5;\n" \
    "mov.b32 {h0,h1}, z5; mov.b32 u1, {h1,h1}; mul.bf16x2 v13, v13, u1;\n" \
    "tanh.approx.f32 t1, z2;\n" \
    "@pr ld.shared.v4.u32 {v4,v5,v6,v7}, [na0+128];\n" \
    "mov.b32 {h0,h1}, z5; mov.b32 u1, {h1,h1}; mul.bf16x2 v12, v12, u1;\n" \
    "mma.sync.aligned.m16n8k16.row.col.f32.bf16.bf16.f32 {%56,%57,%58,%59}, {a0,a1,a2,a3}, {v12,v13}, {%56,%57,%58,%59};\n" \
    "fma.rn.f32 z7, z7, t7, z7;\n" \
    "mov.b32 {h0,h1}, z7; mov.b32 u1, {h1,h1}; mul.bf16x2 v14, v14, u1;\n" \
    "mov.b32 {h0,h1}, z7; mov.b32 u1, {h1,h1}; mul.bf16x2 v15, v15, u1;\n" \
    "mma.sync.aligned.m16n8k16.row.col.f32.bf16.bf16.f32 {%60,%61,%62,%63}, {a0,a1,a2,a3}, {v14,v15}, {%60,%61,%62,%63};\n" \
    "cvt.rn.bf16x2.f32 b0, y2, y0; cvt.rn.bf16x2.f32 b1, y3, y1;\n" \
    "selp.b32 a0, b0, 0, p0; selp.b32 a1, b0, 0, p1; selp.b32 a2, b1, 0, p0; selp.b32 a3, b1, 0, p1;\n" \
    "@q0 bra.uni S0;\n" \
    "@q1 bra.uni S2;\n" \
    "@!q2 bra.uni SLOW;\n" \
    "S1:\n" \
    "mov.b32 ca0, na0; xor.b32 ca1, na0, 32; mov.b32 ef, rx;\n" \
    "add.u32 %160, %160, 16;\n" \
    "tanh.approx.f32 t2, z1;\n" \
    "tanh.approx.f32 t3, z3;\n" \
    "fma.rn.f32 z0, z0, t0, z0;\n" \
    "mov.b32 {h0,h1}, z0; mov.b32 u1, {h1,h1}; mul.bf16x2 v1, v1, u1;\n" \
    "mov.b32 {h0,h1}, z0; mov.b32 u1, {h1,h1}; mul.bf16x2 v0, v0, u1;\n" \
    "mma.sync.aligned.m16n8k16.row.col.f32.bf16.bf16.f32 {%64,%65,%66,%67}, {a0,a1,a2,a3}, {v0,v1}, {%64,%65,%66,%67};\n" \
    "ld.shared.v4.u32 {v8,v9,v10,v11}, [ca0+512];\n" \
    "fma.rn.f32 z2, z2, t1, z2;\n" \
    "mov.b32 {h0,h1}, z2; mov.b32 u1, {h1,h1}; mul.bf16x2 v2, v2, u1;\n" \
    "mov.b32 {h0,h1}, z2; mov.b32 u1, {h1,h1}; mul.bf16x2 v3, v3, u1;\n" \
    "mma.sync.aligned.m16n8k8.row.col.f32.bf16.bf16.f32 {z4,z5,z6,z7}, {%163,%164}, {ef}, {fz,fz,fz,fz};\n" \
    "ld.shared.v4.u32 {v12,v13,v14,v15}, [ca0+640];\n" \
    "tanh.approx.f32 t4, z4;\n" \
    "mma.sync.aligned.m16n8k16.row.col.f32.bf16.bf16.f32 {%68,%69,%70,%71}, {a0,a1,a2,a3}, {v2,v3}, {%68,%69,%70,%71};\n" \
    "fma.rn.f32 z3, z3, t3, z3;\n" \
    "tanh.approx.f32 t5, z6;\n" \
    "fma.rn.f32 z1, z1, t2, z1;\n" \
    "mov.b32 {h0,h1}, z1; mov.b32 u1, {h1,h1}; mul.bf16x2 v5, v5, u1;\n" \
    "mov.b32 {h0,h1}, z1; mov.b32 u1, {h1,h1}; mul.bf16x2 v4, v4, u1;\n" \
    "mma.sync.aligned.m16n8k16.row.col.f32.bf16.bf16.f32 {%72,%73,%74,%75}, {a0,a1,a2,a3}, {v4,v5}, {%72,%73,%74,%75};\n" \
    "mov.b32 {h0,h1}, z3; mov.b32 u1, {h1,h1}; mul.bf16x2 v6, v6, u1;\n" \
    "fma.rn.f32 z4, z4, t4, z4;\n" \
    "mov.b32 {h0,h1}, z4; mov.b32 u1, {h1,h1}; mul.bf16x2 v8, v8, u1;\n" \
    "mov.b32 {h0,h1}, z3; mov.b32 u1, {h1,h1}; mul.bf16x2 v7, v7, u1;\n" \
    "mma.sync.aligned.m16n8k16.row.col.f32.bf16.bf16.f32 {%76,%77,%78,%79}, {a0,a1,a2,a3}, {v6,v7}, {%76,%77,%78,%79};\n" \
    "ld.shared.v4.u32 {v0,v1,v2,v3}, [ca1+0];\n" \
    "mov.b32 {h0,h1}, z4; mov.b32 u1, {h1,h1}; mul.bf16x2 v9, v9, u1;\n" \
    "tanh.approx.f32 t7, z7;\n" \
    "tanh.approx.f32 t6, z5;\n" \
    "mma.sync.aligned.m16n8k16.row.col.f32.bf16.bf16.f32 {%80,%81,%82,%83}, {a0,a1,a2,a3}, {v8,v9}, {%80,%81,%82,%83};\n" \
    "mma.sync.aligned.m16n8k8.row.col.f32.bf16.bf16.f32 {z0,z1,z2,z3}, {%165,%166}, {ef}, {fz,fz,fz,fz};\n" \
    "fma.rn.f32 z6, z6, t5, z6;\n" \
    "mov.b32 {h0,h1}, z6; mov.b32 u1, {h1,h1}; mul.bf16x2 v10, v10, u1;\n" \
    "mov.b32 {h0,h1}, z6; mov.b32 u1, {h1,h1}; mul.bf16x2 v11, v11, u1;\n" \
    "mma.sync.aligned.m16n8k16.row.col.f32.bf16.bf16.f32 {%84,%85,%86,%87}, {a0,a1,a2,a3}, {v10,v11}, {%84,%85,%86,%87};\n" \
    "ld.shared.v4.u32 {v4,v5,v6,v7}, [ca1+128];\n" \
    "tanh.approx.f32 t0, z0;\n" \
    "fma.rn.f32 z5, z5, t6, z5;\n" \
    "mov.b32 {h0,h1}, z5; mov.b32 u1, {h1,h1}; mul.bf16x2 v13, v13, u1;\n" \
    "mov.b32 {h0,h1}, z5; mov.b32 u1, {h1,h1}; mul.bf16x2 v12, v12, u1;\n" \
    "fma.rn.f32 z7, z7, t7, z7;\n" \
    "mma.sync.aligned.m16n8k16.row.col.f32.bf16.bf16.f32 {%88,%89,%90,%91}, {a0,a1,a2,a3}, {v12,v13}, {%88,%89,%90,%91};\n" \
    "mov.b32 {h0,h1}, z7; mov.b32 u1, {h1,h1}; mul.bf16x2 v14, v14, u1;\n" \
    "tanh.approx.f32 t1, z2;\n" \
    "tanh.approx.f32 t2, z1;\n" \
    "mov.b32 {h0,h1}, z7; mov.b32 u1, {h1,h1}; mul.bf16x2 v15, v15, u1;\n" \
    "mma.sync.aligned.m16n8k16.row.col.f32.bf16.bf16.f32 {%92,%93,%94,%95}, {a0,a1,a2,a3}, {v14,v15}, {%92,%93,%94,%95};\n" \
    "prmt.b32 ey, e0, e1, %176;\n" \
    "and.b32 u2, ey, %172; setp.ge.u32 p1, u2, 0x40000; setp.ne.and.u32 p0, u2, 0, !p1;\n" \
    "lop3.b32 u2, ey, 0xfff0, %174, 0xea; @pa ld.shared.v2.u32 {rx,ry}, [u2+%178];\n" \
    "ld.shared.v4.u32 {v8,v9,v10,v11}, [ca1+512];\n" \
    "tanh.approx.f32 t3, z3;\n" \
    "fma.rn.f32 z0, z0, t0, z0;\n" \
    "mov.b32 {h0,h1}, z0; mov.b32 u1, {h1,h1}; mul.bf16x2 v1, v1, u1;\n" \
    "mov.b32 {h0,h1}, z0; mov.b32 u1, {h1,h1}; mul.bf16x2 v0, v0, u1;\n" \
    "mma.sync.aligned.m16n8k16.row.col.f32.bf16.bf16.f32 {%96,%97,%98,%99}, {a0,a1,a2,a3}, {v0,v1}, {%96,%97,%98,%99};\n" \
    "fma.rn.f32 z2, z2, t1, z2;\n" \
    "mov.b32 {h0,h1}, z2; mov.b32 u1, {h1,h1}; mul.bf16x2 v2, v2, u1;\n" \
    "mov.b32 {h0,h1}, z2; mov.b32 u1, {h1,h1}; mul.bf16x2 v3, v3, u1;\n" \
    "mma.sync.aligned.m16n8k16.row.col.f32.bf16.bf16.f32 {%100,%101,%102,%103}, {a0,a1,a2,a3}, {v2,v3}, {%100,%101,%102,%103};\n" \
    "and.b32 u2, ex, 1; mbarrier.test_wait.parity.shared::cta.b64 pr, [e3], u2;\n" \
    "ld.shared.v4.u32 {v12,v13,v14,v15}, [ca1+640];\n" \
    "mma.sync.aligned.m16n8k8.row.col.f32.bf16.bf16.f32 {z4,z5,z6,z7}, {%167,%168}, {ef}, {fz,fz,fz,fz};\n" \
    "fma.rn.f32 z1, z1, t2, z1;\n" \
    "mov.b32 {h0,h1}, z1; mov.b32 u1, {h1,h1}; mul.bf16x2 v5, v5, u1;\n" \
    "shr.u32 u2, ex, 16; add.u32 na0, %171, u2;\n" \
    "mov.b32 {h0,h1}, z1; mov.b32 u1, {h1,h1}; mul.bf16x2 v4, v4, u1;\n" \
    "tanh.approx.f32 t4, z4;\n" \
    "tanh.approx.f32 t5, z6;\n" \
    "mma.sync.aligned.m16n8k16.row.col.f32.bf16.bf16.f32 {%104,%105,%106,%107}, {a0,a1,a2,a3}, {v4,v5}, {%104,%105,%106,%107};\n" \
    "st.volatile.shared.u32 [%177], %160;\n" \
    "fma.rn.f32 z3, z3, t3, z3;\n" \
    "mov.b32 {h0,h1}, z3; mov.b32 u1, {h1,h1}; mul.bf16x2 v6, v6, u1;\n" \
    "mov.b32 {h0,h1}, z3; mov.b32 u1, {h1,h1}; mul.bf16x2 v7, v7, u1;\n" \
    "mma.sync.aligned.m16n8k16.row.col.f32.bf16.bf16.f32 {%108,%109,%110,%111}, {a0,a1,a2,a3}, {v6,v7}, {%108,%109,%110,%111};\n" \
    "fma.rn.f32 z4, z4, t4, z4;\n" \
    "tanh.approx.f32 t6, z5;\n" \
    "@pr ld.shared.v4.u32 {v0,v1,v2,v3}, [na0+0];\n" \
    "mov.b32 {h0,h1}, z4; mov.b32 u1, {h1,h1}; mul.bf16x2 v8, v8, u1;\n" \
    "fma.rn.f32 z6, z6, t5, z6;\n" \
    "mov.b32 {h0,h1}, z4; mov.b32 u1, {h1,h1}; mul.bf16x2 v9, v9, u1;\n" \
    "mov.b32 {h0,h1}, z6; mov.b32 u1, {h1,h1}; mul.bf16x2 v10, v10, u1;\n" \
    "mov.b32 {h0,h1}, z6; mov.b32 u1, {h1,h1}; mul.bf16x2 v11, v11, u1;\n" \
    "tanh.approx.f32 t7, z7;\n" \
    "mma.sync.aligned.m16n8k16.row.col.f32.bf16.bf16.f32 {%116,%117,%118,%119}, {a0,a1,a2,a3}, {v10,v11}, {%116,%117,%118,%119};\n" \
    "mma.sync.aligned.m16n8k16.row.col.f32.bf16.bf16.f32 {%112,%113,%114,%115}, {a0,a1,a2,a3}, {v8,v9}, {%112,%113,%114,%115};\n" \
    "mma.sync.aligned.m16n8k8.row.col.f32.bf16.bf16.f32 {z0,z1,z2,z3}, {%161,%162}, {rx}, {fz,fz,fz,fz};\n" \
    "mma.sync.aligned.m16n8k8.row.col.f32.bf16.bf16.f32 {y0,y1,y2,y3}, {%169,%170}, {ry}, {fz,fz,fz,fz};\n" \
    "and.b32 u2, ex, 6; setp.eq.and.u32 q0, u2, 2, pr; setp.eq.and.u32 q1, u2, 4, pr; setp.eq.and.u32 q2, u2, 6, pr;\n" \
    "ld.shared.v4.u32 {e0,e1,ex,e3}, [%160+16];\n" \
    "tanh.approx.f32 t0, z0;\n" \
    "fma.rn.f32 z5, z5, t6, z5;\n" \
    "mov.b32 {h0,h1}, z5; mov.b32 u1, {h1,h1}; mul.bf16x2 v13, v13, u1;\n" \
    "tanh.approx.f32 t1, z2;\n" \
    "@pr ld.shared.v4.u32 {v4,v5,v6,v7}, [na0+128];\n" \
    "mov.b32 {h0,h1}, z5; mov.b32 u1, {h1,h1}; mul.bf16x2 v12, v12, u1;\n" \
    "mma.sync.aligned.m16n8k16.row.col.f32.bf16.bf16.f32 {%120,%121,%122,%123}, {a0,a1,a2,a3}, {v12,v13}, {%120,%121,%122,%123};\n" \
    "fma.rn.f32 z7, z7, t7, z7;\n" \
    "mov.b32 {h0,h1}, z7; mov.b32 u1, {h1,h1}; mul.bf16x2 v14, v14, u1;\n" \
    "mov.b32 {h0,h1}, z7; mov.b32 u1, {h1,h1}; mul.bf16x2 v15, v15, u1;\n" \
    "mma.sync.aligned.m16n8k16.row.col.f32.bf16.bf16.f32 {%124,%125,%126,%127}, {a0,a1,a2,a3}, {v14,v15}, {%124,%125,%126,%127};\n" \
    "cvt.rn.bf16x2.f32 b0, y2, y0; cvt.rn.bf16x2.f32 b1, y3, y1;\n" \
    "selp.b32 a0, b0, 0, p0; selp.b32 a1, b0, 0, p1; selp.b32 a2, b1, 0, p0; selp.b32 a3, b1, 0, p1;\n" \
    "@q0 bra.uni S0;\n" \
    "@q1 bra.uni S1;\n" \
    "@!q2 bra.uni SLOW;\n" \
    "bra.uni S2;\n" \
    "SLOW:\n" \
    "ld.shared.v2.u32 {gx,gy}, [%160+8];\n" \
    "and.b32 u2, gx, 1; and.b32 gx, gx, 6; setp.eq.u32 q0, gx, 0;\n" \
    "@q0 bra.uni DONE;\n" \
    "mov.b32 cnt, 0;\n" \
    "XW:\n" \
    "mbarrier.try_wait.parity.shared::cta.b64 pr, [gy], u2;\n" \
    "add.u32 cnt, cnt, 1; setp.lt.and.u32 q0, cnt, 1048576, !pr;\n" \
    "@q0 bra.uni XW;\n" \
    "ld.shared.v4.u32 {v0,v1,v2,v3}, [na0+0];\n" \
    "ld.shared.v4.u32 {v4,v5,v6,v7}, [na0+128];\n" \
    "setp.eq.u32 q0, gx, 2; setp.eq.u32 q1, gx, 4;\n" \
    "@q0 bra.uni S0;\n" \
    "@q1 bra.uni S1;\n" \
    "bra.uni S2;\n" \
    "DONE:\n" \
    "}\n" \
    ""
#define MAIN_LOOP_ACC(A) \
    "+f"(A[0][0]), "+f"(A[0][1]), "+f"(A[0][2]), "+f"(A[0][3]), "+f"(A[1][0]), "+f"(A[1][1]), "+f"(A[1][2]), "+f"(A[1][3]), \
    "+f"(A[2][0]), "+f"(A[2][1]), "+f"(A[2][2]), "+f"(A[2][3]), "+f"(A[3][0]), "+f"(A[3][1]), "+f"(A[3][2]), "+f"(A[3][3]), \
    "+f"(A[4][0]), "+f"(A[4][1]), "+f"(A[4][2]), "+f"(A[4][3]), "+f"(A[5][0]), "+f"(A[5][1]), "+f"(A[5][2]), "+f"(A[5][3]), \
    "+f"(A[6][0]), "+f"(A[6][1]), "+f"(A[6][2]), "+f"(A[6][3]), "+f"(A[7][0]), "+f"(A[7][1]), "+f"(A[7][2]), "+f"(A[7][3]), \
    "+f"(A[8][0]), "+f"(A[8][1]), "+f"(A[8][2]), "+f"(A[8][3]), "+f"(A[9][0]), "+f"(A[9][1]), "+f"(A[9][2]), "+f"(A[9][3]), \
    "+f"(A[10][0]), "+f"(A[10][1]), "+f"(A[10][2]), "+f"(A[10][3]), "+f"(A[11][0]), "+f"(A[11][1]), "+f"(A[11][2]), "+f"(A[11][3]), \
    "+f"(A[12][0]), "+f"(A[12][1]), "+f"(A[12][2]), "+f"(A[12][3]), "+f"(A[13][0]), "+f"(A[13][1]), "+f"(A[13][2]), "+f"(A[13][3]), \
    "+f"(A[14][0]), "+f"(A[14][1]), "+f"(A[14][2]), "+f"(A[14][3]), "+f"(A[15][0]), "+f"(A[15][1]), "+f"(A[15][2]), "+f"(A[15][3]), \
    "+f"(A[16][0]), "+f"(A[16][1]), "+f"(A[16][2]), "+f"(A[16][3]), "+f"(A[17][0]), "+f"(A[17][1]), "+f"(A[17][2]), "+f"(A[17][3]), \
    "+f"(A[18][0]), "+f"(A[18][1]), "+f"(A[18][2]), "+f"(A[18][3]), "+f"(A[19][0]), "+f"(A[19][1]), "+f"(A[19][2]), "+f"(A[19][3]), \
    "+f"(A[20][0]), "+f"(A[20][1]), "+f"(A[20][2]), "+f"(A[20][3]), "+f"(A[21][0]), "+f"(A[21][1]), "+f"(A[21][2]), "+f"(A[21][3]), \
    "+f"(A[22][0]), "+f"(A[22][1]), "+f"(A[22][2]), "+f"(A[22][3]), "+f"(A[23][0]), "+f"(A[23][1]), "+f"(A[23][2]), "+f"(A[23][3]), \
    "+f"(A[24][0]), "+f"(A[24][1]), "+f"(A[24][2]), "+f"(A[24][3]), "+f"(A[25][0]), "+f"(A[25][1]), "+f"(A[25][2]), "+f"(A[25][3]), \
    "+f"(A[26][0]), "+f"(A[26][1]), "+f"(A[26][2]), "+f"(A[26][3]), "+f"(A[27][0]), "+f"(A[27][1]), "+f"(A[27][2]), "+f"(A[27][3]), \
    "+f"(A[28][0]), "+f"(A[28][1]), "+f"(A[28][2]), "+f"(A[28][3]), "+f"(A[29][0]), "+f"(A[29][1]), "+f"(A[29][2]), "+f"(A[29][3]), \
    "+f"(A[30][0]), "+f"(A[30][1]), "+f"(A[30][2]), "+f"(A[30][3]), "+f"(A[31][0]), "+f"(A[31][1]), "+f"(A[31][2]), "+f"(A[31][3]), \
    "+f"(A[32][0]), "+f"(A[32][1]), "+f"(A[32][2]), "+f"(A[32][3]), "+f"(A[33][0]), "+f"(A[33][1]), "+f"(A[33][2]), "+f"(A[33][3]), \
    "+f"(A[34][0]), "+f"(A[34][1]), "+f"(A[34][2]), "+f"(A[34][3]), "+f"(A[35][0]), "+f"(A[35][1]), "+f"(A[35][2]), "+f"(A[35][3]), \
    "+f"(A[36][0]), "+f"(A[36][1]), "+f"(A[36][2]), "+f"(A[36][3]), "+f"(A[37][0]), "+f"(A[37][1]), "+f"(A[37][2]), "+f"(A[37][3]), \
    "+f"(A[38][0]), "+f"(A[38][1]), "+f"(A[38][2]), "+f"(A[38][3]), "+f"(A[39][0]), "+f"(A[39][1]), "+f"(A[39][2]), "+f"(A[39][3])
#define PRODUCER_PTX \
    "{\n" \
    ".reg .b32 r<4>, d, b, c, t, w, n; .reg .pred p, q;\n" \
    "mov.b32 n, 0;\n" \
    "TOP:\n" \
    "ld.shared.v4.u32 {r0,r1,r2,r3}, [%0+%16];\n" \
    "ld.shared.u16 t, [%0+72]; setp.ge.u32 q, %0, %10;\n" \
    "mov.u32 c, %%globaltimer_lo; sub.s32 c, c, %11; sub.s32 c, c, t; setp.ge.s32 p, c, 0;\n" \
    "@p bra.uni G0;\n" \
    "T0:\n" \
    "nanosleep.u32 64;\n" \
    "mov.u32 c, %%globaltimer_lo; sub.s32 c, c, %11; sub.s32 c, c, t; setp.lt.s32 p, c, 0;\n" \
    "@p bra.uni T0;\n" \
    "G0:\n" \
    "ld.volatile.shared.u32 w, [%9]; setp.lt.or.u32 p, w, %0, q;\n" \
    "@p bra.uni W0;\n" \
    "add.u32 b, %3, 0;\n" \
    "mbarrier.arrive.expect_tx.shared::cta.b64 _, [b], %12;\n" \
    "add.u32 d, %2, 0*%15+1024;\n" \
    "cp.async.bulk.tensor.2d.shared::cluster.global.tile.mbarrier::complete_tx::bytes [d], [%4, {%5, r0}], [b];\n" \
    "add.u32 d, %2, 1*%15+1024;\n" \
    "cp.async.bulk.tensor.2d.shared::cluster.global.tile.mbarrier::complete_tx::bytes [d], [%4, {%6, r1}], [b];\n" \
    "add.u32 d, %2, 2*%15+1024;\n" \
    "cp.async.bulk.tensor.2d.shared::cluster.global.tile.mbarrier::complete_tx::bytes [d], [%4, {%7, r2}], [b];\n" \
    "add.u32 d, %2, 3*%15+1024;\n" \
    "cp.async.bulk.tensor.2d.shared::cluster.global.tile.mbarrier::complete_tx::bytes [d], [%4, {%8, r3}], [b];\n" \
    "add.u32 %0, %0, 16;\n" \
    "ld.shared.v4.u32 {r0,r1,r2,r3}, [%0+%16];\n" \
    "ld.shared.u16 t, [%0+72]; setp.ge.u32 q, %0, %10;\n" \
    "mov.u32 c, %%globaltimer_lo; sub.s32 c, c, %11; sub.s32 c, c, t; setp.ge.s32 p, c, 0;\n" \
    "@p bra.uni G1;\n" \
    "T1:\n" \
    "nanosleep.u32 64;\n" \
    "mov.u32 c, %%globaltimer_lo; sub.s32 c, c, %11; sub.s32 c, c, t; setp.lt.s32 p, c, 0;\n" \
    "@p bra.uni T1;\n" \
    "G1:\n" \
    "ld.volatile.shared.u32 w, [%9]; setp.lt.or.u32 p, w, %0, q;\n" \
    "@p bra.uni W1;\n" \
    "add.u32 b, %3, 8;\n" \
    "mbarrier.arrive.expect_tx.shared::cta.b64 _, [b], %12;\n" \
    "add.u32 d, %2, 0*%15+2048;\n" \
    "cp.async.bulk.tensor.2d.shared::cluster.global.tile.mbarrier::complete_tx::bytes [d], [%4, {%5, r0}], [b];\n" \
    "add.u32 d, %2, 1*%15+2048;\n" \
    "cp.async.bulk.tensor.2d.shared::cluster.global.tile.mbarrier::complete_tx::bytes [d], [%4, {%6, r1}], [b];\n" \
    "add.u32 d, %2, 2*%15+2048;\n" \
    "cp.async.bulk.tensor.2d.shared::cluster.global.tile.mbarrier::complete_tx::bytes [d], [%4, {%7, r2}], [b];\n" \
    "add.u32 d, %2, 3*%15+2048;\n" \
    "cp.async.bulk.tensor.2d.shared::cluster.global.tile.mbarrier::complete_tx::bytes [d], [%4, {%8, r3}], [b];\n" \
    "add.u32 %0, %0, 16;\n" \
    "ld.shared.v4.u32 {r0,r1,r2,r3}, [%0+%16];\n" \
    "ld.shared.u16 t, [%0+72]; setp.ge.u32 q, %0, %10;\n" \
    "mov.u32 c, %%globaltimer_lo; sub.s32 c, c, %11; sub.s32 c, c, t; setp.ge.s32 p, c, 0;\n" \
    "@p bra.uni G2;\n" \
    "T2:\n" \
    "nanosleep.u32 64;\n" \
    "mov.u32 c, %%globaltimer_lo; sub.s32 c, c, %11; sub.s32 c, c, t; setp.lt.s32 p, c, 0;\n" \
    "@p bra.uni T2;\n" \
    "G2:\n" \
    "ld.volatile.shared.u32 w, [%9]; setp.lt.or.u32 p, w, %0, q;\n" \
    "@p bra.uni W2;\n" \
    "add.u32 b, %3, 16;\n" \
    "mbarrier.arrive.expect_tx.shared::cta.b64 _, [b], %12;\n" \
    "add.u32 d, %2, 0*%15+3072;\n" \
    "cp.async.bulk.tensor.2d.shared::cluster.global.tile.mbarrier::complete_tx::bytes [d], [%4, {%5, r0}], [b];\n" \
    "add.u32 d, %2, 1*%15+3072;\n" \
    "cp.async.bulk.tensor.2d.shared::cluster.global.tile.mbarrier::complete_tx::bytes [d], [%4, {%6, r1}], [b];\n" \
    "add.u32 d, %2, 2*%15+3072;\n" \
    "cp.async.bulk.tensor.2d.shared::cluster.global.tile.mbarrier::complete_tx::bytes [d], [%4, {%7, r2}], [b];\n" \
    "add.u32 d, %2, 3*%15+3072;\n" \
    "cp.async.bulk.tensor.2d.shared::cluster.global.tile.mbarrier::complete_tx::bytes [d], [%4, {%8, r3}], [b];\n" \
    "add.u32 %0, %0, 16;\n" \
    "ld.shared.v4.u32 {r0,r1,r2,r3}, [%0+%16];\n" \
    "ld.shared.u16 t, [%0+72]; setp.ge.u32 q, %0, %10;\n" \
    "mov.u32 c, %%globaltimer_lo; sub.s32 c, c, %11; sub.s32 c, c, t; setp.ge.s32 p, c, 0;\n" \
    "@p bra.uni G3;\n" \
    "T3:\n" \
    "nanosleep.u32 64;\n" \
    "mov.u32 c, %%globaltimer_lo; sub.s32 c, c, %11; sub.s32 c, c, t; setp.lt.s32 p, c, 0;\n" \
    "@p bra.uni T3;\n" \
    "G3:\n" \
    "ld.volatile.shared.u32 w, [%9]; setp.lt.or.u32 p, w, %0, q;\n" \
    "@p bra.uni W3;\n" \
    "add.u32 b, %3, 24;\n" \
    "mbarrier.arrive.expect_tx.shared::cta.b64 _, [b], %12;\n" \
    "add.u32 d, %2, 0*%15+4096;\n" \
    "cp.async.bulk.tensor.2d.shared::cluster.global.tile.mbarrier::complete_tx::bytes [d], [%4, {%5, r0}], [b];\n" \
    "add.u32 d, %2, 1*%15+4096;\n" \
    "cp.async.bulk.tensor.2d.shared::cluster.global.tile.mbarrier::complete_tx::bytes [d], [%4, {%6, r1}], [b];\n" \
    "add.u32 d, %2, 2*%15+4096;\n" \
    "cp.async.bulk.tensor.2d.shared::cluster.global.tile.mbarrier::complete_tx::bytes [d], [%4, {%7, r2}], [b];\n" \
    "add.u32 d, %2, 3*%15+4096;\n" \
    "cp.async.bulk.tensor.2d.shared::cluster.global.tile.mbarrier::complete_tx::bytes [d], [%4, {%8, r3}], [b];\n" \
    "add.u32 %0, %0, 16;\n" \
    "ld.shared.v4.u32 {r0,r1,r2,r3}, [%0+%16];\n" \
    "ld.shared.u16 t, [%0+72]; setp.ge.u32 q, %0, %10;\n" \
    "mov.u32 c, %%globaltimer_lo; sub.s32 c, c, %11; sub.s32 c, c, t; setp.ge.s32 p, c, 0;\n" \
    "@p bra.uni G4;\n" \
    "T4:\n" \
    "nanosleep.u32 64;\n" \
    "mov.u32 c, %%globaltimer_lo; sub.s32 c, c, %11; sub.s32 c, c, t; setp.lt.s32 p, c, 0;\n" \
    "@p bra.uni T4;\n" \
    "G4:\n" \
    "ld.volatile.shared.u32 w, [%9]; setp.lt.or.u32 p, w, %0, q;\n" \
    "@p bra.uni W4;\n" \
    "add.u32 b, %3, 32;\n" \
    "mbarrier.arrive.expect_tx.shared::cta.b64 _, [b], %12;\n" \
    "add.u32 d, %2, 0*%15+5120;\n" \
    "cp.async.bulk.tensor.2d.shared::cluster.global.tile.mbarrier::complete_tx::bytes [d], [%4, {%5, r0}], [b];\n" \
    "add.u32 d, %2, 1*%15+5120;\n" \
    "cp.async.bulk.tensor.2d.shared::cluster.global.tile.mbarrier::complete_tx::bytes [d], [%4, {%6, r1}], [b];\n" \
    "add.u32 d, %2, 2*%15+5120;\n" \
    "cp.async.bulk.tensor.2d.shared::cluster.global.tile.mbarrier::complete_tx::bytes [d], [%4, {%7, r2}], [b];\n" \
    "add.u32 d, %2, 3*%15+5120;\n" \
    "cp.async.bulk.tensor.2d.shared::cluster.global.tile.mbarrier::complete_tx::bytes [d], [%4, {%8, r3}], [b];\n" \
    "add.u32 %0, %0, 16;\n" \
    "setp.lt.u32 p, r0, %1;\n" \
    "@p bra.uni TOP;\n" \
    "mov.b32 %1, 0xffffffff; setp.ne.u32 p, %14, 0;\n" \
    "@p cp.async.bulk.prefetch.L2.global [%13], %14;\n" \
    "bra.uni TOP;\n" \
    "W0:\n" \
    "add.u32 n, n, 1; setp.lt.and.u32 p, n, 0x1000000, !q;\n" \
    "@p bra.uni G0;\n" \
    "bra.uni END;\n" \
    "W1:\n" \
    "add.u32 n, n, 1; setp.lt.and.u32 p, n, 0x1000000, !q;\n" \
    "@p bra.uni G1;\n" \
    "bra.uni END;\n" \
    "W2:\n" \
    "add.u32 n, n, 1; setp.lt.and.u32 p, n, 0x1000000, !q;\n" \
    "@p bra.uni G2;\n" \
    "bra.uni END;\n" \
    "W3:\n" \
    "add.u32 n, n, 1; setp.lt.and.u32 p, n, 0x1000000, !q;\n" \
    "@p bra.uni G3;\n" \
    "bra.uni END;\n" \
    "W4:\n" \
    "add.u32 n, n, 1; setp.lt.and.u32 p, n, 0x1000000, !q;\n" \
    "@p bra.uni G4;\n" \
    "bra.uni END;\n" \
    "END:\n" \
    "}\n" \
    ""

__device__ __forceinline__ void wgmma_n128(float (&d)[64], const uint32_t (&a)[4], uint64_t desc, int acc) {
    asm volatile("{\n\t.reg .pred p;\n\tsetp.ne.u32 p, %69, 0;\n\t"
        "wgmma.mma_async.sync.aligned.m64n128k16.f32.bf16.bf16 {%0,%1,%2,%3,%4,%5,%6,%7,%8,%9,%10,%11,%12,%13,%14,%15,"
        "%16,%17,%18,%19,%20,%21,%22,%23,%24,%25,%26,%27,%28,%29,%30,%31,%32,%33,%34,%35,%36,%37,%38,%39,%40,%41,%42,%43,%44,%45,%46,%47,"
        "%48,%49,%50,%51,%52,%53,%54,%55,%56,%57,%58,%59,%60,%61,%62,%63}, {%64,%65,%66,%67}, %68, p, 1, 1, 1;\n\t}"
        : "+f"(d[0]), "+f"(d[1]), "+f"(d[2]), "+f"(d[3]), "+f"(d[4]), "+f"(d[5]), "+f"(d[6]), "+f"(d[7]),
          "+f"(d[8]), "+f"(d[9]), "+f"(d[10]), "+f"(d[11]), "+f"(d[12]), "+f"(d[13]), "+f"(d[14]), "+f"(d[15]),
          "+f"(d[16]), "+f"(d[17]), "+f"(d[18]), "+f"(d[19]), "+f"(d[20]), "+f"(d[21]), "+f"(d[22]), "+f"(d[23]),
          "+f"(d[24]), "+f"(d[25]), "+f"(d[26]), "+f"(d[27]), "+f"(d[28]), "+f"(d[29]), "+f"(d[30]), "+f"(d[31]),
          "+f"(d[32]), "+f"(d[33]), "+f"(d[34]), "+f"(d[35]), "+f"(d[36]), "+f"(d[37]), "+f"(d[38]), "+f"(d[39]),
          "+f"(d[40]), "+f"(d[41]), "+f"(d[42]), "+f"(d[43]), "+f"(d[44]), "+f"(d[45]), "+f"(d[46]), "+f"(d[47]),
          "+f"(d[48]), "+f"(d[49]), "+f"(d[50]), "+f"(d[51]), "+f"(d[52]), "+f"(d[53]), "+f"(d[54]), "+f"(d[55]),
          "+f"(d[56]), "+f"(d[57]), "+f"(d[58]), "+f"(d[59]), "+f"(d[60]), "+f"(d[61]), "+f"(d[62]), "+f"(d[63])
        : "r"(a[0]), "r"(a[1]), "r"(a[2]), "r"(a[3]), "l"(desc), "r"(acc));
}

#define YFP 3
#define FEN 0
#define KEYM 1
#define PAIRS 6
#define PT0 3500
#define PDT 37.3
#define NSLEEP 64
#define PFA 8000
template <int ID, int COUNT> __device__ __forceinline__ void bar_sync() { asm volatile("bar.sync %0, %1;" ::"n"(ID), "n"(COUNT) : "memory"); }
template <int ID, int COUNT> __device__ __forceinline__ void bar_arrive() { asm volatile("bar.arrive %0, %1;" ::"n"(ID), "n"(COUNT) : "memory"); }
#define REL "relaxed"
__device__ __forceinline__ void await(const uint32_t* p, uint32_t n) {
    uint32_t v;
    int guard = 0;
    do asm volatile("ld.relaxed.gpu.global.u32 %0, [%1];" : "=r"(v) : "l"(p) : "memory");
    while (__any_sync(0xffffffffu, v < n) && ++guard < (1 << 20));
}
template <int BYTES>
__device__ __forceinline__ void fill(uint32_t addr, uint4 v, int tid) {
#pragma unroll
    for (int r = 0; r < (BYTES / 16 + NT - 1) / NT; r++)
        sts128_if((r + 1) * NT <= BYTES / 16 || r * NT + tid < BYTES / 16, addr + (r * NT + tid) * 16, v);
}

__device__ __forceinline__ uint32_t group_cap(uint32_t key, int lane) {
    return __reduce_add_sync(0xffffffffu, min(key >> 5, GK)) > KCAP ? KCAP / NG : lane < 16 ? GK : 128 - 2 * GK;
}
__device__ __forceinline__ bool next_excess(const Scratch* scr, const __nv_bfloat16* x, uint32_t va0) {
    uint32_t tid, cta;
    asm volatile("mov.u32 %0, %tid.x;" : "=r"(tid));
    asm volatile("mov.u32 %0, %ctaid.x;" : "=r"(cta));
    const int lane = tid & 31, wl = tid >> 5;
    const uint32_t bar_w = sb + SM_BAR + NW * S * 8, own = sb + SM_SRC + wl * 128, st = sb + SM_STATE + wl * 16;
    mbar_wait(bar_w, 0);
    __threadfence();
    const uint32_t grp = lds32(sb + SM_MISC + 64 + wl * 4);
    uint4 c = lds128(st);
    __syncwarp();
    for (; c.x <= NCTA; c.x++, c.y = 0) {
        if (c.y == 0 && c.z == 0)
            c.x += __reduce_min_sync(0xffffffffu, c.x + lane >= NCTA || (lds32(sb + SM_SEG + min(c.x + lane, NCTA - 1) * 4) >> 12) > MBE ? lane : 31);
        const uint32_t loc = lds32(sb + SM_SEG + min(c.x, NCTA - 1) * 4);
        const int n = c.x < NCTA ? (int)(loc >> 12) - MBE : lds32(sb + SM_MISC + 12);
        for (; (int)c.y < n; c.y += 32, c.z = 0) {
            uint2 u = make_uint2(0xffffffffu, c.x * SLICE + (loc & 0xfff) + MBE + c.y + lane);
            if ((int)c.y + lane < n) {
                if (c.x < NCTA) u.x = __ldcg(scr->ss + u.y);
                else u = __ldcg(scr->exc + cta * MBW + c.y + lane);
            }
            const uint32_t gw = u.x >> 25 & 31, ja = gw == (grp & 31) ? 1 : gw == (grp >> 5 & 31) ? 2 : gw == grp >> 10 ? 3 : 0;
            unsigned m = __ballot_sync(0xffffffffu, ja) & ~c.z;
            if (!m) continue;
            const uint32_t jf = __shfl_sync(0xffffffffu, ja, __ffs(m) - 1);
            m &= __ballot_sync(0xffffffffu, ja == jf);
            const uint32_t from = __fns(m, 0, (lane & 3) + 1);
            const bool pad = from > 31;
            c.z |= __reduce_or_sync(0xffffffffu, pad ? 0 : 1u << from);
            u.x = __shfl_sync(0xffffffffu, u.x, pad ? __ffs(m) - 1 : from);
            u.y = __shfl_sync(0xffffffffu, u.y, from);
            const uint32_t slot = (lds32(sb + SM_MISC + 32 + wl * 4) / 64 + 1) % S;
            if (lane < 4) {
                sts128_if(true, own + 64 + lane * 16, pad ? make_uint4(0, 0, 0, 0) : ldg128_relaxed(scr->rec + u.y));
                asm volatile("st.shared.u16 [%0], %1;" ::"r"(own + lane * 2), "h"((uint16_t)((own + 64 + lane * 16 - sb - SM_REC) | 1u << (u.x & 3))) : "memory");
                sts32_if(lane == 0, own + 8, jf << 1 | slot << 26);
                sts32_if(lane == 0, own + 12, bar_w);
                sts128_if(lane == 0, own + 16, make_uint4(0, 0, 0, bar_w));
                sts128_if(lane == 0, st, c);
            }
#pragma unroll 1
            for (int k = 0; k < 8; k++)
                sts128_if(true, (va0 ^ (k & 4) * 8) + slot * 1024 + (k & 1) * 128 + (k & 2) * 256,
                          ldg128_relaxed(reinterpret_cast<const uint4*>(x) + (size_t)(u.x >> 3 & 0x3fff) * 64 + chunk_of(k, lane >> 2)));
            __syncwarp();
            return true;
        }
    }
    return false;
}

template <int MODE>
__global__ void __launch_bounds__(NT, 1)
tfn_kernel(const __grid_constant__ CUtensorMap xmap, const __grid_constant__ CUtensorMap wmap, const __nv_bfloat16* __restrict__ x,
           const int* __restrict__ src, const int* __restrict__ dst,
           const uint2* __restrict__ Y, const uint2* __restrict__ ef, const __nv_bfloat16* __restrict__ w_rad,
           const __nv_bfloat16* __restrict__ cg, const __nv_bfloat16* __restrict__ w_mix,
           __nv_bfloat16* __restrict__ out, Scratch* scr, int N, int E, int slice, int npc, uint32_t npc_magic,
           uint32_t bin_magic, uint32_t pace) {
    extern __shared__ __align__(1024) uint8_t smem[];
    const int tid = threadIdx.x, lane = tid & 31, warp = __shfl_sync(0xffffffffu, tid >> 5, 0);
    const int cta = blockIdx.x;
    if ((uint32_t)__cvta_generic_to_shared(smem) != sb) __trap();
    const uint32_t bar_w = sb + SM_BAR + NW * S * 8, bar_raw = bar_w + 8, bar_rec = bar_w + 16, bar_mb = bar_w + 24;
    ANCHOR(0);
    auto prefetch_x = [&](int chunk) {
        const int row = (chunk * NCTA + cta) * 8;
        if (row < N)
            asm volatile("cp.async.bulk.prefetch.L2.global [%0], %1;" ::"l"(x + (size_t)row * 512), "r"(min(8, N - row) * 1024));
    };

    const int e0 = cta * slice, ne = min(E - e0, slice);
    uint32_t a_d[RA], a_s[RA];
    uint32_t tag = 0;
    if (MODE & 1) {
        const int q = min(e0 / 4 + tid, (E - 1) >> 2), e = min(e0 + 4 * NT + tid, E - 1);
        const int4 d4 = __ldcs(reinterpret_cast<const int4*>(dst) + q);
        a_d[4] = __ldcs(dst + e);
        const int4 s4 = __ldcs(reinterpret_cast<const int4*>(src) + q);
        a_s[4] = __ldcs(src + e);
        a_d[0] = d4.x; a_d[1] = d4.y; a_d[2] = d4.z; a_d[3] = d4.w;
        a_s[0] = s4.x; a_s[1] = s4.y; a_s[2] = s4.z; a_s[3] = s4.w;
    }
    if (MODE == 3) asm volatile("ld.relaxed.gpu.global.u32 %0, [%1];" : "=r"(tag) : "l"(&scr->epoch) : "memory");
    auto load_raw = [&]() {
        const int bytes = max((ne + 1) >> 1, 0) * 16;
        asm volatile("mbarrier.arrive.expect_tx.shared::cta.b64 _, [%0], %1;" ::"r"(bar_raw), "r"(2 * bytes) : "memory");
        if (bytes > 0) {
            asm volatile("cp.async.bulk.shared::cluster.global.mbarrier::complete_tx::bytes [%0], [%1], %2, [%3];"
                         ::"r"(sb + SM_RAWY), "l"(Y + e0), "r"(bytes), "r"(bar_raw) : "memory");
            asm volatile("cp.async.bulk.shared::cluster.global.mbarrier::complete_tx::bytes [%0], [%1], %2, [%3];"
                         ::"r"(sb + SM_RAWF), "l"(ef + e0), "r"(bytes), "r"(bar_raw) : "memory");
        }
    };
    if (elect_one()) {
#pragma unroll
        for (int i = 0; i < S; i++)
            if (warp >= NW) mbar_init(sb + SM_BAR + ((warp - NW) * S + i) * 8, 1);
        if (warp == 0) {
            mbar_init(bar_w, NW);
            mbar_init(bar_raw, 1);
            mbar_init(bar_rec, NW);
            mbar_init(bar_mb, 1);
            if ((MODE & 1) && YFP == 0) load_raw();
        }
        asm volatile("fence.proxy.async.shared::cta;" ::: "memory");
        if (warp == 1 && (MODE & 2)) {
            asm volatile("prefetch.tensormap [%0];" ::"l"(&xmap) : "memory");
            asm volatile("prefetch.tensormap [%0];" ::"l"(&wmap) : "memory");
            asm volatile("cp.async.bulk.prefetch.L2.global [%0], 1024;" ::"l"(w_rad));
            asm volatile("cp.async.bulk.prefetch.L2.global [%0], 128;" ::"l"(cg));
        }
    }
    fill<SM_DUM - SM_HIST>(sb + SM_HIST, make_uint4(0, 0, 0, 0), tid);
    if (MODE & 1) {
        const uint32_t em = EMPTY | lane << (BSH + 2);
        fill<NCTA * ASTR * 4>(sb + SM_AMB, make_uint4(em, em + (1 << BSH), em + (2 << BSH), em + (3 << BSH)), tid);
    }
    sts32_if(tid < 128, sb + SM_DUM + tid * 4, 0x10000);
    if (MODE & 2) {
        const uint32_t pad = RCAP << 20 | N << 3;
        fill<SM_BAR - SM_ZERO>(sb + SM_ZERO, make_uint4(0, 0, 0, 0), tid);
        fill<NG * GK * 16>(sb + SM_KSG, make_uint4(pad, pad, pad, pad), tid);
    }
    __syncthreads();
    STAMP(15);
    if (MODE & 1) {
        if (YFP == 1 && tid == 0) load_raw();
        const uint32_t z = lds32(sb + SM_KEY + lane * 4);
        uint32_t cc[RA], rk[RA];
#pragma unroll
        for (int r = 0; r < RA; r++) {
            cc[r] = (r < 4 ? 4 * tid + r : 4 * NT + tid) < ne ? __umulhi(a_d[r], npc_magic + z) : NCTA;
            rk[r] = atoms_inc(sb + SM_HIST + cc[r] * 4);
        }
        if (YFP == 2 && tid == 0) load_raw();
#pragma unroll
        for (int r = 0; r < RA; r++) {
            const uint32_t l = a_d[r] - cc[r] * npc;
            a_s[r] = (l < 64 ? l >> 2 : (l >> 1) - 16) << 25 | ((a_s[r] * (bin_magic + z)) & ((NBIN - 1) << BSH)) | a_s[r] * (8 + z) | (l & (l < 64 ? 3 : 1));
            sts32_if(true, sb + SM_AMB + (cc[r] * ASTR + min(rk[r], MBE)) * 4, a_s[r]);
        }
        tag = (tag & 1) + 1;
        const uint32_t tg = tag << 30;
        STAMP(1);
        __syncthreads();
        auto send = [&](uint32_t* gp, uint4 v) {
            asm volatile("st.relaxed.gpu.global.v4.u32 [%0], {%1,%2,%3,%4};"
                         ::"l"(gp), "r"(v.x | tg), "r"(v.y | tg), "r"(v.z | tg), "r"(v.w | tg) : "memory");
        };
        if (YFP == 3 && warp == 14 && elect_one()) load_raw();
        uint32_t h = 0, off = 0;
        if (warp < 5) {
            h = lds32(sb + SM_HIST + min(tid, NCTA + 1) * 4);
            const bool real = tid < NCTA;
            const uint32_t inc = warp_incl_scan(real ? h : 0, lane);
            off = __shfl_sync(0xffffffffu, atoms_add(sb + SM_HIST + 109 * 4 + lane * 4, lane == 31 ? inc : 0), 31) + inc - h;
            sts32_if(tid <= NCTA, sb + SM_AOFF + tid * 4, real ? off : max(ne, 0));
        }
#pragma unroll
        for (int r = 0; r < 3; r++) {
            if (r == 2 && warp != 15) break;
            const uint32_t i = r < 2 ? r * NT + tid : 2 * NT + lane, c = i >> 3;
            send(scr->mb + c * MBW + cta * 32 + (i & 7) * 4, lds128(sb + SM_AMB + c * (ASTR * 4) + (i & 7) * 16));
        }
        if (tid < NCTA) {
            const uint4 v0 = lds128(sb + SM_AMB + tid * (ASTR * 4) + 128);
            uint4 v1 = lds128(sb + SM_AMB + tid * (ASTR * 4) + 144);
            v1.w = h << 12 | off;
            send(scr->mb + tid * MBW + MB1 + cta * 8, v0);
            send(scr->mb + tid * MBW + MB1 + cta * 8 + 4, v1);
        }
        STAMP(2);
        __syncthreads();
        if (MODE == 3 && tid == NT - 1) asm volatile("red.relaxed.gpu.global.add.u32 [%0], 1;" ::"l"(scr->sent + (tag & 1)) : "memory");
        if (YFP == 4 && warp == 6 && elect_one()) load_raw();
        uint32_t ap[2 * RA];
#pragma unroll
        for (int r = 0; r < RA; r++) ap[r] = rk[r] + lds32(sb + SM_AOFF + cc[r] * 4);
        if (max(max(max(rk[0], rk[1]), max(rk[2], rk[3])), rk[4]) >= MBE) {
#pragma unroll
            for (int r = 0; r < RA; r++)
                if (rk[r] >= MBE && cc[r] < NCTA) {
                    __stcg(scr->ss + cta * SLICE + ap[r], a_s[r]);
                    __threadfence();
                }
        }
        if (warp >= NW) {
            asm volatile("st.shared.v2.u32 [%0], {%1, %2};" ::"r"(sb + SM_AP + (tid - NH) * 8), "r"(ap[0] | ap[1] << 16), "r"(ap[2] | ap[3] << 16) : "memory");
            sts32_if(true, sb + SM_AP + NH * 8 + (tid - NH) * 4, ap[4]);
            bar_arrive<1, NT>();
        } else {
            bar_sync<1, NT>();
            const uint2 u = lds64(sb + SM_AP + tid * 8);
            ap[5] = u.x & 0xffff; ap[6] = u.x >> 16; ap[7] = u.y & 0xffff; ap[8] = u.y >> 16;
            ap[9] = lds32(sb + SM_AP + NH * 8 + tid * 4);
            const bool sw = lane & 4;
            mbar_wait(bar_raw, 0);
            STAMP(10);
#pragma unroll
            for (int hh = 0; hh < 2; hh++) {
                const uint32_t a = sb + SM_RAWY + (hh * NH + tid) * 32 + (lane & 4) * 4, b = sb + SM_RAWY + (4 * NT + hh * NH + tid) * 8;
                const uint4 y0 = lds128(a), f0 = lds128(a + SLICE * 8), y1 = lds128(a ^ 16), f1 = lds128((a ^ 16) + SLICE * 8);
                const uint2 y2 = lds64(b), f2 = lds64(b + SLICE * 8);
                const uint32_t* q = ap + hh * RA;
                sts128_if(true, sb + SM_AREC + (sw ? q[2] : q[0]) * 16, make_uint4(f0.x, y0.x, f0.y, y0.y));
                sts128_if(true, sb + SM_AREC + (sw ? q[3] : q[1]) * 16, make_uint4(f0.z, y0.z, f0.w, y0.w));
                sts128_if(true, sb + SM_AREC + (sw ? q[0] : q[2]) * 16, make_uint4(f1.x, y1.x, f1.y, y1.y));
                sts128_if(true, sb + SM_AREC + (sw ? q[1] : q[3]) * 16, make_uint4(f1.z, y1.z, f1.w, y1.w));
                sts128_if(true, sb + SM_AREC + q[4] * 16, make_uint4(f2.x, y2.x, f2.y, y2.y));
            }
            asm volatile("fence.proxy.async.shared::cta;" ::: "memory");
            bar_sync<7, NH>();
            STAMP(25);
            if (warp == NW - 1 && elect_one()) {
                if (ne > 0)
                    asm volatile("cp.async.bulk.global.shared::cta.bulk_group [%0], [%1], %2;"
                                 ::"l"(scr->rec + cta * SLICE), "r"(sb + SM_AREC), "r"(ne * 16) : "memory");
                asm volatile("cp.async.bulk.commit_group;" ::: "memory");
                asm volatile("cp.async.bulk.wait_group 0;" ::: "memory");
                STAMPT(26, NH - 32);
                if (MODE == 3) asm volatile("red." REL ".gpu.global.add.u32 [%0], 1;" ::"l"(scr->sent2 + (tag & 1)) : "memory");
            }
            __syncwarp();
        }
    } else {
        tag = 1;
    }
    if (!(MODE & 2)) return;
    const int wl = warp & (NW - 1);
    const uint32_t ring = sb + SM_RING + wl * (S * 1024);
    const uint32_t bars = sb + SM_BAR + wl * (S * 8);
    const uint32_t pos = bar_w + 32 + wl * 4;

    if (warp >= NW) {
        uint32_t ss[RL + 8], rk[RL + 7];
        const uint32_t sl = wl + 8 * lane;
        const uint32_t* mp = scr->mb + cta * MBW + wl * 32 + lane;
        const uint4* mq = reinterpret_cast<const uint4*>(scr->mb + cta * MBW + MB1) + min(sl, NCTA - 1) * 2;
        const uint32_t tg = tag << 30, empty = EMPTY | lane << BSH;
        if (wl == 0) {
            if (MODE == 3) await(scr->sent + (tag & 1), NCTA);
            STAMPT(11, NH);
            if (elect_one()) {
                asm volatile("mbarrier.arrive.expect_tx.shared::cta.b64 _, [%0], %1;" ::"r"(bar_mb), "n"(MBW * 4) : "memory");
                asm volatile("cp.async.bulk.shared::cluster.global.mbarrier::complete_tx::bytes [%0], [%1], %2, [%3];"
                             ::"r"(sb + SM_AMB), "l"(scr->mb + cta * MBW), "n"(MBW * 4), "r"(bar_mb) : "memory");
            }
            sts32_if(true, sb + SM_MISC + 4, timer32() + PT0);
        }
        mbar_wait(bar_mb, 0);
        STAMPT(3, NH);
        uint4 v0 = lds128(sb + SM_AMB + (MB1 + min(sl, NCTA - 1) * 8) * 4), v1 = lds128(sb + SM_AMB + (MB1 + min(sl, NCTA - 1) * 8) * 4 + 16);
#pragma unroll
        for (int r = 0; r < RL; r++) ss[r] = lds32(sb + SM_AMB + (r * NH + tid - NH) * 4);
        for (int guard = 0;; guard++) {
            ss[RL] = v0.x; ss[RL + 1] = v0.y; ss[RL + 2] = v0.z; ss[RL + 3] = v0.w;
            ss[RL + 4] = v1.x; ss[RL + 5] = v1.y; ss[RL + 6] = v1.z; ss[RL + 7] = v1.w;
            uint32_t bad = 0;
#pragma unroll
            for (int r = 0; r < RL + 8; r++) bad |= ss[r] ^ tg;
            if (!__any_sync(0xffffffffu, bad >> 30) || guard == 1 << 20) break;
#pragma unroll
            for (int r = 0; r < RL; r++) asm volatile("ld.relaxed.gpu.global.u32 %0, [%1];" : "=r"(ss[r]) : "l"(mp + r * NH) : "memory");
            v0 = ldg128_relaxed(mq);
            v1 = ldg128_relaxed(mq + 1);
        }
        STAMPT(4, NH);
        if (wl + 8 * (RL - 1) >= NCTA) ss[RL - 1] = empty;
#pragma unroll
        for (int r = 0; r < RL; r++) rk[r] = atoms_add(sb + SM_BIN + (ss[r] >> (BSH - 2) & (NBIN * 128 - 4)), 4);
        const uint32_t cnt = sl < NCTA ? ss[RL + 7] >> 12 & 0xfff : 0;
        const bool late = __any_sync(0xffffffffu, cnt > 32);
        if (late) {
#pragma unroll
            for (int r = RL; r < RL + 7; r++) {
                if (r - RL + 32 >= cnt) ss[r] = empty;
                rk[r] = atoms_add(sb + SM_BIN + (ss[r] >> (BSH - 2) & (NBIN * 128 - 4)), 4);
            }
            sts32_if(cnt > MBE, sb + SM_MISC + 8, 1);
        }
        STAMPT(5, NH);
        bar_sync<3, NH>();
        uint32_t dof;
        {
            constexpr int Q = NBIN / 128;
            const uint32_t a = sb + SM_BIN + wl * (NBIN * 12) + lane * (16 * Q), sw = Q == 2 ? (lane & 4) * 4 : 0;
            uint4 u[3][Q];
            uint32_t sum[3], s0[3];
#pragma unroll
            for (int j = 0; j < 3; j++) {
#pragma unroll
                for (int q = 0; q < Q; q++) u[j][q] = lds128(a + j * (NBIN * 4) + (sw ^ q * 16));
                s0[j] = sum[j] = u[j][0].x + u[j][0].y + u[j][0].z + u[j][0].w;
                if (Q == 2) sum[j] += u[j][1].x + u[j][1].y + u[j][1].z + u[j][1].w;
            }
            uint32_t i01 = sum[0] | sum[1] << 16, i2 = sum[2] | min(cnt, MBE) << 16;
#pragma unroll
            for (int o = 1; o < 32; o <<= 1) {
                const uint32_t v01 = __shfl_up_sync(0xffffffffu, i01, o), v2 = __shfl_up_sync(0xffffffffu, i2, o);
                if (lane >= o) { i01 += v01; i2 += v2; }
            }
            dof = atoms_add(sb + SM_MISC - 124 + lane * 4, lane == 31 ? i2 >> 16 : 0);
            const uint32_t inc[3] = {i01 & 0xffff, i01 >> 16, i2 & 0xffff};
#pragma unroll
            for (int j = 0; j < 3; j++) {
#pragma unroll
                for (int q = 0; q < Q; q++) {
                    const uint32_t p = (3 * wl + j) * (GK * 16) + inc[j] - (q == 0 ? (sw ? s0[j] : sum[j]) : (sw ? sum[j] : sum[j] - s0[j]));
                    const uint4 v = u[j][q];
                    sts128_if(true, a + j * (NBIN * 4) + (sw ^ q * 16), make_uint4(p, p + v.x, p + v.x + v.y, p + v.x + v.y + v.z));
                }
                sts32_if(lane == 31, sb + SM_KEY + (3 * wl + j) * 4, (inc[j] + 12) >> 4 << 5 | (3 * wl + j));
            }
            dof = __shfl_sync(0xffffffffu, dof, 31) + (i2 >> 16) - min(cnt, MBE);
            sts32_if(sl < NCTA, sb + SM_SEG + sl * 4, ss[RL + 7] & 0xffffff);
            sts32_if(true, sb + SM_DOFF + (tid - NH) * 4, dof << 20);
            const uint32_t nr = min(min(cnt, MBE), RCAP - min(dof, RCAP));
            const uint64_t from = reinterpret_cast<uint64_t>(scr->rec + (nr ? sl * SLICE + (ss[RL + 7] & 0xfff) : 0));
            sts128_if(true, sb + SM_CPY + (tid - NH) * 16,
                      make_uint4((uint32_t)from, (uint32_t)(from >> 32), nr ? sb + SM_REC + dof * 16 : sb + SM_ZERO + 64, max(nr, 1)));
        }
        STAMPT(12, NH);
        bar_arrive<4, NT - 32>();
        bar_arrive<6, NH + 32>();
        bar_sync<3, NH>();
        const uint32_t key = lds32(sb + SM_KEY + lane * 4), nrec = lds32(sb + SM_MISC);
        uint32_t d20[RL + 3];
#pragma unroll
        for (int r = 0; r < RL; r += 4) {
            const uint4 v = lds128(sb + SM_DOFF + wl * 128 + r * 4);
            d20[r] = v.x; d20[r + 1] = v.y; d20[r + 2] = v.z; d20[r + 3] = v.w;
        }
#pragma unroll
        for (int r = 0; r < RL; r++) rk[r] += lds32(sb + SM_BIN + (ss[r] >> (BSH - 2) & (NBIN * 128 - 4)));
        const uint32_t cap = group_cap(key, lane);
        const uint32_t lim = __any_sync(0xffffffffu, (key >> 5) > cap || nrec > RCAP) ? 0 : 0x20000;
#pragma unroll
        for (int r = 0; r < RL; r++) {
            uint32_t v;
            asm("lop3.b32 %0, %1, 0x1ffff, %2, 0xea;" : "=r"(v) : "r"(ss[r]), "r"(lane << 20));
            sts32_if(rk[r] < lim, sb + SM_KSG + rk[r], v + d20[r]);
        }
        if (late) {
#pragma unroll
            for (int r = RL; r < RL + 7; r++) {
                rk[r] += lds32(sb + SM_BIN + (ss[r] >> (BSH - 2) & (NBIN * 128 - 4)));
                sts32_if(rk[r] < lim, sb + SM_KSG + rk[r], (dof + 32 + r - RL) << 20 | (ss[r] & 0x1ffffu));
            }
        }
        if (lim == 0) {
#pragma unroll
            for (int r = 0; r < RL + 7; r++) {
                if (r >= RL && !late) break;
                const uint32_t rnk = r < RL ? lane : 32 + r - RL, from = r < RL ? r : lane;
                const uint32_t ri = __shfl_sync(0xffffffffu, dof, from) + rnk, gi = __shfl_sync(0xffffffffu, ss[RL + 7] & 0xfff, from) + rnk;
                const bool fits = rk[r] - (ss[r] >> 25 & 31) * (GK * 16) < __shfl_sync(0xffffffffu, cap, ss[r] >> 25) * 16;
                if (rk[r] < 0x20000) {
                    sts32_if(fits, sb + SM_KSG + rk[r], min(ri, RCAP) << 20 | (ss[r] & 0x1ffffu));
                    if (!fits || ri >= RCAP) __stcg(scr->exc + cta * MBW + atoms_inc(sb + SM_MISC + 12), make_uint2(ss[r], (wl + 8 * from) * SLICE + gi));
                }
            }
        }
        STAMPT(13, NH);
        bar_sync<8, NH + 32>();
        const uint4 lt = lds128(sb + SM_LT + wl * 16);
        const uint32_t gq[3] = {lt.x & 31, lt.y & 31, lt.z & 31}, n[3] = {lt.x >> 5, lt.y >> 5, lt.z >> 5};
        const uint32_t lb = lt.w, len = n[0] + n[1] + n[2], le = lb + len;
        {
            uint4 w[4];
            uint32_t p[4], ja[4], key8[4], ba[4];
            const uint32_t lh = sb + SM_LH + wl * (LBIN * 4);
#pragma unroll
            for (int j = 0; j < 4; j++) {
                if (j == 3 && len <= 96) break;
                const uint32_t i = j * 32 + lane;
                ja[j] = (i >= n[0]) + (i >= n[0] + n[1]);
                w[j] = lds128(sb + SM_KSG + (i + (ja[j] == 0 ? gq[0] * GK : ja[j] == 1 ? gq[1] * GK - n[0] : gq[2] * GK - n[0] - n[1])) * 16);
                const uint32_t r0 = w[j].x & 0x1fff8, r1 = w[j].y & 0x1fff8, r2 = w[j].z & 0x1fff8, r3 = w[j].w & 0x1fff8, pad = N * 8;
                key8[j] = min((r0 + r1 + r2 + r3) >> 2, pad - 8);
                ba[j] = i < len ? lh + (key8[j] * bin_magic >> 21) * 4 : sb + SM_DUM + lane * 4;
                p[j] = atoms_inc(ba[j]);
            }
            __syncwarp();
            const uint4 u = lds128(lh + lane * 16);
            const uint32_t sum = u.x + u.y + u.z + u.w, ex = warp_incl_scan(sum, lane) - sum;
            sts128_if(true, lh + lane * 16, make_uint4(ex, ex + u.x, ex + u.x + u.y, ex + u.x + u.y + u.z));
            __syncwarp();
#pragma unroll
            for (int j = 0; j < 4; j++) {
                if (j == 3 && len <= 96) break;
                const uint32_t q = p[j] + lds32(ba[j]), turn = (q * SMG) >> 16, slot = q - turn * S;
                sts128_if(q < len, sb + SM_SRC + (lb + q) * 16, make_uint4(w[j].x & 0x1fff8, w[j].y & 0x1fff8, w[j].z & 0x1fff8, w[j].w & 0x1fff8));
                sts128_if(q < len, sb + SM_LIST + (lb + q) * 16,
                          make_uint4((__byte_perm(w[j].x, w[j].y, 0x7632) & 0xfff0fff0u) | 1u << (w[j].x & 3) | 0x10000u << (w[j].y & 3),
                                     (__byte_perm(w[j].z, w[j].w, 0x7632) & 0xfff0fff0u) | 1u << (w[j].z & 3) | 0x10000u << (w[j].w & 3),
                                     (turn & 1) | (ja[j] + 1) << 1 | (min(__umulhi(key8[j], pace), 0xffff) & 0xfff8) | slot << 26, bars + slot * 8));
            }
        }
        STAMPT(27, NH);
        if (FEN) asm volatile("fence.proxy.async.shared::cta;" ::: "memory");
        bar_arrive<2, NT>();
        bar_sync<5, NT>();
        STAMPT(6, NH);
        asm volatile("setmaxnreg.dec.sync.aligned.u32 24;");
        const uint32_t z = lds32(sb + SM_ZERO + (lane & 3) * 4);
        const uint32_t bytes = opaque(4096 + z);
        if (elect_one()) {
            const uint4 z0 = lds128v(sb + SM_ZERO);
            uint32_t ka = sb + SM_LIST + lb * 16 - 16 * (S - 1);
            uint32_t pf = max(wl * (NCTA * 64) + PFA - NCTA * 64, 0);
            const int row = ((wl + 2) * NCTA + cta) * 8;
            asm volatile(PRODUCER_PTX : "+r"(ka), "+r"(pf)
                : "r"(ring - 1024 + lds32v(sb + SM_ZERO)), "r"(bars), "l"(reinterpret_cast<uint64_t>(&xmap) + lds32v(sb + SM_ZERO)),
                  "r"(z0.x), "r"(z0.y), "r"(z0.z), "r"(z0.w), "r"(pos), "r"(ka + len * 16), "r"(lds32v(sb + SM_MISC + 4)), "r"(bytes),
                  "l"(x + (size_t)row * 512), "r"(min(max(N - row, 0), 8) * 1024), "n"(RSTR), "n"(SM_SRC - SM_LIST + 16 * (S - 1)) : "memory");
            const uint32_t d = ring + (len - ((len * SMG) >> 16) * S) * 1024;
            STAMPT(20, NW * 32);
            for (int guard = 0; lds32v(pos) + 16 * (S - 1) < sb + SM_LIST + le * 16 && guard < (1 << 20); guard++) __nanosleep(NSLEEP);
            asm volatile("mbarrier.arrive.expect_tx.shared::cta.b64 _, [%0], 4096;" ::"r"(bar_w) : "memory");
#pragma unroll
            for (uint32_t r = 0; r < 8; r++)
                asm volatile("cp.async.bulk.tensor.5d.shared::cluster.global.tile.mbarrier::complete_tx::bytes [%0], [%1, {%2, %3, %4, %5, %6}], [%7];"
                             ::"r"(d + (r >> 1) * RSTR + (r & 1) * 512), "l"(&wmap), "r"((r >> 2) * 64), "r"((r >> 1) & 1),
                               "r"((wl >> 1) & 2), "r"(((r ^ (wl >> 1)) & 1) + (wl & 1) * 2), "r"(wl & 2), "r"(bar_w) : "memory");
            STAMPT(21, NW * 32);
        }
        return;
    }

    const int g = lane >> 2, t = lane & 3;
    uint32_t wz[4][2], wt[2];
    {
        if (warp == NW - 1) bar_sync<6, NH + 32>();
        else bar_sync<4, NT - 32>();
        if (warp == 0) {
            const uint32_t key = lds32(sb + SM_KEY + lane * 4);
            int rank = 0;
#pragma unroll
            for (int j = 0; j < 4; j++) {
                const uint4 o = lds128(sb + SM_KEY + (lane & 16) * 4 + j * 16);
                rank += ((key - o.x) >> 31) + ((key - o.y) >> 31) + ((key - o.z) >> 31) + ((key - o.w) >> 31);
            }
            const int n2 = 2 * __popc(__ballot_sync(0xffffffffu, key < 32) & 0xff0000);
            const int other = (rank < n2 ? n2 - 1 : 15 + n2) - rank;
            const int li = lane >= 16 ? 7 - rank : min(rank, other) - (rank < n2 ? 0 : n2 / 2);
            sts32_if(lane < NG, sb + SM_LT + (li < 4 ? li : 11 - li) * 16 + (lane >= 16 ? 8 : rank < other ? 0 : 4), min(key >> 5, group_cap(key, lane)) << 5 | lane);
            __syncwarp();
            const uint4 lt = lds128(sb + SM_LT + (lane & 7) * 16);
            const uint32_t len = (lt.x >> 5) + (lt.y >> 5) + (lt.z >> 5);
            uint32_t le = len + 1;
#pragma unroll
            for (int o = 1; o < 8; o <<= 1) {
                const uint32_t v = __shfl_up_sync(0xffffffffu, le, o);
                if (lane >= o) le += v;
            }
            le -= 1;
            sts32_if(lane < NW, sb + SM_LT + lane * 16 + 12, le - len);
            bar_arrive<8, NH + 32>();
            if (lane < NW) {
                sts32_if(true, sb + SM_LIST + le * 16 + 12, bar_w);
                sts32_if(true, bar_w + 32 + lane * 4, sb + SM_LIST + (le - len) * 16);
                sts32_if(true, sb + SM_MISC + 32 + lane * 4, (lane * S + len - ((len * SMG) >> 16) * S) * 64);
                sts32_if(true, sb + SM_MISC + 64 + lane * 4, (lt.x & 31) | (lt.y & 31) << 5 | (lt.z & 31) << 10);
            }
        }
        uint4 cp3[RL];
#pragma unroll
        for (int r = 0; r < RL; r++) cp3[r] = lds128(sb + SM_CPY + (wl * 32 + r) * 16);
        const uint32_t total = __reduce_add_sync(0xffffffffu, lane < RL ? lds32(sb + SM_CPY + tid * 16 + 12) * 16 : 0);
        if (FEN) asm volatile("fence.proxy.async.shared::cta;" ::: "memory");
        bar_arrive<5, NT>();
        if (lane == 0) asm volatile("mbarrier.arrive.expect_tx.shared::cta.b64 _, [%0], %1;" ::"r"(bar_rec), "r"(total) : "memory");
        if ((warp & 6) == 2 && lane == 0) prefetch_x(warp & 1);
        if (MODE == 3 && cta == 0 && tid == 64) {
            asm volatile("st.relaxed.gpu.global.u32 [%0], %1;" ::"l"(&scr->epoch), "r"(tag) : "memory");
            scr->sent[~tag & 1] = scr->sent2[~tag & 1] = 0;
        }
        STAMP(22);
        {
            const uint32_t* wr = reinterpret_cast<const uint32_t*>(w_rad) + (t & 1) * 128;
            const uint16_t* cp = reinterpret_cast<const uint16_t*>(cg) + (t >> 1) * 32 + (t & 1) * 8 + (g & 3);
            const __nv_bfloat162 half = __floats2bfloat162_rn(0.5f, 0.5f);
#pragma unroll
            for (int j = 0; j < 4; j++) {
                uint32_t u0 = __ldg(wr + chunk_of(2 * j + (t >> 1), g)), u1 = __ldg(wr + chunk_of(2 * j + (t >> 1), g) + 64);
                const __nv_bfloat162 h0 = __hmul2(*reinterpret_cast<__nv_bfloat162*>(&u0), half);
                const __nv_bfloat162 h1 = __hmul2(*reinterpret_cast<__nv_bfloat162*>(&u1), half);
                u0 = *reinterpret_cast<const uint32_t*>(&h0);
                u1 = *reinterpret_cast<const uint32_t*>(&h1);
                wz[j][0] = __byte_perm(u0, u1, 0x5410);
                wz[j][1] = __byte_perm(u0, u1, 0x7632);
            }
            wt[0] = __ldg(cp) | ((uint32_t)__ldg(cp + 4) << 16);
            wt[1] = __ldg(cp + 16) | ((uint32_t)__ldg(cp + 20) << 16);
        }
        if (MODE == 3) {
            if (warp == NW - 2) await(scr->sent2 + (tag & 1), NCTA);
            bar_sync<7, NH>();
        }
        STAMP(24);
        asm volatile("fence.proxy.async.global;" ::: "memory");
        if (elect_one()) {
#pragma unroll
            for (int r = 0; r < RL; r++)
                asm volatile("cp.async.bulk.shared::cluster.global.mbarrier::complete_tx::bytes [%0], [%1], %2, [%3];"
                             ::"r"(cp3[r].z), "l"((uint64_t)cp3[r].y << 32 | cp3[r].x), "r"((cp3[r].w & 0xffff) * 16), "r"(bar_rec) : "memory");
        }
        STAMP(23);
        if (tid == 0 && cta < 128) asm volatile("cp.async.bulk.prefetch.L2.global [%0], 256;" ::"l"(w_mix + cta * 128));
        asm volatile("setmaxnreg.inc.sync.aligned.u32 232;" ::: "memory");
        bar_sync<2, NT>();
        STAMP(14);
    }

    float acc[40][4];
    const uint32_t z = lds32(sb + SM_ZERO + t * 4);
    const float zero = __uint_as_float(z);
#pragma unroll
    for (int j = 0; j < 40; j++) acc[j][0] = acc[j][1] = acc[j][2] = acc[j][3] = zero;
    const bool bact = (g & 1) == (t >> 1);
    mbar_wait(bar_rec, 0);
    STAMP(9);
    {
        auto keep = [&](uint32_t v) { return __shfl_sync(0xffffffffu, v + z, lane); };
        const uint32_t va0 = keep(ring + t * RSTR + (g & 2) * 128 + (g & 1) * 16 + ((((g >> 1) & 2) ^ ((((g >> 1) & 1) + t) & 3)) << 5));
        const uint32_t hm0 = keep(HM0 << (g >> 2)), hm1 = keep(0x40000u << (g >> 2)), sel = keep(0x1010u + (g >> 1) * 0x22 + t * 0x2200);
        const uint32_t rl = keep(bact ? (t & 1) * 8 : SM_ZERO - SM_REC), rm = keep(bact ? 0xfff0u : 0u);
        uint32_t lp = keep(lds32(pos));
        for (;;) {
        asm volatile(MAIN_LOOP_PTX : MAIN_LOOP_ACC(acc), "+r"(lp)
            : "r"(wz[0][0]), "r"(wz[0][1]), "r"(wz[1][0]), "r"(wz[1][1]), "r"(wz[2][0]), "r"(wz[2][1]), "r"(wz[3][0]), "r"(wz[3][1]),
              "r"(wt[0]), "r"(wt[1]), "r"(va0), "r"(hm0), "r"(hm1), "r"(rl), "r"(rm), "r"(sel), "r"(pos), "n"(sb + SM_REC)
            : "memory");
            sts32_if(true, sb + SM_ZERO + 96, lp);
            const uint2 left = lds64(sb + SM_MISC + 8);
            if (!(left.x | left.y)) break;
            if (!next_excess(scr, x, va0)) break;
            lp = sb + SM_SRC + wl * 128 + (hm0 & 1);
        }
    }
    STAMP(7);
    const uint32_t grp = lds32(sb + SM_MISC + 64 + wl * 4);

    uint32_t aq[3][8][4];
#pragma unroll
    for (int m = 0; m < 8; m++) {
#pragma unroll
        for (int j = 0; j < 2; j++)
#pragma unroll
            for (int q = 0; q < 4; q++) {
                const float* a = acc[16 * j + 2 * m + (q >> 1)] + (q & 1) * 2;
                aq[j][m][q] = pack_bf16(a[m & 1], a[~m & 1]);
            }
        aq[2][m][0] = movm(pack_bf16(acc[32 + m][0], acc[32 + m][1]));
        aq[2][m][2] = movm(pack_bf16(acc[32 + m][2], acc[32 + m][3]));
        if (m & 1) {
            aq[2][m][0] = __byte_perm(aq[2][m][0], 0, 0x1032);
            aq[2][m][2] = __byte_perm(aq[2][m][2], 0, 0x1032);
        }
        aq[2][m][1] = aq[2][m][3] = 0;
    }
    STAMP(16);
    mbar_wait(bar_w, 0);
    STAMP(17);
    const uint4 ws0 = lds128(sb + SM_MISC + 32), ws1 = lds128(sb + SM_MISC + 48);
    const uint32_t ws[8] = {ws0.x, ws0.y, ws0.z, ws0.w, ws1.x, ws1.y, ws1.z, ws1.w};
    const uint64_t wdesc = ((sb + SM_RING) >> 4) | ((uint64_t)(2 * RSTR >> 4) << 16) | ((uint64_t)(RSTR >> 4) << 32) | (1ull << 62);
    const int nloc = min(npc, N - cta * npc);
    uint2* op = reinterpret_cast<uint2*>(out) + (size_t)(cta * npc) * 128 + g + (t & 1) * 8;
    float d[64];
    auto mix = [&](int job) {
        asm volatile("wgmma.fence.sync.aligned;" ::: "memory");
#pragma unroll
        for (int m = 0; m < 8; m++) wgmma_n128(d, aq[job][m], wdesc + ws[m], m);
        asm volatile("wgmma.commit_group.sync.aligned;" ::: "memory");
    };
    mix(0);
#pragma unroll
    for (int job = 0; job < 3; job++) {
        asm volatile("wgmma.wait_group.sync.aligned 0;" ::: "memory");
        if (job == 0) STAMP(18);
        if (job == 2) STAMP(19);
#pragma unroll
        for (int k = 0; k < 64; k++) asm volatile("" : "+f"(d[k]));
        uint32_t pk[32];
#pragma unroll
        for (int k = 0; k < 32; k++) pk[k] = pack_bf16(d[2 * k], d[2 * k + 1]);
        if (job < 2) mix(job + 1);
#pragma unroll
        for (int h = 0; h < (job < 2 ? 2 : 1); h++) {
            const int gj = grp >> (5 * job) & 31;
            const int l = job < 2 ? gj * 4 + 2 * h + (t >> 1) : gj * 2 + 32 + (t >> 1);
            const bool ok = l < nloc;
#pragma unroll
            for (int j = 0; j < 16; j += 2) {
                const uint32_t p0 = movm(pk[2 * j + h]), p1 = movm(pk[2 * j + 2 + h]);
                const uint32_t rv = __shfl_xor_sync(0xffffffffu, (t & 1) ? p0 : p1, 1);
                if (ok) op[l * 128 + j * 8] = (t & 1) ? make_uint2(rv, p1) : make_uint2(p0, rv);
            }
        }
    }
    __syncwarp();
    ANCHOR(1);
}

}

extern "C" void kernel_launch(void* const* d_in, const int* in_sizes, int n_in, void* d_out, int out_size) {
    const __nv_bfloat16* x     = (const __nv_bfloat16*)d_in[0];
    const int*           src   = (const int*)d_in[1];
    const int*           dst   = (const int*)d_in[2];
    const uint2*         Y     = (const uint2*)d_in[3];
    const uint2*         ef    = (const uint2*)d_in[4];
    const __nv_bfloat16* w_rad = (const __nv_bfloat16*)d_in[5];
    const __nv_bfloat16* cg    = (const __nv_bfloat16*)d_in[6];
    const __nv_bfloat16* w_mix = (const __nv_bfloat16*)d_in[7];
    __nv_bfloat16*       out   = (__nv_bfloat16*)d_out;
    const int N = in_sizes[0] / 512;
    const int E = in_sizes[1];

    static int n_sm = 0;
    static Scratch* scr = nullptr;
    static decltype(&cuTensorMapEncodeTiled) encode = nullptr;
    if (n_sm == 0) {
        cudaDriverEntryPointQueryResult qr;
        cudaGetDriverEntryPoint("cuTensorMapEncodeTiled", (void**)&encode, cudaEnableDefault, &qr);
        cudaGetSymbolAddress((void**)&scr, g_scr);
        int dev = 0;
        cudaGetDevice(&dev);
        cudaDeviceGetAttribute(&n_sm, cudaDevAttrMultiProcessorCount, dev);
        cudaFuncSetAttribute(tfn_kernel<1>, cudaFuncAttributeMaxDynamicSharedMemorySize, SM_TOTAL);
        cudaFuncSetAttribute(tfn_kernel<2>, cudaFuncAttributeMaxDynamicSharedMemorySize, SM_TOTAL);
        cudaFuncSetAttribute(tfn_kernel<3>, cudaFuncAttributeMaxDynamicSharedMemorySize, SM_TOTAL);
    }
    CUtensorMap xmap;
    {
        const cuuint64_t dims[2] = {64, (cuuint64_t)N * 8}, strides[1] = {128};
        const cuuint32_t box[2] = {64, 8}, es[2] = {1, 1};
        encode(&xmap, CU_TENSOR_MAP_DATA_TYPE_BFLOAT16, 2, (void*)x, dims, strides, box, es, CU_TENSOR_MAP_INTERLEAVE_NONE,
               CU_TENSOR_MAP_SWIZZLE_128B, CU_TENSOR_MAP_L2_PROMOTION_NONE, CU_TENSOR_MAP_FLOAT_OOB_FILL_NONE);
    }
    CUtensorMap wmap;
    {
        const cuuint64_t dims[5] = {128, 2, 4, 4, 4}, strides[4] = {256, 512, 2048, 8192};
        const cuuint32_t box[5] = {64, 1, 2, 1, 2}, es[5] = {1, 1, 1, 1, 1};
        encode(&wmap, CU_TENSOR_MAP_DATA_TYPE_BFLOAT16, 5, (void*)w_mix, dims, strides, box, es, CU_TENSOR_MAP_INTERLEAVE_NONE,
               CU_TENSOR_MAP_SWIZZLE_128B, CU_TENSOR_MAP_L2_PROMOTION_NONE, CU_TENSOR_MAP_FLOAT_OOB_FILL_NONE);
    }
    const int slice = ((E + NCTA - 1) / NCTA + 3) / 4 * 4;
    const int npc   = (N + NCTA - 1) / NCTA;
    const uint32_t npc_magic = (uint32_t)((0x100000000ull + npc - 1) / npc);
    const uint32_t bin_magic = (uint32_t)((1ull << 25) / N);
    const double want = PDT * (double)E / (32.0 * N);
    const uint32_t pace = (uint32_t)((want < 1 ? 1 : want > 127 ? 127 : want) * (1 << 25));
    cudaStream_t st = cudaStreamPerThread;
    if (n_sm >= NCTA) {
        tfn_kernel<3><<<NCTA, NT, SM_TOTAL, st>>>(xmap, wmap, x, src, dst, Y, ef, w_rad, cg, w_mix, out, scr, N, E, slice, npc, npc_magic, bin_magic, pace);
    } else {
        tfn_kernel<1><<<NCTA, NT, SM_TOTAL, st>>>(xmap, wmap, x, src, dst, Y, ef, w_rad, cg, w_mix, out, scr, N, E, slice, npc, npc_magic, bin_magic, pace);
        tfn_kernel<2><<<NCTA, NT, SM_TOTAL, st>>>(xmap, wmap, x, src, dst, Y, ef, w_rad, cg, w_mix, out, scr, N, E, slice, npc, npc_magic, bin_magic, pace);
    }
}
```

```cpp
#include <cuda.h>
#include <cuda_runtime.h>
#include <cuda_bf16.h>
#include <stdint.h>

namespace {

constexpr int NCTA   = 132;
constexpr int NW     = 8;
constexpr int NT     = 2 * NW * 32;
constexpr int RA     = 5;
constexpr int SLICE  = RA * NT;
constexpr int MBE    = 39;
constexpr int MB1    = NCTA * 32;
constexpr int MBW    = NCTA * 40;
constexpr int ASTR   = 44;
constexpr int NH     = NW * 32;
constexpr int RL     = 17;
constexpr int NG     = 24;
constexpr int KCAP   = 684;
constexpr int RCAP   = 2688;
constexpr int GK     = 48;
#define NBIN_ 256
constexpr int NBIN   = NBIN_;
constexpr int BSH    = NBIN == 256 ? 17 : 18;
constexpr int LBIN   = 128;
#define S_ 5
constexpr int S      = S_;
constexpr int SMG    = (65535 + S) / S;
constexpr int LCAP   = KCAP + NW + 4;
constexpr uint32_t EMPTY = NG << 25;

constexpr uint32_t sb = 1024;
constexpr int SM_RING = 0;
constexpr int RSTR    = NW * S * 1024 + 256;
constexpr int SM_REC  = SM_RING + 4 * RSTR - (S - 5) * 32768;
constexpr int SM_ZERO = SM_REC + RCAP * 16;
constexpr int SM_LIST = SM_ZERO + 128;
constexpr int SM_MISC = SM_LIST + LCAP * 16;
constexpr int SM_STATE = SM_MISC + 256;
constexpr int SM_BAR  = SM_STATE + 128;
constexpr int SM_SRC  = SM_BAR + NW * S * 8 + 96;
constexpr int SM_SEG  = SM_SRC + LCAP * 16;
constexpr int SM_TOTAL = SM_SEG + NCTA * 4;
constexpr int SM_AREC = SM_RING;
constexpr int SM_AP   = SM_AREC + (SLICE + 80) * 16;
constexpr int SM_AMB  = SM_AP + NH * 12;
constexpr int SM_AOFF = SM_AMB + (NCTA + 32) * ASTR * 4;
constexpr int SM_HIST = SM_AOFF + 672;
constexpr int SM_KEY  = SM_HIST + 672;
constexpr int SM_LH   = SM_KEY + 128;
constexpr int SM_BIN  = SM_LH + NW * LBIN * 4;
constexpr int SM_DUM  = SM_BIN + NG * NBIN * 4;
constexpr int SM_KSG  = SM_DUM + 128 * 4;
constexpr int SM_CPY  = SM_KSG + NG * GK * 16;
constexpr int SM_DOFF = SM_CPY + NH * 16;
constexpr int SM_LT   = SM_DOFF + NH * 4;
constexpr int SM_RAWY = SM_REC;
constexpr int SM_RAWF = SM_RAWY + SLICE * 8;
static_assert(SM_LT + 144 <= SM_REC && SM_RAWF + SLICE * 8 <= SM_ZERO, "temporaries must fit");
static_assert(SM_TOTAL <= 232448, "smem");
static_assert(SM_AMB % 128 == 0 && SM_LIST % 128 == 0 && SM_BAR % 128 == 0 && SM_HIST % 16 == 0 && SM_BIN % 16 == 0 && SM_MISC % 16 == 0 && SM_KSG % 16 == 0, "align");
static_assert(NCTA <= RL * NW && SM_SRC + NW * 128 - SM_REC < 65536 && LBIN == 128 && SM_SRC % 16 == 0 && SM_ZERO % 128 == 0, "layout");

struct Scratch {
    uint4    rec[NCTA * SLICE];
    uint32_t mb[NCTA * MBW];
    uint32_t ss[NCTA * SLICE];
    uint2    exc[NCTA * MBW];
    uint32_t epoch;
    uint32_t sent[2];
    uint32_t gap[61];
    uint2    sent2[2];
};
__device__ __align__(128) Scratch g_scr;

#define STAMP(i)
#define STAMPT(i, th)
#define ANCHOR(i)

__device__ __forceinline__ uint32_t pack_bf16(float lo, float hi) {
    __nv_bfloat162 v = __floats2bfloat162_rn(lo, hi);
    return *reinterpret_cast<uint32_t*>(&v);
}
__device__ __forceinline__ uint4 lds128(uint32_t addr) {
    uint4 v;
    asm volatile("ld.shared.v4.u32 {%0,%1,%2,%3}, [%4];" : "=r"(v.x), "=r"(v.y), "=r"(v.z), "=r"(v.w) : "r"(addr) : "memory");
    return v;
}
__device__ __forceinline__ uint32_t movm(uint32_t v) {
    uint32_t r;
    asm volatile("movmatrix.sync.aligned.m8n8.trans.b16 %0, %1;" : "=r"(r) : "r"(v));
    return r;
}
__device__ __forceinline__ void cp16(uint32_t dst, const void* src) {
    asm volatile("cp.async.cg.shared.global [%0], [%1], 16;" ::"r"(dst), "l"(src) : "memory");
}
__device__ __forceinline__ uint4 ldg128_relaxed(const uint4* p) {
    uint4 v;
    asm volatile("ld.relaxed.gpu.global.v4.u32 {%0,%1,%2,%3}, [%4];" : "=r"(v.x), "=r"(v.y), "=r"(v.z), "=r"(v.w) : "l"(p) : "memory");
    return v;
}
__device__ __forceinline__ uint32_t atoms_inc(uint32_t addr) {
    uint32_t v;
    asm volatile("atom.shared.add.u32 %0, [%1], 1;" : "=r"(v) : "r"(addr) : "memory");
    return v;
}
__device__ __forceinline__ uint32_t lds32(uint32_t addr) {
    uint32_t v;
    asm volatile("ld.shared.u32 %0, [%1];" : "=r"(v) : "r"(addr) : "memory");
    return v;
}
__device__ __forceinline__ void sts32_if(bool p, uint32_t addr, uint32_t v) {
    asm volatile("{\n\t.reg .pred p;\n\tsetp.ne.u32 p, %2, 0;\n\t@p st.shared.u32 [%0], %1;\n\t}"
                 ::"r"(addr), "r"(v), "r"((uint32_t)p) : "memory");
}
__device__ __forceinline__ uint32_t lds32v(uint32_t addr) {
    uint32_t v;
    asm volatile("ld.volatile.shared.u32 %0, [%1];" : "=r"(v) : "r"(addr) : "memory");
    return v;
}
__device__ __forceinline__ uint32_t clock32() {
    uint32_t c;
    asm volatile("mov.u32 %0, %clock;" : "=r"(c));
    return c;
}
__device__ __forceinline__ uint32_t timer32() {
    uint32_t c;
    asm volatile("mov.u32 %0, %globaltimer_lo;" : "=r"(c));
    return c;
}
__device__ __forceinline__ uint32_t opaque(uint32_t v) {
    asm volatile("" : "+r"(v));
    return v;
}
#define HINT ""
__device__ __forceinline__ bool mbar_try(uint32_t bar, uint32_t parity) {
    uint32_t ok;
    asm volatile("{\n\t.reg .pred p;\n\t"
                 "mbarrier.try_wait.parity.shared::cta.b64 p, [%1], %2" HINT ";\n\t"
                 "selp.u32 %0, 1, 0, p;\n\t}"
                 : "=r"(ok) : "r"(bar), "r"(parity) : "memory");
    return ok;
}
__device__ __forceinline__ void mbar_wait(uint32_t bar, uint32_t parity) {
    int guard = 0;
    while (!mbar_try(bar, parity) && ++guard < (1 << 20)) {}
}
__device__ __forceinline__ void mbar_init(uint32_t bar, uint32_t count) {
    asm volatile("mbarrier.init.shared::cta.b64 [%0], %1;" ::"r"(bar), "r"(count) : "memory");
}
__device__ __forceinline__ uint32_t atoms_add(uint32_t addr, uint32_t x) {
    uint32_t v;
    asm volatile("atom.shared.add.u32 %0, [%1], %2;" : "=r"(v) : "r"(addr), "r"(x) : "memory");
    return v;
}
__device__ __forceinline__ uint2 lds64(uint32_t addr) {
    uint2 v;
    asm volatile("ld.shared.v2.u32 {%0,%1}, [%2];" : "=r"(v.x), "=r"(v.y) : "r"(addr) : "memory");
    return v;
}
__device__ __forceinline__ void sts128_if(bool p, uint32_t addr, uint4 v) {
    asm volatile("{\n\t.reg .pred p;\n\tsetp.ne.u32 p, %5, 0;\n\t@p st.shared.v4.u32 [%0], {%1,%2,%3,%4};\n\t}"
                 ::"r"(addr), "r"(v.x), "r"(v.y), "r"(v.z), "r"(v.w), "r"((uint32_t)p) : "memory");
}
__device__ __forceinline__ void scan_step(uint32_t& v, int o) {
    asm volatile("{\n\t.reg .pred p;\n\t.reg .b32 u;\n\tshfl.sync.up.b32 u|p, %0, %1, 0, 0xffffffff;\n\t@p add.u32 %0, %0, u;\n\t}" : "+r"(v) : "r"(o));
}
__device__ __forceinline__ uint32_t warp_incl_scan(uint32_t v) {
#pragma unroll
    for (int o = 1; o < 32; o <<= 1) scan_step(v, o);
    return v;
}
__device__ __forceinline__ void mma_k16v(float (&d)[4], uint32_t a0, uint32_t a1, uint32_t a2, uint32_t a3,
                                         uint32_t b0, uint32_t b1) {
    asm volatile("mma.sync.aligned.m16n8k16.row.col.f32.bf16.bf16.f32 {%0,%1,%2,%3}, {%4,%5,%6,%7}, {%8,%9}, {%0,%1,%2,%3};"
        : "+f"(d[0]), "+f"(d[1]), "+f"(d[2]), "+f"(d[3])
        : "r"(a0), "r"(a1), "r"(a2), "r"(a3), "r"(b0), "r"(b1));
}
__device__ __forceinline__ bool elect_one() {
    uint32_t ok;
    asm volatile("{\n\t.reg .pred p;\n\telect.sync _|p, 0xffffffff;\n\tselp.u32 %0, 1, 0, p;\n\t}" : "=r"(ok));
    return ok;
}
__host__ __device__ constexpr int chunk_of(int m, int g) {
    return ((m & 1) + (g & 2) + 2 * (m & 2)) * 8 + ((g ^ m) & 1) + ((m >> 2) & 1) * 2 + 4 * (((g >> 2) ^ (m >> 1)) & 1);
}
__device__ __forceinline__ uint4 lds128v(uint32_t addr) {
    uint4 v;
    asm volatile("ld.volatile.shared.v4.u32 {%0,%1,%2,%3}, [%4];" : "=r"(v.x), "=r"(v.y), "=r"(v.z), "=r"(v.w) : "r"(addr) : "memory");
    return v;
}
#define HM0(h) (0x10000u << (h))
#define MAIN_LOOP_PTX \
    "{\n" \
    ".reg .b32 v<16>, a<4>, u<4>, b<2>, c<2>, w<4>, ca0, ca1, na0, na1, ef, rx, ry, ex, ey, e0, e1, e3, gx, gy, cnt;\n" \
    ".reg .f32 z<16>, t<8>, y<4>, fz;\n" \
    ".reg .b16 h<2>;\n" \
    ".reg .pred pa, pr, p<2>, q<3>, s<2>;\n" \
    "mov.f32 fz, 0f00000000;\n" \
    "setp.ne.u32 pa, %175, 0; mov.b32 rx, 0; mov.b32 ry, 0;\n" \
    "ld.shared.v4.u32 {e0,e1,ex,e3}, [%160];\n" \
    "prmt.b32 ey, e0, e1, %176;\n" \
    "lop3.b32 u2, ey, 0xfff0, %174, 0xea; @pa ld.shared.v2.u32 {rx,ry}, [u2+%178];\n" \
    "and.b32 u2, ey, %172; setp.ne.u32 p0, u2, 0; and.b32 u2, ey, %173; setp.ne.u32 p1, u2, 0;\n" \
    "shr.u32 u2, ex, 16; add.u32 na0, %171, u2;\n" \
    "mma.sync.aligned.m16n8k8.row.col.f32.bf16.bf16.f32 {y0,y1,y2,y3}, {%169,%170}, {ry}, {fz,fz,fz,fz};\n" \
    "cvt.rn.bf16x2.f32 b0, y2, y0; cvt.rn.bf16x2.f32 b1, y3, y1;\n" \
    "selp.b32 a0, b0, 0, p0; selp.b32 a1, b0, 0, p1; selp.b32 a2, b1, 0, p0; selp.b32 a3, b1, 0, p1;\n" \
    "mma.sync.aligned.m16n8k8.row.col.f32.bf16.bf16.f32 {z0,z1,z2,z3}, {%161,%162}, {rx}, {fz,fz,fz,fz};\n" \
    "mma.sync.aligned.m16n8k8.row.col.f32.bf16.bf16.f32 {z4,z5,z6,z7}, {%163,%164}, {rx}, {fz,fz,fz,fz};\n" \
    "mma.sync.aligned.m16n8k8.row.col.f32.bf16.bf16.f32 {z8,z9,z10,z11}, {%165,%166}, {rx}, {fz,fz,fz,fz};\n" \
    "tanh.approx.f32 t0, z0; tanh.approx.f32 t1, z2;\n" \
    "fma.rn.f32 z0, z0, t0, z0; fma.rn.f32 z2, z2, t1, z2;\n" \
    "tanh.approx.f32 t2, z1; tanh.approx.f32 t3, z3;\n" \
    "fma.rn.f32 z1, z1, t2, z1; fma.rn.f32 z3, z3, t3, z3;\n" \
    "tanh.approx.f32 t4, z4; tanh.approx.f32 t5, z6;\n" \
    "fma.rn.f32 z4, z4, t4, z4; fma.rn.f32 z6, z6, t5, z6;\n" \
    "tanh.approx.f32 t6, z5; tanh.approx.f32 t7, z7;\n" \
    "ld.shared.v4.u32 {e0,e1,ex,e3}, [%160+16];\n" \
    "mov.u32 cnt, %%globaltimer_hi; st.shared.u32 [%177+32], cnt;\n" \
    "bra.uni SLOW;\n" \
    "S2:\n" \
    "prmt.b32 ey, e0, e1, %176;\n" \
    "mov.b32 ca0, na0; xor.b32 ca1, na0, 32; mov.b32 ef, rx;\n" \
    "mov.b32 {h0,h1}, z0; mov.b32 u1, {h1,h1}; mul.bf16x2 w1, v1, u1;\n" \
    "fma.rn.f32 z5, z5, t6, z5;\n" \
    "add.u32 %160, %160, 16;\n" \
    "mov.b32 {h0,h1}, z2; mov.b32 u1, {h1,h1}; mul.bf16x2 w2, v2, u1;\n" \
    "mov.b32 {h0,h1}, z0; mov.b32 u1, {h1,h1}; mul.bf16x2 w0, v0, u1;\n" \
    "and.b32 u2, ey, %172; setp.ne.u32 p0, u2, 0; and.b32 u2, ey, %173; setp.ne.u32 p1, u2, 0;\n" \
    "lop3.b32 u2, ey, 0xfff0, %174, 0xea; @pa ld.shared.v2.u32 {rx,ry}, [u2+%178];\n" \
    "or.b32 c0, a0, a1; or.b32 c1, a2, a3;\n" \
    "tanh.approx.f32 t3, z11;\n" \
    "tanh.approx.f32 t0, z8;\n" \
    "fma.rn.f32 z7, z7, t7, z7;\n" \
    "tanh.approx.f32 t2, z9;\n" \
    "fma.rn.f32 z11, z11, t3, z11;\n" \
    "ld.shared.v4.u32 {v12,v13,v14,v15}, [ca0+640];\n" \
    "fma.rn.f32 z8, z8, t0, z8;\n" \
    "tanh.approx.f32 t1, z10;\n" \
    "fma.rn.f32 z10, z10, t1, z10;\n" \
    "mov.b32 {h0,h1}, z2; mov.b32 u1, {h1,h1}; mul.bf16x2 w3, v3, u1;\n" \
    "ld.shared.v4.u32 {v0,v1,v2,v3}, [ca1+0];\n" \
    "mma.sync.aligned.m16n8k16.row.col.f32.bf16.bf16.f32 {%128,%129,%130,%131}, {w0,w2,w1,w3}, {c0,c1}, {%128,%129,%130,%131};\n" \
    "mov.b32 {h0,h1}, z3; mov.b32 u1, {h1,h1}; mul.bf16x2 w2, v6, u1;\n" \
    "mma.sync.aligned.m16n8k8.row.col.f32.bf16.bf16.f32 {z12,z13,z14,z15}, {%167,%168}, {ef}, {fz,fz,fz,fz};\n" \
    "tanh.approx.f32 t4, z12;\n" \
    "mov.b32 {h0,h1}, z1; mov.b32 u1, {h1,h1}; mul.bf16x2 w0, v4, u1;\n" \
    "mov.b32 {h0,h1}, z3; mov.b32 u1, {h1,h1}; mul.bf16x2 w3, v7, u1;\n" \
    "mov.b32 {h0,h1}, z1; mov.b32 u1, {h1,h1}; mul.bf16x2 w1, v5, u1;\n" \
    "mma.sync.aligned.m16n8k16.row.col.f32.bf16.bf16.f32 {%132,%133,%134,%135}, {w0,w2,w1,w3}, {c0,c1}, {%132,%133,%134,%135};\n" \
    "mov.b32 {h0,h1}, z6; mov.b32 u1, {h1,h1}; mul.bf16x2 w2, v10, u1;\n" \
    "mov.b32 {h0,h1}, z4; mov.b32 u1, {h1,h1}; mul.bf16x2 w1, v9, u1;\n" \
    "fma.rn.f32 z9, z9, t2, z9;\n" \
    "fma.rn.f32 z12, z12, t4, z12;\n" \
    "mov.b32 {h0,h1}, z4; mov.b32 u1, {h1,h1}; mul.bf16x2 w0, v8, u1;\n" \
    "shr.u32 u2, ex, 16; add.u32 na0, %171, u2;\n" \
    "ld.shared.v4.u32 {v4,v5,v6,v7}, [ca1+128];\n" \
    "tanh.approx.f32 t5, z14;\n" \
    "fma.rn.f32 z14, z14, t5, z14;\n" \
    "tanh.approx.f32 t6, z13;\n" \
    "mma.sync.aligned.m16n8k8.row.col.f32.bf16.bf16.f32 {z0,z1,z2,z3}, {%161,%162}, {rx}, {fz,fz,fz,fz};\n" \
    "tanh.approx.f32 t1, z2;\n" \
    "tanh.approx.f32 t0, z0;\n" \
    "tanh.approx.f32 t2, z1;\n" \
    "fma.rn.f32 z13, z13, t6, z13;\n" \
    "mov.b32 {h0,h1}, z6; mov.b32 u1, {h1,h1}; mul.bf16x2 w3, v11, u1;\n" \
    "mma.sync.aligned.m16n8k16.row.col.f32.bf16.bf16.f32 {%136,%137,%138,%139}, {w0,w2,w1,w3}, {c0,c1}, {%136,%137,%138,%139};\n" \
    "mov.b32 {h0,h1}, z5; mov.b32 u1, {h1,h1}; mul.bf16x2 w1, v13, u1;\n" \
    "mov.b32 {h0,h1}, z5; mov.b32 u1, {h1,h1}; mul.bf16x2 w0, v12, u1;\n" \
    "ld.shared.v4.u32 {v8,v9,v10,v11}, [ca1+512];\n" \
    "mov.b32 {h0,h1}, z7; mov.b32 u1, {h1,h1}; mul.bf16x2 w2, v14, u1;\n" \
    "fma.rn.f32 z0, z0, t0, z0;\n" \
    "tanh.approx.f32 t7, z15;\n" \
    "fma.rn.f32 z15, z15, t7, z15;\n" \
    "mov.b32 {h0,h1}, z7; mov.b32 u1, {h1,h1}; mul.bf16x2 w3, v15, u1;\n" \
    "mma.sync.aligned.m16n8k16.row.col.f32.bf16.bf16.f32 {%140,%141,%142,%143}, {w0,w2,w1,w3}, {c0,c1}, {%140,%141,%142,%143};\n" \
    "mov.b32 {h0,h1}, z8; mov.b32 u1, {h1,h1}; mul.bf16x2 w0, v0, u1;\n" \
    "mov.b32 {h0,h1}, z8; mov.b32 u1, {h1,h1}; mul.bf16x2 w1, v1, u1;\n" \
    "ld.shared.v4.u32 {v12,v13,v14,v15}, [ca1+640];\n" \
    "mov.b32 {h0,h1}, z10; mov.b32 u1, {h1,h1}; mul.bf16x2 w3, v3, u1;\n" \
    "fma.rn.f32 z2, z2, t1, z2;\n" \
    "fma.rn.f32 z1, z1, t2, z1;\n" \
    "and.b32 u2, ex, 1; mbarrier.try_wait.parity.shared::cta.b64 pr, [e3], u2;\n" \
    "mov.b32 {h0,h1}, z10; mov.b32 u1, {h1,h1}; mul.bf16x2 w2, v2, u1;\n" \
    "st.volatile.shared.u32 [%177], %160;\n" \
    "@pr ld.shared.v4.u32 {v0,v1,v2,v3}, [na0+0];\n" \
    "mma.sync.aligned.m16n8k16.row.col.f32.bf16.bf16.f32 {%144,%145,%146,%147}, {w0,w2,w1,w3}, {c0,c1}, {%144,%145,%146,%147};\n" \
    "mov.b32 {h0,h1}, z11; mov.b32 u1, {h1,h1}; mul.bf16x2 w3, v7, u1;\n" \
    "mma.sync.aligned.m16n8k8.row.col.f32.bf16.bf16.f32 {z4,z5,z6,z7}, {%163,%164}, {rx}, {fz,fz,fz,fz};\n" \
    "tanh.approx.f32 t4, z4;\n" \
    "tanh.approx.f32 t5, z6;\n" \
    "mov.b32 {h0,h1}, z9; mov.b32 u1, {h1,h1}; mul.bf16x2 w1, v5, u1;\n" \
    "mov.b32 {h0,h1}, z9; mov.b32 u1, {h1,h1}; mul.bf16x2 w0, v4, u1;\n" \
    "mov.b32 {h0,h1}, z11; mov.b32 u1, {h1,h1}; mul.bf16x2 w2, v6, u1;\n" \
    "mma.sync.aligned.m16n8k16.row.col.f32.bf16.bf16.f32 {%148,%149,%150,%151}, {w0,w2,w1,w3}, {c0,c1}, {%148,%149,%150,%151};\n" \
    "mov.b32 {h0,h1}, z12; mov.b32 u1, {h1,h1}; mul.bf16x2 w1, v9, u1;\n" \
    "@pr ld.shared.v4.u32 {v4,v5,v6,v7}, [na0+128];\n" \
    "mov.b32 {h0,h1}, z14; mov.b32 u1, {h1,h1}; mul.bf16x2 w2, v10, u1;\n" \
    "fma.rn.f32 z4, z4, t4, z4;\n" \
    "tanh.approx.f32 t3, z3;\n" \
    "fma.rn.f32 z3, z3, t3, z3;\n" \
    "mma.sync.aligned.m16n8k8.row.col.f32.bf16.bf16.f32 {y0,y1,y2,y3}, {%169,%170}, {ry}, {fz,fz,fz,fz};\n" \
    "tanh.approx.f32 t7, z7;\n" \
    "mma.sync.aligned.m16n8k8.row.col.f32.bf16.bf16.f32 {z8,z9,z10,z11}, {%165,%166}, {rx}, {fz,fz,fz,fz};\n" \
    "and.b32 u2, ex, 14; setp.eq.and.u32 q0, u2, 2, pr; setp.eq.and.u32 q1, u2, 4, pr; setp.eq.and.u32 q2, u2, 8, pr;\n" \
    "tanh.approx.f32 t6, z5;\n" \
    "mov.b32 {h0,h1}, z14; mov.b32 u1, {h1,h1}; mul.bf16x2 w3, v11, u1;\n" \
    "mov.b32 {h0,h1}, z12; mov.b32 u1, {h1,h1}; mul.bf16x2 w0, v8, u1;\n" \
    "@pr ld.shared.v4.u32 {v8,v9,v10,v11}, [na0+512];\n" \
    "mma.sync.aligned.m16n8k16.row.col.f32.bf16.bf16.f32 {%152,%153,%154,%155}, {w0,w2,w1,w3}, {c0,c1}, {%152,%153,%154,%155};\n" \
    "mov.b32 {h0,h1}, z13; mov.b32 u1, {h1,h1}; mul.bf16x2 w0, v12, u1;\n" \
    "mov.b32 {h0,h1}, z15; mov.b32 u1, {h1,h1}; mul.bf16x2 w3, v15, u1;\n" \
    "ld.shared.v4.u32 {e0,e1,ex,e3}, [%160+16];\n" \
    "fma.rn.f32 z6, z6, t5, z6;\n" \
    "cvt.rn.bf16x2.f32 b0, y2, y0; cvt.rn.bf16x2.f32 b1, y3, y1;\n" \
    "mov.b32 {h0,h1}, z13; mov.b32 u1, {h1,h1}; mul.bf16x2 w1, v13, u1;\n" \
    "mov.b32 {h0,h1}, z15; mov.b32 u1, {h1,h1}; mul.bf16x2 w2, v14, u1;\n" \
    "selp.b32 a0, b0, 0, p0; selp.b32 a1, b0, 0, p1; selp.b32 a2, b1, 0, p0; selp.b32 a3, b1, 0, p1;\n" \
    "mma.sync.aligned.m16n8k16.row.col.f32.bf16.bf16.f32 {%156,%157,%158,%159}, {w0,w2,w1,w3}, {c0,c1}, {%156,%157,%158,%159};\n" \
    "@q1 bra.uni S1;\n" \
    "@!q0 bra.uni D;\n" \
    "S0:\n" \
    "prmt.b32 ey, e0, e1, %176;\n" \
    "mov.b32 {h0,h1}, z0; mov.b32 u1, {h1,h1}; mul.bf16x2 v0, v0, u1;\n" \
    "add.u32 %160, %160, 16;\n" \
    "mov.b32 {h0,h1}, z2; mov.b32 u1, {h1,h1}; mul.bf16x2 v2, v2, u1;\n" \
    "mov.b32 {h0,h1}, z0; mov.b32 u1, {h1,h1}; mul.bf16x2 v1, v1, u1;\n" \
    "mma.sync.aligned.m16n8k16.row.col.f32.bf16.bf16.f32 {%0,%1,%2,%3}, {a0,a1,a2,a3}, {v0,v1}, {%0,%1,%2,%3};\n" \
    "and.b32 u2, ey, %172; setp.ne.u32 p0, u2, 0; and.b32 u2, ey, %173; setp.ne.u32 p1, u2, 0;\n" \
    "mov.b32 ca0, na0; xor.b32 ca1, na0, 32; mov.b32 ef, rx;\n" \
    "lop3.b32 u2, ey, 0xfff0, %174, 0xea; @pa ld.shared.v2.u32 {rx,ry}, [u2+%178];\n" \
    "ld.shared.v4.u32 {v12,v13,v14,v15}, [ca0+640];\n" \
    "mov.b32 {h0,h1}, z3; mov.b32 u1, {h1,h1}; mul.bf16x2 v7, v7, u1;\n" \
    "fma.rn.f32 z5, z5, t6, z5;\n" \
    "fma.rn.f32 z7, z7, t7, z7;\n" \
    "tanh.approx.f32 t2, z9;\n" \
    "tanh.approx.f32 t0, z8;\n" \
    "fma.rn.f32 z8, z8, t0, z8;\n" \
    "tanh.approx.f32 t3, z11;\n" \
    "tanh.approx.f32 t1, z10;\n" \
    "fma.rn.f32 z10, z10, t1, z10;\n" \
    "mov.b32 {h0,h1}, z2; mov.b32 u1, {h1,h1}; mul.bf16x2 v3, v3, u1;\n" \
    "mma.sync.aligned.m16n8k16.row.col.f32.bf16.bf16.f32 {%4,%5,%6,%7}, {a0,a1,a2,a3}, {v2,v3}, {%4,%5,%6,%7};\n" \
    "ld.shared.v4.u32 {v0,v1,v2,v3}, [ca1+0];\n" \
    "mov.b32 {h0,h1}, z6; mov.b32 u1, {h1,h1}; mul.bf16x2 v10, v10, u1;\n" \
    "mov.b32 {h0,h1}, z4; mov.b32 u1, {h1,h1}; mul.bf16x2 v8, v8, u1;\n" \
    "mov.b32 {h0,h1}, z1; mov.b32 u1, {h1,h1}; mul.bf16x2 v4, v4, u1;\n" \
    "mov.b32 {h0,h1}, z3; mov.b32 u1, {h1,h1}; mul.bf16x2 v6, v6, u1;\n" \
    "mma.sync.aligned.m16n8k16.row.col.f32.bf16.bf16.f32 {%12,%13,%14,%15}, {a0,a1,a2,a3}, {v6,v7}, {%12,%13,%14,%15};\n" \
    "mov.b32 {h0,h1}, z1; mov.b32 u1, {h1,h1}; mul.bf16x2 v5, v5, u1;\n" \
    "mma.sync.aligned.m16n8k16.row.col.f32.bf16.bf16.f32 {%8,%9,%10,%11}, {a0,a1,a2,a3}, {v4,v5}, {%8,%9,%10,%11};\n" \
    "ld.shared.v4.u32 {v4,v5,v6,v7}, [ca1+128];\n" \
    "fma.rn.f32 z9, z9, t2, z9;\n" \
    "mov.b32 {h0,h1}, z7; mov.b32 u1, {h1,h1}; mul.bf16x2 v15, v15, u1;\n" \
    "mma.sync.aligned.m16n8k8.row.col.f32.bf16.bf16.f32 {z12,z13,z14,z15}, {%167,%168}, {ef}, {fz,fz,fz,fz};\n" \
    "tanh.approx.f32 t5, z14;\n" \
    "tanh.approx.f32 t6, z13;\n" \
    "tanh.approx.f32 t4, z12;\n" \
    "fma.rn.f32 z12, z12, t4, z12;\n" \
    "fma.rn.f32 z13, z13, t6, z13;\n" \
    "mov.b32 {h0,h1}, z5; mov.b32 u1, {h1,h1}; mul.bf16x2 v13, v13, u1;\n" \
    "mov.b32 {h0,h1}, z4; mov.b32 u1, {h1,h1}; mul.bf16x2 v9, v9, u1;\n" \
    "mma.sync.aligned.m16n8k16.row.col.f32.bf16.bf16.f32 {%16,%17,%18,%19}, {a0,a1,a2,a3}, {v8,v9}, {%16,%17,%18,%19};\n" \
    "mov.b32 {h0,h1}, z7; mov.b32 u1, {h1,h1}; mul.bf16x2 v14, v14, u1;\n" \
    "mov.b32 {h0,h1}, z6; mov.b32 u1, {h1,h1}; mul.bf16x2 v11, v11, u1;\n" \
    "mma.sync.aligned.m16n8k16.row.col.f32.bf16.bf16.f32 {%20,%21,%22,%23}, {a0,a1,a2,a3}, {v10,v11}, {%20,%21,%22,%23};\n" \
    "ld.shared.v4.u32 {v8,v9,v10,v11}, [ca1+512];\n" \
    "mma.sync.aligned.m16n8k8.row.col.f32.bf16.bf16.f32 {z0,z1,z2,z3}, {%161,%162}, {rx}, {fz,fz,fz,fz};\n" \
    "fma.rn.f32 z14, z14, t5, z14;\n" \
    "tanh.approx.f32 t0, z0;\n" \
    "shr.u32 u2, ex, 16; add.u32 na0, %171, u2;\n" \
    "fma.rn.f32 z11, z11, t3, z11;\n" \
    "mma.sync.aligned.m16n8k16.row.col.f32.bf16.bf16.f32 {%28,%29,%30,%31}, {a0,a1,a2,a3}, {v14,v15}, {%28,%29,%30,%31};\n" \
    "mov.b32 {h0,h1}, z8; mov.b32 u1, {h1,h1}; mul.bf16x2 v0, v0, u1;\n" \
    "mov.b32 {h0,h1}, z5; mov.b32 u1, {h1,h1}; mul.bf16x2 v12, v12, u1;\n" \
    "mma.sync.aligned.m16n8k16.row.col.f32.bf16.bf16.f32 {%24,%25,%26,%27}, {a0,a1,a2,a3}, {v12,v13}, {%24,%25,%26,%27};\n" \
    "ld.shared.v4.u32 {v12,v13,v14,v15}, [ca1+640];\n" \
    "and.b32 u2, ex, 1; mbarrier.try_wait.parity.shared::cta.b64 pr, [e3], u2;\n" \
    "mov.b32 {h0,h1}, z11; mov.b32 u1, {h1,h1}; mul.bf16x2 v6, v6, u1;\n" \
    "tanh.approx.f32 t7, z15;\n" \
    "mma.sync.aligned.m16n8k8.row.col.f32.bf16.bf16.f32 {z4,z5,z6,z7}, {%163,%164}, {rx}, {fz,fz,fz,fz};\n" \
    "fma.rn.f32 z0, z0, t0, z0;\n" \
    "mov.b32 {h0,h1}, z11; mov.b32 u1, {h1,h1}; mul.bf16x2 v7, v7, u1;\n" \
    "mov.b32 {h0,h1}, z10; mov.b32 u1, {h1,h1}; mul.bf16x2 v3, v3, u1;\n" \
    "fma.rn.f32 z15, z15, t7, z15;\n" \
    "mov.b32 {h0,h1}, z8; mov.b32 u1, {h1,h1}; mul.bf16x2 v1, v1, u1;\n" \
    "mma.sync.aligned.m16n8k16.row.col.f32.bf16.bf16.f32 {%32,%33,%34,%35}, {a0,a1,a2,a3}, {v0,v1}, {%32,%33,%34,%35};\n" \
    "mov.b32 {h0,h1}, z9; mov.b32 u1, {h1,h1}; mul.bf16x2 v5, v5, u1;\n" \
    "mov.b32 {h0,h1}, z10; mov.b32 u1, {h1,h1}; mul.bf16x2 v2, v2, u1;\n" \
    "mma.sync.aligned.m16n8k16.row.col.f32.bf16.bf16.f32 {%36,%37,%38,%39}, {a0,a1,a2,a3}, {v2,v3}, {%36,%37,%38,%39};\n" \
    "tanh.approx.f32 t1, z2;\n" \
    "fma.rn.f32 z2, z2, t1, z2;\n" \
    "tanh.approx.f32 t3, z3;\n" \
    "st.volatile.shared.u32 [%177], %160;\n" \
    "@pr ld.shared.v4.u32 {v0,v1,v2,v3}, [na0+0];\n" \
    "mov.b32 {h0,h1}, z9; mov.b32 u1, {h1,h1}; mul.bf16x2 v4, v4, u1;\n" \
    "mma.sync.aligned.m16n8k16.row.col.f32.bf16.bf16.f32 {%40,%41,%42,%43}, {a0,a1,a2,a3}, {v4,v5}, {%40,%41,%42,%43};\n" \
    "fma.rn.f32 z3, z3, t3, z3;\n" \
    "tanh.approx.f32 t2, z1;\n" \
    "fma.rn.f32 z1, z1, t2, z1;\n" \
    "tanh.approx.f32 t4, z4;\n" \
    "mov.b32 {h0,h1}, z13; mov.b32 u1, {h1,h1}; mul.bf16x2 v13, v13, u1;\n" \
    "tanh.approx.f32 t7, z7;\n" \
    "tanh.approx.f32 t5, z6;\n" \
    "mov.b32 {h0,h1}, z12; mov.b32 u1, {h1,h1}; mul.bf16x2 v9, v9, u1;\n" \
    "mov.b32 {h0,h1}, z14; mov.b32 u1, {h1,h1}; mul.bf16x2 v10, v10, u1;\n" \
    "fma.rn.f32 z4, z4, t4, z4;\n" \
    "mov.b32 {h0,h1}, z12; mov.b32 u1, {h1,h1}; mul.bf16x2 v8, v8, u1;\n" \
    "mma.sync.aligned.m16n8k16.row.col.f32.bf16.bf16.f32 {%48,%49,%50,%51}, {a0,a1,a2,a3}, {v8,v9}, {%48,%49,%50,%51};\n" \
    "mma.sync.aligned.m16n8k16.row.col.f32.bf16.bf16.f32 {%44,%45,%46,%47}, {a0,a1,a2,a3}, {v6,v7}, {%44,%45,%46,%47};\n" \
    "@pr ld.shared.v4.u32 {v4,v5,v6,v7}, [na0+128];\n" \
    "fma.rn.f32 z6, z6, t5, z6;\n" \
    "mma.sync.aligned.m16n8k8.row.col.f32.bf16.bf16.f32 {z8,z9,z10,z11}, {%165,%166}, {rx}, {fz,fz,fz,fz};\n" \
    "mma.sync.aligned.m16n8k8.row.col.f32.bf16.bf16.f32 {y0,y1,y2,y3}, {%169,%170}, {ry}, {fz,fz,fz,fz};\n" \
    "mov.b32 {h0,h1}, z15; mov.b32 u1, {h1,h1}; mul.bf16x2 v14, v14, u1;\n" \
    "and.b32 u2, ex, 14; setp.eq.and.u32 q0, u2, 2, pr; setp.eq.and.u32 q1, u2, 4, pr; setp.eq.and.u32 q2, u2, 8, pr;\n" \
    "mov.b32 {h0,h1}, z14; mov.b32 u1, {h1,h1}; mul.bf16x2 v11, v11, u1;\n" \
    "mma.sync.aligned.m16n8k16.row.col.f32.bf16.bf16.f32 {%52,%53,%54,%55}, {a0,a1,a2,a3}, {v10,v11}, {%52,%53,%54,%55};\n" \
    "@pr ld.shared.v4.u32 {v8,v9,v10,v11}, [na0+512];\n" \
    "tanh.approx.f32 t6, z5;\n" \
    "mov.b32 {h0,h1}, z15; mov.b32 u1, {h1,h1}; mul.bf16x2 v15, v15, u1;\n" \
    "mma.sync.aligned.m16n8k16.row.col.f32.bf16.bf16.f32 {%60,%61,%62,%63}, {a0,a1,a2,a3}, {v14,v15}, {%60,%61,%62,%63};\n" \
    "ld.shared.v4.u32 {e0,e1,ex,e3}, [%160+16];\n" \
    "mov.b32 {h0,h1}, z13; mov.b32 u1, {h1,h1}; mul.bf16x2 v12, v12, u1;\n" \
    "mma.sync.aligned.m16n8k16.row.col.f32.bf16.bf16.f32 {%56,%57,%58,%59}, {a0,a1,a2,a3}, {v12,v13}, {%56,%57,%58,%59};\n" \
    "cvt.rn.bf16x2.f32 b0, y2, y0; cvt.rn.bf16x2.f32 b1, y3, y1;\n" \
    "selp.b32 a0, b0, 0, p0; selp.b32 a1, b0, 0, p1; selp.b32 a2, b1, 0, p0; selp.b32 a3, b1, 0, p1;\n" \
    "@!q1 bra.uni D;\n" \
    "S1:\n" \
    "prmt.b32 ey, e0, e1, %176;\n" \
    "mov.b32 {h0,h1}, z0; mov.b32 u1, {h1,h1}; mul.bf16x2 v0, v0, u1;\n" \
    "add.u32 %160, %160, 16;\n" \
    "mov.b32 {h0,h1}, z2; mov.b32 u1, {h1,h1}; mul.bf16x2 v2, v2, u1;\n" \
    "mov.b32 {h0,h1}, z0; mov.b32 u1, {h1,h1}; mul.bf16x2 v1, v1, u1;\n" \
    "mma.sync.aligned.m16n8k16.row.col.f32.bf16.bf16.f32 {%64,%65,%66,%67}, {a0,a1,a2,a3}, {v0,v1}, {%64,%65,%66,%67};\n" \
    "and.b32 u2, ey, %172; setp.ne.u32 p0, u2, 0; and.b32 u2, ey, %173; setp.ne.u32 p1, u2, 0;\n" \
    "mov.b32 ca0, na0; xor.b32 ca1, na0, 32; mov.b32 ef, rx;\n" \
    "lop3.b32 u2, ey, 0xfff0, %174, 0xea; @pa ld.shared.v2.u32 {rx,ry}, [u2+%178];\n" \
    "ld.shared.v4.u32 {v12,v13,v14,v15}, [ca0+640];\n" \
    "mov.b32 {h0,h1}, z3; mov.b32 u1, {h1,h1}; mul.bf16x2 v7, v7, u1;\n" \
    "fma.rn.f32 z5, z5, t6, z5;\n" \
    "fma.rn.f32 z7, z7, t7, z7;\n" \
    "tanh.approx.f32 t2, z9;\n" \
    "tanh.approx.f32 t0, z8;\n" \
    "fma.rn.f32 z8, z8, t0, z8;\n" \
    "tanh.approx.f32 t3, z11;\n" \
    "tanh.approx.f32 t1, z10;\n" \
    "fma.rn.f32 z10, z10, t1, z10;\n" \
    "mov.b32 {h0,h1}, z2; mov.b32 u1, {h1,h1}; mul.bf16x2 v3, v3, u1;\n" \
    "mma.sync.aligned.m16n8k16.row.col.f32.bf16.bf16.f32 {%68,%69,%70,%71}, {a0,a1,a2,a3}, {v2,v3}, {%68,%69,%70,%71};\n" \
    "ld.shared.v4.u32 {v0,v1,v2,v3}, [ca1+0];\n" \
    "mov.b32 {h0,h1}, z6; mov.b32 u1, {h1,h1}; mul.bf16x2 v10, v10, u1;\n" \
    "mov.b32 {h0,h1}, z4; mov.b32 u1, {h1,h1}; mul.bf16x2 v8, v8, u1;\n" \
    "mov.b32 {h0,h1}, z1; mov.b32 u1, {h1,h1}; mul.bf16x2 v4, v4, u1;\n" \
    "mov.b32 {h0,h1}, z3; mov.b32 u1, {h1,h1}; mul.bf16x2 v6, v6, u1;\n" \
    "mma.sync.aligned.m16n8k16.row.col.f32.bf16.bf16.f32 {%76,%77,%78,%79}, {a0,a1,a2,a3}, {v6,v7}, {%76,%77,%78,%79};\n" \
    "mov.b32 {h0,h1}, z1; mov.b32 u1, {h1,h1}; mul.bf16x2 v5, v5, u1;\n" \
    "mma.sync.aligned.m16n8k16.row.col.f32.bf16.bf16.f32 {%72,%73,%74,%75}, {a0,a1,a2,a3}, {v4,v5}, {%72,%73,%74,%75};\n" \
    "ld.shared.v4.u32 {v4,v5,v6,v7}, [ca1+128];\n" \
    "fma.rn.f32 z9, z9, t2, z9;\n" \
    "mov.b32 {h0,h1}, z7; mov.b32 u1, {h1,h1}; mul.bf16x2 v15, v15, u1;\n" \
    "mma.sync.aligned.m16n8k8.row.col.f32.bf16.bf16.f32 {z12,z13,z14,z15}, {%167,%168}, {ef}, {fz,fz,fz,fz};\n" \
    "tanh.approx.f32 t5, z14;\n" \
    "tanh.approx.f32 t6, z13;\n" \
    "tanh.approx.f32 t4, z12;\n" \
    "fma.rn.f32 z12, z12, t4, z12;\n" \
    "fma.rn.f32 z13, z13, t6, z13;\n" \
    "mov.b32 {h0,h1}, z5; mov.b32 u1, {h1,h1}; mul.bf16x2 v13, v13, u1;\n" \
    "mov.b32 {h0,h1}, z4; mov.b32 u1, {h1,h1}; mul.bf16x2 v9, v9, u1;\n" \
    "mma.sync.aligned.m16n8k16.row.col.f32.bf16.bf16.f32 {%80,%81,%82,%83}, {a0,a1,a2,a3}, {v8,v9}, {%80,%81,%82,%83};\n" \
    "mov.b32 {h0,h1}, z7; mov.b32 u1, {h1,h1}; mul.bf16x2 v14, v14, u1;\n" \
    "mov.b32 {h0,h1}, z6; mov.b32 u1, {h1,h1}; mul.bf16x2 v11, v11, u1;\n" \
    "mma.sync.aligned.m16n8k16.row.col.f32.bf16.bf16.f32 {%84,%85,%86,%87}, {a0,a1,a2,a3}, {v10,v11}, {%84,%85,%86,%87};\n" \
    "ld.shared.v4.u32 {v8,v9,v10,v11}, [ca1+512];\n" \
    "mma.sync.aligned.m16n8k8.row.col.f32.bf16.bf16.f32 {z0,z1,z2,z3}, {%161,%162}, {rx}, {fz,fz,fz,fz};\n" \
    "fma.rn.f32 z14, z14, t5, z14;\n" \
    "tanh.approx.f32 t0, z0;\n" \
    "shr.u32 u2, ex, 16; add.u32 na0, %171, u2;\n" \
    "fma.rn.f32 z11, z11, t3, z11;\n" \
    "mma.sync.aligned.m16n8k16.row.col.f32.bf16.bf16.f32 {%92,%93,%94,%95}, {a0,a1,a2,a3}, {v14,v15}, {%92,%93,%94,%95};\n" \
    "mov.b32 {h0,h1}, z8; mov.b32 u1, {h1,h1}; mul.bf16x2 v0, v0, u1;\n" \
    "mov.b32 {h0,h1}, z5; mov.b32 u1, {h1,h1}; mul.bf16x2 v12, v12, u1;\n" \
    "mma.sync.aligned.m16n8k16.row.col.f32.bf16.bf16.f32 {%88,%89,%90,%91}, {a0,a1,a2,a3}, {v12,v13}, {%88,%89,%90,%91};\n" \
    "ld.shared.v4.u32 {v12,v13,v14,v15}, [ca1+640];\n" \
    "and.b32 u2, ex, 1; mbarrier.try_wait.parity.shared::cta.b64 pr, [e3], u2;\n" \
    "mov.b32 {h0,h1}, z11; mov.b32 u1, {h1,h1}; mul.bf16x2 v6, v6, u1;\n" \
    "tanh.approx.f32 t7, z15;\n" \
    "mma.sync.aligned.m16n8k8.row.col.f32.bf16.bf16.f32 {z4,z5,z6,z7}, {%163,%164}, {rx}, {fz,fz,fz,fz};\n" \
    "fma.rn.f32 z0, z0, t0, z0;\n" \
    "mov.b32 {h0,h1}, z11; mov.b32 u1, {h1,h1}; mul.bf16x2 v7, v7, u1;\n" \
    "mov.b32 {h0,h1}, z10; mov.b32 u1, {h1,h1}; mul.bf16x2 v3, v3, u1;\n" \
    "fma.rn.f32 z15, z15, t7, z15;\n" \
    "mov.b32 {h0,h1}, z8; mov.b32 u1, {h1,h1}; mul.bf16x2 v1, v1, u1;\n" \
    "mma.sync.aligned.m16n8k16.row.col.f32.bf16.bf16.f32 {%96,%97,%98,%99}, {a0,a1,a2,a3}, {v0,v1}, {%96,%97,%98,%99};\n" \
    "mov.b32 {h0,h1}, z9; mov.b32 u1, {h1,h1}; mul.bf16x2 v5, v5, u1;\n" \
    "mov.b32 {h0,h1}, z10; mov.b32 u1, {h1,h1}; mul.bf16x2 v2, v2, u1;\n" \
    "mma.sync.aligned.m16n8k16.row.col.f32.bf16.bf16.f32 {%100,%101,%102,%103}, {a0,a1,a2,a3}, {v2,v3}, {%100,%101,%102,%103};\n" \
    "tanh.approx.f32 t1, z2;\n" \
    "fma.rn.f32 z2, z2, t1, z2;\n" \
    "tanh.approx.f32 t3, z3;\n" \
    "st.volatile.shared.u32 [%177], %160;\n" \
    "@pr ld.shared.v4.u32 {v0,v1,v2,v3}, [na0+0];\n" \
    "mov.b32 {h0,h1}, z9; mov.b32 u1, {h1,h1}; mul.bf16x2 v4, v4, u1;\n" \
    "mma.sync.aligned.m16n8k16.row.col.f32.bf16.bf16.f32 {%104,%105,%106,%107}, {a0,a1,a2,a3}, {v4,v5}, {%104,%105,%106,%107};\n" \
    "fma.rn.f32 z3, z3, t3, z3;\n" \
    "tanh.approx.f32 t2, z1;\n" \
    "fma.rn.f32 z1, z1, t2, z1;\n" \
    "tanh.approx.f32 t4, z4;\n" \
    "mov.b32 {h0,h1}, z13; mov.b32 u1, {h1,h1}; mul.bf16x2 v13, v13, u1;\n" \
    "tanh.approx.f32 t7, z7;\n" \
    "tanh.approx.f32 t5, z6;\n" \
    "mov.b32 {h0,h1}, z12; mov.b32 u1, {h1,h1}; mul.bf16x2 v9, v9, u1;\n" \
    "mov.b32 {h0,h1}, z14; mov.b32 u1, {h1,h1}; mul.bf16x2 v10, v10, u1;\n" \
    "fma.rn.f32 z4, z4, t4, z4;\n" \
    "mov.b32 {h0,h1}, z12; mov.b32 u1, {h1,h1}; mul.bf16x2 v8, v8, u1;\n" \
    "mma.sync.aligned.m16n8k16.row.col.f32.bf16.bf16.f32 {%112,%113,%114,%115}, {a0,a1,a2,a3}, {v8,v9}, {%112,%113,%114,%115};\n" \
    "mma.sync.aligned.m16n8k16.row.col.f32.bf16.bf16.f32 {%108,%109,%110,%111}, {a0,a1,a2,a3}, {v6,v7}, {%108,%109,%110,%111};\n" \
    "@pr ld.shared.v4.u32 {v4,v5,v6,v7}, [na0+128];\n" \
    "fma.rn.f32 z6, z6, t5, z6;\n" \
    "mma.sync.aligned.m16n8k8.row.col.f32.bf16.bf16.f32 {z8,z9,z10,z11}, {%165,%166}, {rx}, {fz,fz,fz,fz};\n" \
    "mma.sync.aligned.m16n8k8.row.col.f32.bf16.bf16.f32 {y0,y1,y2,y3}, {%169,%170}, {ry}, {fz,fz,fz,fz};\n" \
    "mov.b32 {h0,h1}, z15; mov.b32 u1, {h1,h1}; mul.bf16x2 v14, v14, u1;\n" \
    "and.b32 u2, ex, 14; setp.eq.and.u32 q0, u2, 2, pr; setp.eq.and.u32 q1, u2, 4, pr; setp.eq.and.u32 q2, u2, 8, pr;\n" \
    "mov.b32 {h0,h1}, z14; mov.b32 u1, {h1,h1}; mul.bf16x2 v11, v11, u1;\n" \
    "mma.sync.aligned.m16n8k16.row.col.f32.bf16.bf16.f32 {%116,%117,%118,%119}, {a0,a1,a2,a3}, {v10,v11}, {%116,%117,%118,%119};\n" \
    "@pr ld.shared.v4.u32 {v8,v9,v10,v11}, [na0+512];\n" \
    "tanh.approx.f32 t6, z5;\n" \
    "mov.b32 {h0,h1}, z15; mov.b32 u1, {h1,h1}; mul.bf16x2 v15, v15, u1;\n" \
    "mma.sync.aligned.m16n8k16.row.col.f32.bf16.bf16.f32 {%124,%125,%126,%127}, {a0,a1,a2,a3}, {v14,v15}, {%124,%125,%126,%127};\n" \
    "ld.shared.v4.u32 {e0,e1,ex,e3}, [%160+16];\n" \
    "mov.b32 {h0,h1}, z13; mov.b32 u1, {h1,h1}; mul.bf16x2 v12, v12, u1;\n" \
    "mma.sync.aligned.m16n8k16.row.col.f32.bf16.bf16.f32 {%120,%121,%122,%123}, {a0,a1,a2,a3}, {v12,v13}, {%120,%121,%122,%123};\n" \
    "cvt.rn.bf16x2.f32 b0, y2, y0; cvt.rn.bf16x2.f32 b1, y3, y1;\n" \
    "selp.b32 a0, b0, 0, p0; selp.b32 a1, b0, 0, p1; selp.b32 a2, b1, 0, p0; selp.b32 a3, b1, 0, p1;\n" \
    "D:\n" \
    "@q0 bra.uni S0;\n" \
    "@q2 bra.uni S2;\n" \
    "@q1 bra.uni S1;\n" \
    "SLOW:\n" \
    "ld.shared.v2.u32 {gx,gy}, [%160+8];\n" \
    "and.b32 u2, gx, 1; and.b32 gx, gx, 14; setp.eq.u32 q0, gx, 2; setp.eq.u32 q1, gx, 4; setp.eq.u32 q2, gx, 8;\n" \
    "@q0 bra.uni W0;\n" \
    "@q1 bra.uni W1;\n" \
    "@!q2 bra.uni DONE;\n" \
    "W2:\n" \
    "mbarrier.try_wait.parity.shared::cta.b64 pr, [gy], u2;\n" \
    "@!pr bra.uni X2;\n" \
    "ld.shared.v4.u32 {v0,v1,v2,v3}, [na0+0];\n" \
    "ld.shared.v4.u32 {v4,v5,v6,v7}, [na0+128];\n" \
    "ld.shared.v4.u32 {v8,v9,v10,v11}, [na0+512];\n" \
    "bra.uni S2;\n" \
    "X2:\n" \
    "mov.u32 cnt, %%globaltimer_hi; ld.shared.u32 gx, [%177+32]; sub.u32 cnt, cnt, gx; setp.lt.u32 pr, cnt, 2;\n" \
    "@pr bra.uni W2;\n" \
    "bra.uni DONE;\n" \
    "W0:\n" \
    "mbarrier.try_wait.parity.shared::cta.b64 pr, [gy], u2;\n" \
    "@!pr bra.uni X0;\n" \
    "ld.shared.v4.u32 {v0,v1,v2,v3}, [na0+0];\n" \
    "ld.shared.v4.u32 {v4,v5,v6,v7}, [na0+128];\n" \
    "ld.shared.v4.u32 {v8,v9,v10,v11}, [na0+512];\n" \
    "bra.uni S0;\n" \
    "X0:\n" \
    "mov.u32 cnt, %%globaltimer_hi; ld.shared.u32 gx, [%177+32]; sub.u32 cnt, cnt, gx; setp.lt.u32 pr, cnt, 2;\n" \
    "@pr bra.uni W0;\n" \
    "bra.uni DONE;\n" \
    "W1:\n" \
    "mbarrier.try_wait.parity.shared::cta.b64 pr, [gy], u2;\n" \
    "@!pr bra.uni X1;\n" \
    "ld.shared.v4.u32 {v0,v1,v2,v3}, [na0+0];\n" \
    "ld.shared.v4.u32 {v4,v5,v6,v7}, [na0+128];\n" \
    "ld.shared.v4.u32 {v8,v9,v10,v11}, [na0+512];\n" \
    "bra.uni S1;\n" \
    "X1:\n" \
    "mov.u32 cnt, %%globaltimer_hi; ld.shared.u32 gx, [%177+32]; sub.u32 cnt, cnt, gx; setp.lt.u32 pr, cnt, 2;\n" \
    "@pr bra.uni W1;\n" \
    "bra.uni DONE;\n" \
    "DONE:\n" \
    "mov.b32 u2, z0; xor.b32 %160, %160, u2;\n" \
    "mov.b32 u2, z2; xor.b32 %160, %160, u2;\n" \
    "mov.b32 u2, z1; xor.b32 %160, %160, u2;\n" \
    "mov.b32 u2, z3; xor.b32 %160, %160, u2;\n" \
    "mov.b32 u2, z4; xor.b32 %160, %160, u2;\n" \
    "mov.b32 u2, z6; xor.b32 %160, %160, u2;\n" \
    "}\n" \
    ""
#define MAIN_LOOP_ACC(A) \
    "+f"(A[0][0]), "+f"(A[0][1]), "+f"(A[0][2]), "+f"(A[0][3]), "+f"(A[1][0]), "+f"(A[1][1]), "+f"(A[1][2]), "+f"(A[1][3]), \
    "+f"(A[2][0]), "+f"(A[2][1]), "+f"(A[2][2]), "+f"(A[2][3]), "+f"(A[3][0]), "+f"(A[3][1]), "+f"(A[3][2]), "+f"(A[3][3]), \
    "+f"(A[4][0]), "+f"(A[4][1]), "+f"(A[4][2]), "+f"(A[4][3]), "+f"(A[5][0]), "+f"(A[5][1]), "+f"(A[5][2]), "+f"(A[5][3]), \
    "+f"(A[6][0]), "+f"(A[6][1]), "+f"(A[6][2]), "+f"(A[6][3]), "+f"(A[7][0]), "+f"(A[7][1]), "+f"(A[7][2]), "+f"(A[7][3]), \
    "+f"(A[8][0]), "+f"(A[8][1]), "+f"(A[8][2]), "+f"(A[8][3]), "+f"(A[9][0]), "+f"(A[9][1]), "+f"(A[9][2]), "+f"(A[9][3]), \
    "+f"(A[10][0]), "+f"(A[10][1]), "+f"(A[10][2]), "+f"(A[10][3]), "+f"(A[11][0]), "+f"(A[11][1]), "+f"(A[11][2]), "+f"(A[11][3]), \
    "+f"(A[12][0]), "+f"(A[12][1]), "+f"(A[12][2]), "+f"(A[12][3]), "+f"(A[13][0]), "+f"(A[13][1]), "+f"(A[13][2]), "+f"(A[13][3]), \
    "+f"(A[14][0]), "+f"(A[14][1]), "+f"(A[14][2]), "+f"(A[14][3]), "+f"(A[15][0]), "+f"(A[15][1]), "+f"(A[15][2]), "+f"(A[15][3]), \
    "+f"(A[16][0]), "+f"(A[16][1]), "+f"(A[16][2]), "+f"(A[16][3]), "+f"(A[17][0]), "+f"(A[17][1]), "+f"(A[17][2]), "+f"(A[17][3]), \
    "+f"(A[18][0]), "+f"(A[18][1]), "+f"(A[18][2]), "+f"(A[18][3]), "+f"(A[19][0]), "+f"(A[19][1]), "+f"(A[19][2]), "+f"(A[19][3]), \
    "+f"(A[20][0]), "+f"(A[20][1]), "+f"(A[20][2]), "+f"(A[20][3]), "+f"(A[21][0]), "+f"(A[21][1]), "+f"(A[21][2]), "+f"(A[21][3]), \
    "+f"(A[22][0]), "+f"(A[22][1]), "+f"(A[22][2]), "+f"(A[22][3]), "+f"(A[23][0]), "+f"(A[23][1]), "+f"(A[23][2]), "+f"(A[23][3]), \
    "+f"(A[24][0]), "+f"(A[24][1]), "+f"(A[24][2]), "+f"(A[24][3]), "+f"(A[25][0]), "+f"(A[25][1]), "+f"(A[25][2]), "+f"(A[25][3]), \
    "+f"(A[26][0]), "+f"(A[26][1]), "+f"(A[26][2]), "+f"(A[26][3]), "+f"(A[27][0]), "+f"(A[27][1]), "+f"(A[27][2]), "+f"(A[27][3]), \
    "+f"(A[28][0]), "+f"(A[28][1]), "+f"(A[28][2]), "+f"(A[28][3]), "+f"(A[29][0]), "+f"(A[29][1]), "+f"(A[29][2]), "+f"(A[29][3]), \
    "+f"(A[30][0]), "+f"(A[30][1]), "+f"(A[30][2]), "+f"(A[30][3]), "+f"(A[31][0]), "+f"(A[31][1]), "+f"(A[31][2]), "+f"(A[31][3]), \
    "+f"(A[32][0]), "+f"(A[32][1]), "+f"(A[32][2]), "+f"(A[32][3]), "+f"(A[33][0]), "+f"(A[33][1]), "+f"(A[33][2]), "+f"(A[33][3]), \
    "+f"(A[34][0]), "+f"(A[34][1]), "+f"(A[34][2]), "+f"(A[34][3]), "+f"(A[35][0]), "+f"(A[35][1]), "+f"(A[35][2]), "+f"(A[35][3]), \
    "+f"(A[36][0]), "+f"(A[36][1]), "+f"(A[36][2]), "+f"(A[36][3]), "+f"(A[37][0]), "+f"(A[37][1]), "+f"(A[37][2]), "+f"(A[37][3]), \
    "+f"(A[38][0]), "+f"(A[38][1]), "+f"(A[38][2]), "+f"(A[38][3]), "+f"(A[39][0]), "+f"(A[39][1]), "+f"(A[39][2]), "+f"(A[39][3])
#define PRODUCER_PTX \
    "{\n" \
    ".reg .b32 r<4>, d, b, c, t, w, n; .reg .pred p, q;\n" \
    "mov.b32 n, 0;\n" \
    "TOP:\n" \
    "ld.shared.v4.u32 {r0,r1,r2,r3}, [%0+%16];\n" \
    "ld.shared.u16 t, [%0+72]; setp.ge.u32 q, %0, %10;\n" \
    "mov.u32 c, %%globaltimer_lo; sub.s32 c, c, %11; sub.s32 c, c, t; setp.ge.s32 p, c, 0;\n" \
    "@p bra.uni G0;\n" \
    "T0:\n" \
    "nanosleep.u32 64;\n" \
    "mov.u32 c, %%globaltimer_lo; sub.s32 c, c, %11; sub.s32 c, c, t; setp.lt.s32 p, c, 0;\n" \
    "@p bra.uni T0;\n" \
    "G0:\n" \
    "ld.volatile.shared.u32 w, [%9]; setp.lt.or.u32 p, w, %0, q;\n" \
    "@p bra.uni W0;\n" \
    "add.u32 b, %3, 0;\n" \
    "mbarrier.arrive.expect_tx.shared::cta.b64 _, [b], %12;\n" \
    "add.u32 d, %2, 0*%15+1024;\n" \
    "cp.async.bulk.tensor.2d.shared::cluster.global.tile.mbarrier::complete_tx::bytes [d], [%4, {%5, r0}], [b];\n" \
    "add.u32 d, %2, 1*%15+1024;\n" \
    "cp.async.bulk.tensor.2d.shared::cluster.global.tile.mbarrier::complete_tx::bytes [d], [%4, {%6, r1}], [b];\n" \
    "add.u32 d, %2, 2*%15+1024;\n" \
    "cp.async.bulk.tensor.2d.shared::cluster.global.tile.mbarrier::complete_tx::bytes [d], [%4, {%7, r2}], [b];\n" \
    "add.u32 d, %2, 3*%15+1024;\n" \
    "cp.async.bulk.tensor.2d.shared::cluster.global.tile.mbarrier::complete_tx::bytes [d], [%4, {%8, r3}], [b];\n" \
    "add.u32 %0, %0, 16;\n" \
    "ld.shared.v4.u32 {r0,r1,r2,r3}, [%0+%16];\n" \
    "ld.shared.u16 t, [%0+72]; setp.ge.u32 q, %0, %10;\n" \
    "mov.u32 c, %%globaltimer_lo; sub.s32 c, c, %11; sub.s32 c, c, t; setp.ge.s32 p, c, 0;\n" \
    "@p bra.uni G1;\n" \
    "T1:\n" \
    "nanosleep.u32 64;\n" \
    "mov.u32 c, %%globaltimer_lo; sub.s32 c, c, %11; sub.s32 c, c, t; setp.lt.s32 p, c, 0;\n" \
    "@p bra.uni T1;\n" \
    "G1:\n" \
    "ld.volatile.shared.u32 w, [%9]; setp.lt.or.u32 p, w, %0, q;\n" \
    "@p bra.uni W1;\n" \
    "add.u32 b, %3, 8;\n" \
    "mbarrier.arrive.expect_tx.shared::cta.b64 _, [b], %12;\n" \
    "add.u32 d, %2, 0*%15+2048;\n" \
    "cp.async.bulk.tensor.2d.shared::cluster.global.tile.mbarrier::complete_tx::bytes [d], [%4, {%5, r0}], [b];\n" \
    "add.u32 d, %2, 1*%15+2048;\n" \
    "cp.async.bulk.tensor.2d.shared::cluster.global.tile.mbarrier::complete_tx::bytes [d], [%4, {%6, r1}], [b];\n" \
    "add.u32 d, %2, 2*%15+2048;\n" \
    "cp.async.bulk.tensor.2d.shared::cluster.global.tile.mbarrier::complete_tx::bytes [d], [%4, {%7, r2}], [b];\n" \
    "add.u32 d, %2, 3*%15+2048;\n" \
    "cp.async.bulk.tensor.2d.shared::cluster.global.tile.mbarrier::complete_tx::bytes [d], [%4, {%8, r3}], [b];\n" \
    "add.u32 %0, %0, 16;\n" \
    "ld.shared.v4.u32 {r0,r1,r2,r3}, [%0+%16];\n" \
    "ld.shared.u16 t, [%0+72]; setp.ge.u32 q, %0, %10;\n" \
    "mov.u32 c, %%globaltimer_lo; sub.s32 c, c, %11; sub.s32 c, c, t; setp.ge.s32 p, c, 0;\n" \
    "@p bra.uni G2;\n" \
    "T2:\n" \
    "nanosleep.u32 64;\n" \
    "mov.u32 c, %%globaltimer_lo; sub.s32 c, c, %11; sub.s32 c, c, t; setp.lt.s32 p, c, 0;\n" \
    "@p bra.uni T2;\n" \
    "G2:\n" \
    "ld.volatile.shared.u32 w, [%9]; setp.lt.or.u32 p, w, %0, q;\n" \
    "@p bra.uni W2;\n" \
    "add.u32 b, %3, 16;\n" \
    "mbarrier.arrive.expect_tx.shared::cta.b64 _, [b], %12;\n" \
    "add.u32 d, %2, 0*%15+3072;\n" \
    "cp.async.bulk.tensor.2d.shared::cluster.global.tile.mbarrier::complete_tx::bytes [d], [%4, {%5, r0}], [b];\n" \
    "add.u32 d, %2, 1*%15+3072;\n" \
    "cp.async.bulk.tensor.2d.shared::cluster.global.tile.mbarrier::complete_tx::bytes [d], [%4, {%6, r1}], [b];\n" \
    "add.u32 d, %2, 2*%15+3072;\n" \
    "cp.async.bulk.tensor.2d.shared::cluster.global.tile.mbarrier::complete_tx::bytes [d], [%4, {%7, r2}], [b];\n" \
    "add.u32 d, %2, 3*%15+3072;\n" \
    "cp.async.bulk.tensor.2d.shared::cluster.global.tile.mbarrier::complete_tx::bytes [d], [%4, {%8, r3}], [b];\n" \
    "add.u32 %0, %0, 16;\n" \
    "ld.shared.v4.u32 {r0,r1,r2,r3}, [%0+%16];\n" \
    "ld.shared.u16 t, [%0+72]; setp.ge.u32 q, %0, %10;\n" \
    "mov.u32 c, %%globaltimer_lo; sub.s32 c, c, %11; sub.s32 c, c, t; setp.ge.s32 p, c, 0;\n" \
    "@p bra.uni G3;\n" \
    "T3:\n" \
    "nanosleep.u32 64;\n" \
    "mov.u32 c, %%globaltimer_lo; sub.s32 c, c, %11; sub.s32 c, c, t; setp.lt.s32 p, c, 0;\n" \
    "@p bra.uni T3;\n" \
    "G3:\n" \
    "ld.volatile.shared.u32 w, [%9]; setp.lt.or.u32 p, w, %0, q;\n" \
    "@p bra.uni W3;\n" \
    "add.u32 b, %3, 24;\n" \
    "mbarrier.arrive.expect_tx.shared::cta.b64 _, [b], %12;\n" \
    "add.u32 d, %2, 0*%15+4096;\n" \
    "cp.async.bulk.tensor.2d.shared::cluster.global.tile.mbarrier::complete_tx::bytes [d], [%4, {%5, r0}], [b];\n" \
    "add.u32 d, %2, 1*%15+4096;\n" \
    "cp.async.bulk.tensor.2d.shared::cluster.global.tile.mbarrier::complete_tx::bytes [d], [%4, {%6, r1}], [b];\n" \
    "add.u32 d, %2, 2*%15+4096;\n" \
    "cp.async.bulk.tensor.2d.shared::cluster.global.tile.mbarrier::complete_tx::bytes [d], [%4, {%7, r2}], [b];\n" \
    "add.u32 d, %2, 3*%15+4096;\n" \
    "cp.async.bulk.tensor.2d.shared::cluster.global.tile.mbarrier::complete_tx::bytes [d], [%4, {%8, r3}], [b];\n" \
    "add.u32 %0, %0, 16;\n" \
    "ld.shared.v4.u32 {r0,r1,r2,r3}, [%0+%16];\n" \
    "ld.shared.u16 t, [%0+72]; setp.ge.u32 q, %0, %10;\n" \
    "mov.u32 c, %%globaltimer_lo; sub.s32 c, c, %11; sub.s32 c, c, t; setp.ge.s32 p, c, 0;\n" \
    "@p bra.uni G4;\n" \
    "T4:\n" \
    "nanosleep.u32 64;\n" \
    "mov.u32 c, %%globaltimer_lo; sub.s32 c, c, %11; sub.s32 c, c, t; setp.lt.s32 p, c, 0;\n" \
    "@p bra.uni T4;\n" \
    "G4:\n" \
    "ld.volatile.shared.u32 w, [%9]; setp.lt.or.u32 p, w, %0, q;\n" \
    "@p bra.uni W4;\n" \
    "add.u32 b, %3, 32;\n" \
    "mbarrier.arrive.expect_tx.shared::cta.b64 _, [b], %12;\n" \
    "add.u32 d, %2, 0*%15+5120;\n" \
    "cp.async.bulk.tensor.2d.shared::cluster.global.tile.mbarrier::complete_tx::bytes [d], [%4, {%5, r0}], [b];\n" \
    "add.u32 d, %2, 1*%15+5120;\n" \
    "cp.async.bulk.tensor.2d.shared::cluster.global.tile.mbarrier::complete_tx::bytes [d], [%4, {%6, r1}], [b];\n" \
    "add.u32 d, %2, 2*%15+5120;\n" \
    "cp.async.bulk.tensor.2d.shared::cluster.global.tile.mbarrier::complete_tx::bytes [d], [%4, {%7, r2}], [b];\n" \
    "add.u32 d, %2, 3*%15+5120;\n" \
    "cp.async.bulk.tensor.2d.shared::cluster.global.tile.mbarrier::complete_tx::bytes [d], [%4, {%8, r3}], [b];\n" \
    "add.u32 %0, %0, 16;\n" \
    "setp.lt.u32 p, r0, %1;\n" \
    "@p bra.uni TOP;\n" \
    "mov.b32 %1, 0xffffffff; setp.ne.u32 p, %14, 0;\n" \
    "@p cp.async.bulk.prefetch.L2.global [%13], %14;\n" \
    "bra.uni TOP;\n" \
    "W0:\n" \
    "add.u32 n, n, 1; setp.lt.and.u32 p, n, 0x1000000, !q;\n" \
    "@p bra.uni G0;\n" \
    "bra.uni END;\n" \
    "W1:\n" \
    "add.u32 n, n, 1; setp.lt.and.u32 p, n, 0x1000000, !q;\n" \
    "@p bra.uni G1;\n" \
    "bra.uni END;\n" \
    "W2:\n" \
    "add.u32 n, n, 1; setp.lt.and.u32 p, n, 0x1000000, !q;\n" \
    "@p bra.uni G2;\n" \
    "bra.uni END;\n" \
    "W3:\n" \
    "add.u32 n, n, 1; setp.lt.and.u32 p, n, 0x1000000, !q;\n" \
    "@p bra.uni G3;\n" \
    "bra.uni END;\n" \
    "W4:\n" \
    "add.u32 n, n, 1; setp.lt.and.u32 p, n, 0x1000000, !q;\n" \
    "@p bra.uni G4;\n" \
    "bra.uni END;\n" \
    "END:\n" \
    "}\n" \
    ""

__device__ __forceinline__ void wgmma_n128(float (&d)[64], const uint32_t (&a)[4], uint64_t desc, int acc) {
    asm volatile("{\n\t.reg .pred p;\n\tsetp.ne.u32 p, %69, 0;\n\t"
        "wgmma.mma_async.sync.aligned.m64n128k16.f32.bf16.bf16 {%0,%1,%2,%3,%4,%5,%6,%7,%8,%9,%10,%11,%12,%13,%14,%15,"
        "%16,%17,%18,%19,%20,%21,%22,%23,%24,%25,%26,%27,%28,%29,%30,%31,%32,%33,%34,%35,%36,%37,%38,%39,%40,%41,%42,%43,%44,%45,%46,%47,"
        "%48,%49,%50,%51,%52,%53,%54,%55,%56,%57,%58,%59,%60,%61,%62,%63}, {%64,%65,%66,%67}, %68, p, 1, 1, 1;\n\t}"
        : "+f"(d[0]), "+f"(d[1]), "+f"(d[2]), "+f"(d[3]), "+f"(d[4]), "+f"(d[5]), "+f"(d[6]), "+f"(d[7]),
          "+f"(d[8]), "+f"(d[9]), "+f"(d[10]), "+f"(d[11]), "+f"(d[12]), "+f"(d[13]), "+f"(d[14]), "+f"(d[15]),
          "+f"(d[16]), "+f"(d[17]), "+f"(d[18]), "+f"(d[19]), "+f"(d[20]), "+f"(d[21]), "+f"(d[22]), "+f"(d[23]),
          "+f"(d[24]), "+f"(d[25]), "+f"(d[26]), "+f"(d[27]), "+f"(d[28]), "+f"(d[29]), "+f"(d[30]), "+f"(d[31]),
          "+f"(d[32]), "+f"(d[33]), "+f"(d[34]), "+f"(d[35]), "+f"(d[36]), "+f"(d[37]), "+f"(d[38]), "+f"(d[39]),
          "+f"(d[40]), "+f"(d[41]), "+f"(d[42]), "+f"(d[43]), "+f"(d[44]), "+f"(d[45]), "+f"(d[46]), "+f"(d[47]),
          "+f"(d[48]), "+f"(d[49]), "+f"(d[50]), "+f"(d[51]), "+f"(d[52]), "+f"(d[53]), "+f"(d[54]), "+f"(d[55]),
          "+f"(d[56]), "+f"(d[57]), "+f"(d[58]), "+f"(d[59]), "+f"(d[60]), "+f"(d[61]), "+f"(d[62]), "+f"(d[63])
        : "r"(a[0]), "r"(a[1]), "r"(a[2]), "r"(a[3]), "l"(desc), "r"(acc));
}

#define YFP 1
#define ORD 1
#define ZC 40
#define FEN 0
#define PAIRS 6
#define PT0 2050
#define PDT 36.6
#define NSLEEP 64
#define PFA 8000
template <int ID, int COUNT> __device__ __forceinline__ void bar_sync() { asm volatile("bar.sync %0, %1;" ::"n"(ID), "n"(COUNT) : "memory"); }
template <int ID, int COUNT> __device__ __forceinline__ void bar_arrive() { asm volatile("bar.arrive %0, %1;" ::"n"(ID), "n"(COUNT) : "memory"); }
__device__ __forceinline__ void await(const uint32_t* p, uint32_t n) {
    uint32_t v;
    int guard = 0;
    do asm volatile("ld.relaxed.gpu.global.u32 %0, [%1];" : "=r"(v) : "l"(p) : "memory");
    while (__any_sync(0xffffffffu, v < n) && ++guard < (1 << 20));
}
template <int BYTES>
__device__ __forceinline__ void fill(uint32_t addr, uint4 v, int tid) {
#pragma unroll
    for (int r = 0; r < (BYTES / 16 + NT - 1) / NT; r++)
        sts128_if((r + 1) * NT <= BYTES / 16 || r * NT + tid < BYTES / 16, addr + (r * NT + tid) * 16, v);
}

__device__ __forceinline__ uint32_t group_cap(uint32_t key, int lane) {
    return __reduce_add_sync(0xffffffffu, min(key >> 5, GK)) > KCAP ? KCAP / NG : lane < 16 ? GK : 128 - 2 * GK;
}
template <int NR>
__device__ __forceinline__ void build_list(uint4 lt, uint32_t len, int wl, int lane, int N, uint32_t bin_magic, uint32_t pace) {
    const uint32_t n0 = lt.x >> 5, n01 = n0 + (lt.y >> 5), lh = sb + SM_LH + wl * (LBIN * 4);
    const uint32_t o0 = (lt.x & 31) * GK, o1 = (lt.y & 31) * GK - n0, o2 = (lt.z & 31) * GK - n01;
    uint4 w[NR], e[NR];
    uint32_t p[NR], ba[NR];
#pragma unroll
    for (int j = 0; j < NR; j++) {
        const uint32_t i = j * 32 + lane;
        w[j] = lds128(sb + SM_KSG + (i + (i < n0 ? o0 : i < n01 ? o1 : o2)) * 16);
        e[j].z = i < n0 ? 2 : i < n01 ? 4 : 8;
    }
#pragma unroll
    for (int j = 0; j < NR; j++) {
        const uint32_t key = min(((w[j].x & 0x1fff8) + (w[j].y & 0x1fff8) + (w[j].z & 0x1fff8) + (w[j].w & 0x1fff8)) >> 2, N * 8 - 8);
        ba[j] = j * 32 + lane < len ? lh + (key * bin_magic >> 21) * 4 : sb + SM_DUM + lane * 4;
        e[j].z |= min(__umulhi(key, pace), 0xffff) & 0xfff0;
    }
#pragma unroll
    for (int j = 0; j < NR; j++) p[j] = atoms_inc(ba[j]);
    __syncwarp();
    const uint4 u = lds128(lh + lane * 16);
#pragma unroll
    for (int j = 0; j < NR; j++) {
        e[j].x = (__byte_perm(w[j].x, w[j].y, 0x7632) & 0xfff0fff0u) | 1u << (w[j].x & 3) | 0x10000u << (w[j].y & 3);
        e[j].y = (__byte_perm(w[j].z, w[j].w, 0x7632) & 0xfff0fff0u) | 1u << (w[j].z & 3) | 0x10000u << (w[j].w & 3);
        asm volatile("" : "+r"(e[j].x), "+r"(e[j].y), "+r"(e[j].z));
    }
    const uint32_t sum = u.x + u.y + u.z + u.w, ex = warp_incl_scan(sum) - sum;
    sts128_if(true, lh + lane * 16, make_uint4(ex, ex + u.x, ex + u.x + u.y, ex + u.x + u.y + u.z));
    __syncwarp();
#pragma unroll
    for (int j = 0; j < NR; j++) p[j] += lds32(ba[j]);
#pragma unroll
    for (int j = 0; j < NR; j++) {
        const uint32_t turn = (p[j] * SMG) >> 16, slot = p[j] - turn * S;
        sts128_if(p[j] < len, sb + SM_SRC + (lt.w + p[j]) * 16, make_uint4(w[j].x & 0x1fff8, w[j].y & 0x1fff8, w[j].z & 0x1fff8, w[j].w & 0x1fff8));
        sts128_if(p[j] < len, sb + SM_LIST + (lt.w + p[j]) * 16,
                  make_uint4(e[j].x, e[j].y, e[j].z | (turn & 1) | slot << 26, sb + SM_BAR + (wl * S + slot) * 8));
    }
}
__device__ __forceinline__ bool next_excess(const Scratch* scr, const __nv_bfloat16* x, uint32_t va0) {
    uint32_t tid, cta;
    asm volatile("mov.u32 %0, %tid.x;" : "=r"(tid));
    asm volatile("mov.u32 %0, %ctaid.x;" : "=r"(cta));
    const int lane = tid & 31, wl = tid >> 5;
    const uint32_t bar_w = sb + SM_BAR + NW * S * 8, own = sb + SM_SRC + wl * 128, st = sb + SM_STATE + wl * 16;
    const uint32_t grp = lds32(sb + SM_MISC + 64 + wl * 4);
    uint4 c = lds128(st);
    __syncwarp();
    for (; c.x <= NCTA; c.x++, c.y = 0) {
        if (c.y == 0 && c.z == 0)
            c.x += __reduce_min_sync(0xffffffffu, c.x + lane >= NCTA || (lds32(sb + SM_SEG + min(c.x + lane, NCTA - 1) * 4) >> 12) > MBE ? lane : 31);
        const uint32_t loc = lds32(sb + SM_SEG + min(c.x, NCTA - 1) * 4);
        const int n = c.x < NCTA ? (int)(loc >> 12) - MBE : lds32(sb + SM_MISC + 12);
        for (; (int)c.y < n; c.y += 32, c.z = 0) {
            uint2 u = make_uint2(0xffffffffu, c.x * SLICE + (loc & 0xfff) + MBE + c.y + lane);
            if ((int)c.y + lane < n) {
                if (c.x < NCTA) u.x = __ldcg(scr->ss + u.y);
                else u = __ldcg(scr->exc + cta * MBW + c.y + lane);
            }
            const uint32_t gw = u.x >> 25 & 31, ja = gw == (grp & 31) ? 1 : gw == (grp >> 5 & 31) ? 2 : gw == grp >> 10 ? 3 : 0;
            const unsigned todo = __ballot_sync(0xffffffffu, ja) & ~c.z;
            if (!todo) continue;
            const uint32_t jf = __shfl_sync(0xffffffffu, ja, __ffs(todo) - 1);
            const unsigned m = todo & __ballot_sync(0xffffffffu, ja == jf);
            const uint32_t from = __fns(m, 0, (lane & 3) + 1);
            const bool pad = from > 31;
            c.z |= __reduce_or_sync(0xffffffffu, pad ? 0 : 1u << from);
            if (!(todo & ~c.z)) { c.y += 32; c.z = 0; }
            u.x = __shfl_sync(0xffffffffu, u.x, pad ? __ffs(m) - 1 : from);
            u.y = __shfl_sync(0xffffffffu, u.y, from);
            const uint32_t slot = (lds32(sb + SM_MISC + 32 + wl * 4) / 64 + 1) % S;
#pragma unroll 1
            for (int k = 0; k < 8; k++)
                cp16((va0 ^ (k & 4) * 8) + slot * 1024 + (k & 1) * 128 + (k & 2) * 256,
                     reinterpret_cast<const uint4*>(x) + (size_t)(u.x >> 3 & 0x3fff) * 64 + chunk_of(k, lane >> 2));
            mbar_wait(bar_w, 0);
            if (lane < 4) {
                if (!pad) cp16(own + 64 + lane * 16, scr->rec + u.y);
                asm volatile("st.shared.u16 [%0], %1;" ::"r"(own + lane * 2),
                             "h"((uint16_t)(((pad ? sb + SM_ZERO : own + 64 + lane * 16) - sb - SM_REC) | 1u << (u.x & 3))) : "memory");
                sts32_if(lane == 0, own + 8, 1u << jf | slot << 26);
                sts32_if(lane == 0, own + 12, bar_w);
                sts128_if(lane == 0, own + 16, make_uint4(0, 0, 0, bar_w));
                sts128_if(lane == 0, st, c);
            }
            asm volatile("cp.async.wait_all;" ::: "memory");
            __syncwarp();
            return true;
        }
    }
    return false;
}

template <int MODE>
__global__ void __launch_bounds__(NT, 1)
tfn_kernel(const int* __restrict__ dst, const int* __restrict__ src, Scratch* scr, int E, int slice,
           int N, int npc, uint32_t npc_magic, uint32_t bin_magic, const uint2* __restrict__ Y, const uint2* __restrict__ ef,
           const __nv_bfloat16* __restrict__ w_rad, const __nv_bfloat16* __restrict__ cg, const __nv_bfloat16* __restrict__ x,
           const __nv_bfloat16* __restrict__ w_mix, __nv_bfloat16* __restrict__ out, uint32_t pace,
           const __grid_constant__ CUtensorMap xmap, const __grid_constant__ CUtensorMap wmap) {
    extern __shared__ __align__(1024) uint8_t smem[];
    const int tid = threadIdx.x, lane = tid & 31, warp = __shfl_sync(0xffffffffu, tid >> 5, 0);
    const int cta = blockIdx.x;
    const uint32_t bar_w = sb + SM_BAR + NW * S * 8, bar_raw = bar_w + 8, bar_rec = bar_w + 16, bar_mb = bar_w + 24;
    auto prefetch_x = [&](int chunk) {
        const int row = (chunk * NCTA + cta) * 8;
        if (row < N)
            asm volatile("cp.async.bulk.prefetch.L2.global [%0], %1;" ::"l"(x + (size_t)row * 512), "r"(min(8, N - row) * 1024));
    };

    const int g = lane >> 2, t = lane & 3;
    uint32_t wz[4][2], wt[2];
    auto weights = [&]() {
            const uint32_t* wr = reinterpret_cast<const uint32_t*>(w_rad) + (t & 1) * 128;
            const uint16_t* cp = reinterpret_cast<const uint16_t*>(cg) + (t >> 1) * 32 + (t & 1) * 8 + (g & 3);
            const __nv_bfloat162 half = __floats2bfloat162_rn(0.5f, 0.5f);
#pragma unroll
            for (int j = 0; j < 4; j++) {
                uint32_t u0 = __ldg(wr + chunk_of(2 * j + (t >> 1), g)), u1 = __ldg(wr + chunk_of(2 * j + (t >> 1), g) + 64);
                const __nv_bfloat162 h0 = __hmul2(*reinterpret_cast<__nv_bfloat162*>(&u0), half);
                const __nv_bfloat162 h1 = __hmul2(*reinterpret_cast<__nv_bfloat162*>(&u1), half);
                u0 = *reinterpret_cast<const uint32_t*>(&h0);
                u1 = *reinterpret_cast<const uint32_t*>(&h1);
                wz[j][0] = __byte_perm(u0, u1, 0x5410);
                wz[j][1] = __byte_perm(u0, u1, 0x7632);
            }
            wt[0] = __ldg(cp) | ((uint32_t)__ldg(cp + 4) << 16);
            wt[1] = __ldg(cp + 16) | ((uint32_t)__ldg(cp + 20) << 16);
            sts32_if((wz[0][0] ^ wz[0][1] ^ wz[1][0] ^ wz[1][1] ^ wz[2][0] ^ wz[2][1] ^ wz[3][0] ^ wz[3][1] ^ wt[0] ^ wt[1]) == 1,
                     sb + SM_ZERO + 96, 0);
    };

    const int e0 = cta * slice, ne = min(E - e0, slice);
    uint32_t a_d[RA], a_s[RA];
    uint32_t tag = 0;
    if (MODE & 1) {
        const int q = min(e0 / 4 + tid, (E - 1) >> 2), e = min(e0 + 4 * NT + tid, E - 1);
        const int4 d4 = __ldcs(reinterpret_cast<const int4*>(dst) + q);
        a_d[4] = __ldcs(dst + e);
        const int4 s4 = __ldcs(reinterpret_cast<const int4*>(src) + q);
        a_s[4] = __ldcs(src + e);
        a_d[0] = d4.x; a_d[1] = d4.y; a_d[2] = d4.z; a_d[3] = d4.w;
        a_s[0] = s4.x; a_s[1] = s4.y; a_s[2] = s4.z; a_s[3] = s4.w;
    }
    if (MODE == 3) asm volatile("ld.relaxed.gpu.global.u32 %0, [%1];" : "=r"(tag) : "l"(&scr->epoch) : "memory");
    auto load_raw = [&]() {
        const int bytes = max((ne + 1) >> 1, 0) * 16;
        asm volatile("mbarrier.arrive.expect_tx.shared::cta.b64 _, [%0], %1;" ::"r"(bar_raw), "r"(2 * bytes) : "memory");
        if (bytes > 0) {
            asm volatile("cp.async.bulk.shared::cluster.global.mbarrier::complete_tx::bytes [%0], [%1], %2, [%3];"
                         ::"r"(sb + SM_RAWY), "l"(Y + e0), "r"(bytes), "r"(bar_raw) : "memory");
            asm volatile("cp.async.bulk.shared::cluster.global.mbarrier::complete_tx::bytes [%0], [%1], %2, [%3];"
                         ::"r"(sb + SM_RAWF), "l"(ef + e0), "r"(bytes), "r"(bar_raw) : "memory");
        }
    };
    if ((uint32_t)__cvta_generic_to_shared(smem) != sb) __trap();
    if (elect_one()) {
#pragma unroll
        for (int i = 0; i < S; i++)
            if (warp >= NW) mbar_init(sb + SM_BAR + ((warp - NW) * S + i) * 8, 1);
        if (warp == 0) {
            mbar_init(bar_w, NW);
            mbar_init(bar_raw, 1);
            mbar_init(bar_rec, NW);
            mbar_init(bar_mb, 1);
        }
        asm volatile("fence.mbarrier_init.release.cluster;" ::: "memory");
    }
    fill<SM_DUM - SM_HIST>(sb + SM_HIST, make_uint4(0, 0, 0, 0), tid);
    if (MODE & 1) {
        const uint32_t em = EMPTY | lane << (BSH + 2);
        fill<NCTA * ASTR * 4>(sb + SM_AMB, make_uint4(em, em + (1 << BSH), em + (2 << BSH), em + (3 << BSH)), tid);
    }
    sts32_if(tid < 32, sb + SM_AOFF + (NCTA + tid) * 4, SLICE);
    sts32_if(tid < 128, sb + SM_DUM + tid * 4, 0x10000);
    if (MODE & 2) {
        const uint32_t pad = RCAP << 20 | N << 3;
        fill<SM_BAR - SM_ZERO>(sb + SM_ZERO, make_uint4(0, 0, 0, 0), tid);
        fill<NG * GK * 16>(sb + SM_KSG, make_uint4(pad, pad, pad, pad), tid);
    }
    __syncthreads();
    STAMP(15);
    if (warp == 13 && (MODE & 2) && elect_one()) {
        asm volatile("cp.async.bulk.prefetch.L2.global [%0], 1024;" ::"l"(w_rad));
        asm volatile("cp.async.bulk.prefetch.L2.global [%0], 128;" ::"l"(cg));
        asm volatile("prefetch.tensormap [%0];" ::"l"(&xmap) : "memory");
        asm volatile("prefetch.tensormap [%0];" ::"l"(&wmap) : "memory");
    }
    if (MODE & 1) {
        if (YFP == 1 && warp == 14 && elect_one()) load_raw();
        const uint32_t z = lds32(sb + SM_KEY + lane * 4);
        uint32_t cc[RA], rk[RA];
#pragma unroll
        for (int r = 0; r < RA; r++) {
            cc[r] = (r < 4 ? 4 * tid + r : 4 * NT + tid) < ne ? __umulhi(a_d[r], npc_magic + z) : NCTA + lane;
            rk[r] = atoms_inc(sb + SM_HIST + cc[r] * 4);
        }
        if (YFP == 2 && tid == 0) load_raw();
#pragma unroll
        for (int r = 0; r < RA; r++) {
            const uint32_t l = a_d[r] - cc[r] * npc;
            a_s[r] = (l < 64 ? l >> 2 : (l >> 1) - 16) << 25 | ((a_s[r] * (bin_magic + z)) & ((NBIN - 1) << BSH)) | a_s[r] * (8 + z) | (l & (l < 64 ? 3 : 1));
            sts32_if(true, sb + SM_AMB + (cc[r] * ASTR + min(rk[r], MBE)) * 4, a_s[r]);
        }
        tag = (tag & 1) + 1;
        const uint32_t tg = tag << 30;
        STAMP(1);
        __syncthreads();
        auto send = [&](uint32_t* gp, uint4 v) {
            asm volatile("st.relaxed.gpu.global.v4.u32 [%0], {%1,%2,%3,%4};"
                         ::"l"(gp), "r"(v.x | tg), "r"(v.y | tg), "r"(v.z | tg), "r"(v.w | tg) : "memory");
        };
        STAMP(28);
        if (YFP == 3 && warp == 14 && elect_one()) load_raw();
#pragma unroll
        for (int r = 0; r < 3; r++) {
            if (r == 2 && warp != 15) break;
            const uint32_t i = r < 2 ? r * NT + tid : 2 * NT + lane, c = i >> 3;
            send(scr->mb + c * MBW + cta * 32 + (i & 7) * 4, lds128(sb + SM_AMB + c * (ASTR * 4) + (i & 7) * 16));
        }
        if (warp < 9) {
            const uint32_t c = tid >> 1, h = (tid & 1) && c < NCTA ? lds32(sb + SM_HIST + c * 4) : 0;
            uint4 v = lds128(sb + SM_AMB + c * (ASTR * 4) + 128 + (tid & 1) * 16);
            const uint32_t inc = warp_incl_scan(h);
            const uint32_t off = __shfl_sync(0xffffffffu, atoms_add(sb + SM_HIST + 135 * 4 + lane * 4, lane == 31 ? inc : 0), 31) + inc - h;
            if (tid & 1) v.w = h << 12 | off;
            if (c < NCTA) send(scr->mb + c * MBW + MB1 + cta * 8 + (tid & 1) * 4, v);
            sts32_if((tid & 1) && c < NCTA, sb + SM_AOFF + c * 4, off);
        }
        STAMP(2);
        __syncthreads();
        if (MODE == 3 && tid == NT - 1) asm volatile("red.relaxed.gpu.global.add.u32 [%0], 1;" ::"l"(scr->sent + (tag & 1)) : "memory");
        if (YFP == 4 && warp == 6 && elect_one()) load_raw();
        uint32_t ap[2 * RA];
#pragma unroll
        for (int r = 0; r < RA; r++) ap[r] = rk[r] + lds32(sb + SM_AOFF + cc[r] * 4);
        if (max(max(max(rk[0], rk[1]), max(rk[2], rk[3])), rk[4]) >= MBE) {
#pragma unroll
            for (int r = 0; r < RA; r++)
                if (rk[r] >= MBE && cc[r] < NCTA) {
                    __stcg(scr->ss + cta * SLICE + ap[r], a_s[r]);
                    __threadfence();
                }
        }
        if (warp >= NW) {
            asm volatile("st.shared.v2.u32 [%0], {%1, %2};" ::"r"(sb + SM_AP + (tid - NH) * 8), "r"(ap[0] | ap[1] << 16), "r"(ap[2] | ap[3] << 16) : "memory");
            sts32_if(true, sb + SM_AP + NH * 8 + (tid - NH) * 4, ap[4]);
            bar_arrive<1, NT>();
        } else {
            bar_sync<1, NT>();
            const uint2 u = lds64(sb + SM_AP + tid * 8);
            ap[5] = u.x & 0xffff; ap[6] = u.x >> 16; ap[7] = u.y & 0xffff; ap[8] = u.y >> 16;
            ap[9] = lds32(sb + SM_AP + NH * 8 + tid * 4);
            const bool sw = lane & 4;
            mbar_wait(bar_raw, 0);
            STAMP(10);
#pragma unroll
            for (int hh = 0; hh < 2; hh++) {
                const uint32_t a = sb + SM_RAWY + (hh * NH + tid) * 32 + (lane & 4) * 4, b = sb + SM_RAWY + (4 * NT + hh * NH + tid) * 8;
                const uint4 y0 = lds128(a), f0 = lds128(a + SLICE * 8), y1 = lds128(a ^ 16), f1 = lds128((a ^ 16) + SLICE * 8);
                const uint2 y2 = lds64(b), f2 = lds64(b + SLICE * 8);
                const uint32_t* q = ap + hh * RA;
                sts128_if(true, sb + SM_AREC + (sw ? q[2] : q[0]) * 16, make_uint4(f0.x, y0.x, f0.y, y0.y));
                sts128_if(true, sb + SM_AREC + (sw ? q[3] : q[1]) * 16, make_uint4(f0.z, y0.z, f0.w, y0.w));
                sts128_if(true, sb + SM_AREC + (sw ? q[0] : q[2]) * 16, make_uint4(f1.x, y1.x, f1.y, y1.y));
                sts128_if(true, sb + SM_AREC + (sw ? q[1] : q[3]) * 16, make_uint4(f1.z, y1.z, f1.w, y1.w));
                sts128_if(true, sb + SM_AREC + q[4] * 16, make_uint4(f2.x, y2.x, f2.y, y2.y));
            }
            asm volatile("fence.proxy.async.shared::cta;" ::: "memory");
            bar_sync<7, NH>();
            STAMP(25);
            if (MODE == 3 && ORD && warp == NW - 1) bar_sync<9, 64>();
            if (warp == NW - 1 && lane == 0 && ne > 0)
                asm volatile("cp.async.bulk.global.shared::cta.bulk_group [%0], [%1], %2;"
                             ::"l"(scr->rec + cta * SLICE), "r"(sb + SM_AREC), "r"(ne * 16) : "memory");
            if (MODE == 3 && warp == NW - 1) {
                mbar_wait(bar_mb, 0);
                if (lane == 0) asm volatile("red.relaxed.gpu.global.max.u32 [%0], %1;" ::"l"(&scr->sent2[tag & 1].y), "r"(timer32()) : "memory");
            }
            if (MODE == 3) weights();
            if (warp == NW - 1) {
                asm volatile("cp.async.bulk.commit_group;" ::: "memory");
                asm volatile("cp.async.bulk.wait_group 0;" ::: "memory");
                STAMPT(26, NH - 32);
                if (MODE == 3) {
                    if (lane == 0) asm volatile("red.relaxed.gpu.global.add.u32 [%0], 1;" ::"l"(scr->sent2 + (tag & 1)) : "memory");
                    uint2 v;
                    int guard = 0;
                    do asm volatile("ld.relaxed.gpu.global.v2.u32 {%0, %1}, [%2];" : "=r"(v.x), "=r"(v.y) : "l"(scr->sent2 + (tag & 1)) : "memory");
                    while (__any_sync(0xffffffffu, v.x < NCTA) && ++guard < (1 << 20));
                    if (lane == 0) asm volatile("mbarrier.arrive.shared::cta.b64 _, [%0];" ::"r"(bar_raw) : "memory");
                    sts32_if(true, sb + SM_MISC + 4, v.y + PT0);
                }
            }
        }
    } else {
        tag = 1;
    }
    if (!(MODE & 2)) return;
    const int wl = warp & (NW - 1);
    const uint32_t ring = sb + SM_RING + wl * (S * 1024);
    const uint32_t bars = sb + SM_BAR + wl * (S * 8);
    const uint32_t pos = bar_w + 32 + wl * 4;

    if (warp >= NW) {
        uint32_t ss[RL + 8], rk[RL + 7];
        const uint32_t sl = wl + 8 * lane;
        const uint32_t* mp = scr->mb + cta * MBW + wl * 32 + lane;
        const uint4* mq = reinterpret_cast<const uint4*>(scr->mb + cta * MBW + MB1) + min(sl, NCTA - 1) * 2;
        const uint32_t tg = tag << 30, empty = EMPTY | lane << BSH;
        if (wl == 0) {
            if (MODE == 3) await(scr->sent + (tag & 1), NCTA);
            STAMPT(11, NH);
            if (elect_one()) {
                asm volatile("mbarrier.arrive.expect_tx.shared::cta.b64 _, [%0], %1;" ::"r"(bar_mb), "n"(MBW * 4) : "memory");
                asm volatile("cp.async.bulk.shared::cluster.global.mbarrier::complete_tx::bytes [%0], [%1], %2, [%3];"
                             ::"r"(sb + SM_AMB), "l"(scr->mb + cta * MBW), "n"(MBW * 4), "r"(bar_mb) : "memory");
            }
            if (MODE == 3 && ORD) bar_arrive<9, 64>();
            if (MODE != 3) sts32_if(true, sb + SM_MISC + 4, timer32() + PT0);
        }
        mbar_wait(bar_mb, 0);
        STAMPT(3, NH);
        uint4 v0 = lds128(sb + SM_AMB + (MB1 + min(sl, NCTA - 1) * 8) * 4), v1 = lds128(sb + SM_AMB + (MB1 + min(sl, NCTA - 1) * 8) * 4 + 16);
#pragma unroll
        for (int r = 0; r < RL; r++) ss[r] = lds32(sb + SM_AMB + (r * NH + tid - NH) * 4);
        for (int guard = 0;; guard++) {
            ss[RL] = v0.x; ss[RL + 1] = v0.y; ss[RL + 2] = v0.z; ss[RL + 3] = v0.w;
            ss[RL + 4] = v1.x; ss[RL + 5] = v1.y; ss[RL + 6] = v1.z; ss[RL + 7] = v1.w;
            uint32_t bad = 0;
#pragma unroll
            for (int r = 0; r < RL + 8; r++) bad |= ss[r] ^ tg;
            if (!__any_sync(0xffffffffu, bad >> 30) || guard == 1 << 20) break;
#pragma unroll
            for (int r = 0; r < RL; r++) asm volatile("ld.relaxed.gpu.global.u32 %0, [%1];" : "=r"(ss[r]) : "l"(mp + r * NH) : "memory");
            v0 = ldg128_relaxed(mq);
            v1 = ldg128_relaxed(mq + 1);
        }
        STAMPT(4, NH);
        if (wl + 8 * (RL - 1) >= NCTA) ss[RL - 1] = empty;
#pragma unroll
        for (int r = 0; r < RL; r++) rk[r] = atoms_add(sb + SM_BIN + (ss[r] >> (BSH - 2) & (NBIN * 128 - 4)), 4);
        const uint32_t cnt = sl < NCTA ? ss[RL + 7] >> 12 & 0xfff : 0;
        const bool late = __any_sync(0xffffffffu, cnt > 32);
        if (late) {
#pragma unroll
            for (int r = RL; r < RL + 7; r++) {
                if (r - RL + 32 >= cnt) ss[r] = empty;
                rk[r] = atoms_add(sb + SM_BIN + (ss[r] >> (BSH - 2) & (NBIN * 128 - 4)), 4);
            }
            sts32_if(cnt > MBE, sb + SM_MISC + 8, 1);
        }
        STAMPT(5, NH);
        bar_sync<3, NH>();
        uint32_t dof;
        {
            constexpr int Q = NBIN / 128;
            const uint32_t a = sb + SM_BIN + wl * (NBIN * 12) + lane * (16 * Q), sw = Q == 2 ? (lane & 4) * 4 : 0;
            uint4 u[3][Q];
            uint32_t sum[3], s0[3];
#pragma unroll
            for (int j = 0; j < 3; j++) {
#pragma unroll
                for (int q = 0; q < Q; q++) u[j][q] = lds128(a + j * (NBIN * 4) + (sw ^ q * 16));
                s0[j] = sum[j] = u[j][0].x + u[j][0].y + u[j][0].z + u[j][0].w;
                if (Q == 2) sum[j] += u[j][1].x + u[j][1].y + u[j][1].z + u[j][1].w;
            }
            uint32_t i01 = sum[0] | sum[1] << 16, i2 = sum[2] | min(cnt, MBE) << 16;
#pragma unroll
            for (int o = 1; o < 32; o <<= 1) {
                scan_step(i01, o);
                scan_step(i2, o);
            }
            dof = atoms_add(sb + SM_MISC - 124 + lane * 4, lane == 31 ? i2 >> 16 : 0);
            const uint32_t inc[3] = {i01 & 0xffff, i01 >> 16, i2 & 0xffff};
#pragma unroll
            for (int j = 0; j < 3; j++) {
#pragma unroll
                for (int q = 0; q < Q; q++) {
                    const uint32_t p = (3 * wl + j) * (GK * 16) + inc[j] - (q == 0 ? (sw ? s0[j] : sum[j]) : (sw ? sum[j] : sum[j] - s0[j]));
                    const uint4 v = u[j][q];
                    sts128_if(true, a + j * (NBIN * 4) + (sw ^ q * 16), make_uint4(p, p + v.x, p + v.x + v.y, p + v.x + v.y + v.z));
                }
                sts32_if(lane == 31, sb + SM_KEY + (3 * wl + j) * 4, (inc[j] + 12) >> 4 << 5 | (3 * wl + j));
            }
            dof = __shfl_sync(0xffffffffu, dof, 31) + (i2 >> 16) - min(cnt, MBE);
            sts32_if(sl < NCTA, sb + SM_SEG + sl * 4, ss[RL + 7] & 0xffffff);
            sts32_if(true, sb + SM_DOFF + (tid - NH) * 4, dof << 20);
            const uint32_t nr = min(min(cnt, MBE), RCAP - min(dof, RCAP));
            const uint64_t from = reinterpret_cast<uint64_t>(scr->rec + (nr ? sl * SLICE + (ss[RL + 7] & 0xfff) : 0));
            sts128_if(true, sb + SM_CPY + (tid - NH) * 16,
                      make_uint4((uint32_t)from, (uint32_t)(from >> 32), nr ? sb + SM_REC + dof * 16 : sb + SM_ZERO + 64, max(nr, 1)));
        }
        STAMPT(12, NH);
        bar_arrive<4, NT - 32>();
        bar_arrive<6, NH + 32>();
        bar_sync<3, NH>();
        const uint32_t key = lds32(sb + SM_KEY + lane * 4), nrec = lds32(sb + SM_MISC);
        uint32_t d20[RL + 3];
#pragma unroll
        for (int r = 0; r < RL; r += 4) {
            const uint4 v = lds128(sb + SM_DOFF + wl * 128 + r * 4);
            d20[r] = v.x; d20[r + 1] = v.y; d20[r + 2] = v.z; d20[r + 3] = v.w;
        }
#pragma unroll
        for (int r = 0; r < RL; r++) rk[r] += lds32(sb + SM_BIN + (ss[r] >> (BSH - 2) & (NBIN * 128 - 4)));
        const uint32_t cap = group_cap(key, lane);
        const uint32_t lim = __any_sync(0xffffffffu, (key >> 5) > cap || nrec > RCAP) ? 0 : 0x20000;
#pragma unroll
        for (int r = 0; r < RL; r++) {
            uint32_t v;
            asm("lop3.b32 %0, %1, 0x1ffff, %2, 0xea;" : "=r"(v) : "r"(ss[r]), "r"(lane << 20));
            sts32_if(rk[r] < lim, sb + SM_KSG + rk[r], v + d20[r]);
        }
        if (late) {
#pragma unroll
            for (int r = RL; r < RL + 7; r++) {
                rk[r] += lds32(sb + SM_BIN + (ss[r] >> (BSH - 2) & (NBIN * 128 - 4)));
                sts32_if(rk[r] < lim, sb + SM_KSG + rk[r], (dof + 32 + r - RL) << 20 | (ss[r] & 0x1ffffu));
            }
        }
        if (lim == 0) {
#pragma unroll
            for (int r = 0; r < RL + 7; r++) {
                if (r >= RL && !late) break;
                const uint32_t rnk = r < RL ? lane : 32 + r - RL, from = r < RL ? r : lane;
                const uint32_t ri = __shfl_sync(0xffffffffu, dof, from) + rnk, gi = __shfl_sync(0xffffffffu, ss[RL + 7] & 0xfff, from) + rnk;
                const bool fits = rk[r] - (ss[r] >> 25 & 31) * (GK * 16) < __shfl_sync(0xffffffffu, cap, ss[r] >> 25) * 16;
                if (rk[r] < 0x20000) {
                    sts32_if(fits, sb + SM_KSG + rk[r], min(ri, RCAP) << 20 | (ss[r] & 0x1ffffu));
                    if (!fits || ri >= RCAP) __stcg(scr->exc + cta * MBW + atoms_inc(sb + SM_MISC + 12), make_uint2(ss[r], (wl + 8 * from) * SLICE + gi));
                }
            }
        }
        STAMPT(13, NH);
        bar_sync<8, NH + 32>();
        STAMPT(31, NH);
        const uint4 lt = lds128(sb + SM_LT + wl * 16);
        const uint32_t lb = lt.w, len = (lt.x >> 5) + (lt.y >> 5) + (lt.z >> 5), le = lb + len;
        if (len <= 96) build_list<3>(lt, len, wl, lane, N, bin_magic, pace);
        else build_list<4>(lt, len, wl, lane, N, bin_magic, pace);
        STAMPT(27, NH);
        if (FEN) asm volatile("fence.proxy.async.shared::cta;" ::: "memory");
        bar_arrive<2, NT>();
        bar_sync<5, NT>();
        STAMPT(6, NH);
        asm volatile("setmaxnreg.dec.sync.aligned.u32 24;");
        const uint32_t z = lds32(sb + SM_ZERO + (lane & 3) * 4);
        const uint32_t bytes = opaque(4096 + z);
        if (elect_one()) {
            const uint4 z0 = lds128v(sb + SM_ZERO);
            uint32_t ka = sb + SM_LIST + lb * 16 - 16 * (S - 1);
            uint32_t pf = max(wl * (NCTA * 64) + PFA - NCTA * 64, 0);
            const int row = ((wl + 2) * NCTA + cta) * 8;
            asm volatile(PRODUCER_PTX : "+r"(ka), "+r"(pf)
                : "r"(ring - 1024 + lds32v(sb + SM_ZERO)), "r"(bars), "l"(reinterpret_cast<uint64_t>(&xmap) + lds32v(sb + SM_ZERO)),
                  "r"(z0.x), "r"(z0.y), "r"(z0.z), "r"(z0.w), "r"(pos), "r"(ka + len * 16), "r"(lds32v(sb + SM_MISC + 4)), "r"(bytes),
                  "l"(x + (size_t)row * 512), "r"(min(max(N - row, 0), 8) * 1024), "n"(RSTR), "n"(SM_SRC - SM_LIST + 16 * (S - 1)) : "memory");
            const uint32_t d = ring + (len - ((len * SMG) >> 16) * S) * 1024;
            STAMPT(20, NW * 32);
            for (int guard = 0; lds32v(pos) + 16 * (S - 1) < sb + SM_LIST + le * 16 && guard < (1 << 20); guard++) __nanosleep(NSLEEP);
            asm volatile("mbarrier.arrive.expect_tx.shared::cta.b64 _, [%0], 4096;" ::"r"(bar_w) : "memory");
#pragma unroll
            for (uint32_t r = 0; r < 8; r++)
                asm volatile("cp.async.bulk.tensor.5d.shared::cluster.global.tile.mbarrier::complete_tx::bytes [%0], [%1, {%2, %3, %4, %5, %6}], [%7];"
                             ::"r"(d + (r >> 1) * RSTR + (r & 1) * 512), "l"(&wmap), "r"((r >> 2) * 64), "r"((r >> 1) & 1),
                               "r"((wl >> 1) & 2), "r"(((r ^ (wl >> 1)) & 1) + (wl & 1) * 2), "r"(wl & 2), "r"(bar_w) : "memory");
            STAMPT(21, NW * 32);
        }
        return;
    }

    {
        if (MODE == 2) weights();
        if (warp == NW - 1) bar_sync<6, NH + 32>();
        else bar_sync<4, NT - 32>();
        if (warp == 0) {
            const uint32_t key = lds32(sb + SM_KEY + lane * 4);
            int rank = 0;
#pragma unroll
            for (int j = 0; j < 4; j++) {
                const uint4 o = lds128(sb + SM_KEY + (lane & 16) * 4 + j * 16);
                rank += ((key - o.x) >> 31) + ((key - o.y) >> 31) + ((key - o.z) >> 31) + ((key - o.w) >> 31);
            }
            const int n2 = 2 * __popc(__ballot_sync(0xffffffffu, key < 32) & 0xff0000);
            const int other = (rank < n2 ? n2 - 1 : 15 + n2) - rank;
            const int li = lane >= 16 ? 7 - rank : min(rank, other) - (rank < n2 ? 0 : n2 / 2);
            sts32_if(lane < NG, sb + SM_LT + (li < 4 ? li : 11 - li) * 16 + (lane >= 16 ? 8 : rank < other ? 0 : 4), min(key >> 5, group_cap(key, lane)) << 5 | lane);
            __syncwarp();
            const uint4 lt = lds128(sb + SM_LT + (lane & 7) * 16);
            const uint32_t len = (lt.x >> 5) + (lt.y >> 5) + (lt.z >> 5);
            uint32_t le = len + 1;
#pragma unroll
            for (int o = 1; o < 8; o <<= 1) scan_step(le, o);
            le -= 1;
            sts32_if(lane < NW, sb + SM_LT + lane * 16 + 12, le - len);
            bar_arrive<8, NH + 32>();
            if (lane < NW) {
                sts32_if(true, sb + SM_LIST + le * 16 + 12, bar_rec);
                sts32_if(true, bar_w + 32 + lane * 4, sb + SM_LIST + (le - len) * 16);
                sts32_if(true, sb + SM_MISC + 32 + lane * 4, (lane * S + len - ((len * SMG) >> 16) * S) * 64);
                sts32_if(true, sb + SM_MISC + 64 + lane * 4, (lt.x & 31) | (lt.y & 31) << 5 | (lt.z & 31) << 10);
            }
        }
        uint4 cp3[RL];
#pragma unroll
        for (int r = 0; r < RL; r++) cp3[r] = lds128(sb + SM_CPY + (wl * 32 + r) * 16);
        const uint32_t total = __reduce_add_sync(0xffffffffu, lane < RL ? lds32(sb + SM_CPY + tid * 16 + 12) * 16 : 0);
        if (FEN) asm volatile("fence.proxy.async.shared::cta;" ::: "memory");
        bar_arrive<5, NT>();
        if (lane == 0) asm volatile("mbarrier.arrive.expect_tx.shared::cta.b64 _, [%0], %1;" ::"r"(bar_rec), "r"(total) : "memory");
        if ((warp & 6) == 2 && lane == 0) prefetch_x(warp & 1);
        if (MODE == 3 && cta == 0 && tid == 64) {
            scr->epoch = tag;
            scr->sent[~tag & 1] = 0;
            scr->sent2[~tag & 1] = make_uint2(0, 0);
        }
        STAMP(22);
        if (MODE == 3) mbar_wait(bar_raw, 1);
        STAMP(24);
        asm volatile("fence.proxy.async.global;" ::: "memory");
        if (elect_one()) {
#pragma unroll
            for (int r = 0; r < RL; r++)
                asm volatile("cp.async.bulk.shared::cluster.global.mbarrier::complete_tx::bytes [%0], [%1], %2, [%3];"
                             ::"r"(cp3[r].z), "l"((uint64_t)cp3[r].y << 32 | cp3[r].x), "r"((cp3[r].w & 0xffff) * 16), "r"(bar_rec) : "memory");
        }
        STAMP(23);
        if (tid == 0 && cta < 128) asm volatile("cp.async.bulk.prefetch.L2.global [%0], 256;" ::"l"(w_mix + cta * 128));
        asm volatile("setmaxnreg.inc.sync.aligned.u32 232;" ::: "memory");
        bar_sync<2, NT>();
        STAMP(14);
    }

    float acc[40][4];
    const uint32_t z = lds32(sb + SM_ZERO + t * 4);
    const float zero = __uint_as_float(z);
#pragma unroll
    for (int j = 0; j < 40; j++) acc[j][0] = acc[j][1] = acc[j][2] = acc[j][3] = j < ZC ? 0.f : zero;
    const bool bact = (g & 1) == (t >> 1);
    mbar_wait(bar_rec, 0);
    STAMP(9);
    {
        auto keep = [&](uint32_t v) { return __shfl_sync(0xffffffffu, v + z, lane); };
        const uint32_t va0 = keep(ring + t * RSTR + (g & 2) * 128 + (g & 1) * 16 + ((((g >> 1) & 2) ^ ((((g >> 1) & 1) + t) & 3)) << 5));
        const uint32_t hm0 = keep(HM0(g >> 2)), hm1 = keep(0x40000u << (g >> 2)), sel = keep(0x1010u + (g >> 1) * 0x22 + t * 0x2200);
        const uint32_t rl = keep(bact ? (t & 1) * 8 : SM_ZERO - SM_REC), rm = keep(bact ? 0xfff0u : 0u);
        uint32_t lp = keep(lds32(pos));
        for (;;) {
        asm volatile(MAIN_LOOP_PTX : MAIN_LOOP_ACC(acc), "+r"(lp)
            : "r"(wz[0][0]), "r"(wz[0][1]), "r"(wz[1][0]), "r"(wz[1][1]), "r"(wz[2][0]), "r"(wz[2][1]), "r"(wz[3][0]), "r"(wz[3][1]),
              "r"(wt[0]), "r"(wt[1]), "r"(va0), "r"(hm0), "r"(hm1), "r"(rl), "r"(rm), "r"(sel), "r"(pos), "n"(sb + SM_REC)
            : "memory");
            sts32_if(true, sb + SM_ZERO + 96, lp);
            const uint2 left = lds64(sb + SM_MISC + 8);
            if (!(left.x | left.y)) break;
            if (!next_excess(scr, x, va0)) break;
            lp = sb + SM_SRC + wl * 128 + (sel & 1);
        }
    }
    STAMP(7);
    const uint32_t grp = lds32(sb + SM_MISC + 64 + wl * 4);

    uint32_t aq[3][8][4];
    auto pack = [&](int j) {
#pragma unroll
        for (int m = 0; m < 8; m++) {
            if (j < 2) {
#pragma unroll
                for (int q = 0; q < 4; q++) {
                    const float* a = acc[16 * j + 2 * m + (q >> 1)] + (q & 1) * 2;
                    asm volatile("cvt.rn.bf16x2.f32 %0, %1, %2;" : "=r"(aq[j][m][q]) : "f"(a[~m & 1]), "f"(a[m & 1]));
                }
            } else {
                aq[2][m][0] = movm(pack_bf16(acc[32 + m][0], acc[32 + m][1]));
                aq[2][m][2] = movm(pack_bf16(acc[32 + m][2], acc[32 + m][3]));
                if (m & 1) {
                    aq[2][m][0] = __byte_perm(aq[2][m][0], 0, 0x1032);
                    aq[2][m][2] = __byte_perm(aq[2][m][2], 0, 0x1032);
                }
                aq[2][m][1] = aq[2][m][3] = 0;
#pragma unroll
                for (int q = 0; q < 4; q++) asm volatile("" : "+r"(aq[2][m][q]));
            }
        }
    };
    pack(0);
    STAMP(16);
    mbar_wait(bar_w, 0);
    STAMP(17);
    const uint4 ws0 = lds128(sb + SM_MISC + 32), ws1 = lds128(sb + SM_MISC + 48);
    const uint32_t ws[8] = {ws0.x, ws0.y, ws0.z, ws0.w, ws1.x, ws1.y, ws1.z, ws1.w};
    const uint64_t wdesc = ((sb + SM_RING) >> 4) | ((uint64_t)(2 * RSTR >> 4) << 16) | ((uint64_t)(RSTR >> 4) << 32) | (1ull << 62);
    const int nloc = min(npc, N - cta * npc);
    uint32_t ln;
    asm volatile("mov.u32 %0, %laneid;" : "=r"(ln));
    const bool odd = ln & 1;
    const int hi = ln >> 1 & 1;
    uint2* op = reinterpret_cast<uint2*>(out) + (size_t)(cta * npc) * 128 + (ln >> 2) + (ln & 1) * 8;
    float d[64];
    auto mix = [&](int job) {
        asm volatile("wgmma.fence.sync.aligned;" ::: "memory");
#pragma unroll
        for (int m = 0; m < 8; m++) wgmma_n128(d, aq[job][m], wdesc + ws[m], m);
        asm volatile("wgmma.commit_group.sync.aligned;" ::: "memory");
    };
    mix(0);
    pack(1);
    pack(2);
#pragma unroll
    for (int job = 0; job < 3; job++) {
        asm volatile("wgmma.wait_group.sync.aligned 0;" ::: "memory");
        if (job == 0) STAMP(18);
        if (job == 2) STAMP(19);
#pragma unroll
        for (int k = 0; k < 64; k++) asm volatile("" : "+f"(d[k]));
        uint32_t pk[32];
#pragma unroll
        for (int k = 0; k < 32; k++) pk[k] = pack_bf16(d[2 * k], d[2 * k + 1]);
        if (job < 2) mix(job + 1);
#pragma unroll
        for (int h = 0; h < (job < 2 ? 2 : 1); h++) {
            const int gj = grp >> (5 * job) & 31;
            const int l = job < 2 ? gj * 4 + 2 * h + hi : gj * 2 + 32 + hi;
            const bool ok = l < nloc;
#pragma unroll
            for (int j = 0; j < 16; j += 2) {
                const uint32_t p0 = movm(pk[2 * j + h]), p1 = movm(pk[2 * j + 2 + h]);
                const uint32_t rv = __shfl_xor_sync(0xffffffffu, odd ? p0 : p1, 1);
                if (ok) op[l * 128 + j * 8] = odd ? make_uint2(rv, p1) : make_uint2(p0, rv);
            }
        }
    }
    __syncwarp();
    ANCHOR(1);
}

}

extern "C" void kernel_launch(void* const* d_in, const int* in_sizes, int n_in, void* d_out, int out_size) {
    const __nv_bfloat16* x     = (const __nv_bfloat16*)d_in[0];
    const int*           src   = (const int*)d_in[1];
    const int*           dst   = (const int*)d_in[2];
    const uint2*         Y     = (const uint2*)d_in[3];
    const uint2*         ef    = (const uint2*)d_in[4];
    const __nv_bfloat16* w_rad = (const __nv_bfloat16*)d_in[5];
    const __nv_bfloat16* cg    = (const __nv_bfloat16*)d_in[6];
    const __nv_bfloat16* w_mix = (const __nv_bfloat16*)d_in[7];
    __nv_bfloat16*       out   = (__nv_bfloat16*)d_out;
    const int N = in_sizes[0] / 512;
    const int E = in_sizes[1];

    static int n_sm = 0;
    static Scratch* scr = nullptr;
    static decltype(&cuTensorMapEncodeTiled) encode = nullptr;
    if (n_sm == 0) {
        cudaDriverEntryPointQueryResult qr;
        cudaGetDriverEntryPoint("cuTensorMapEncodeTiled", (void**)&encode, cudaEnableDefault, &qr);
        cudaGetSymbolAddress((void**)&scr, g_scr);
        int dev = 0;
        cudaGetDevice(&dev);
        cudaDeviceGetAttribute(&n_sm, cudaDevAttrMultiProcessorCount, dev);
        cudaFuncSetAttribute(tfn_kernel<1>, cudaFuncAttributeMaxDynamicSharedMemorySize, SM_TOTAL);
        cudaFuncSetAttribute(tfn_kernel<2>, cudaFuncAttributeMaxDynamicSharedMemorySize, SM_TOTAL);
        cudaFuncSetAttribute(tfn_kernel<3>, cudaFuncAttributeMaxDynamicSharedMemorySize, SM_TOTAL);
    }
    CUtensorMap xmap;
    {
        const cuuint64_t dims[2] = {64, (cuuint64_t)N * 8}, strides[1] = {128};
        const cuuint32_t box[2] = {64, 8}, es[2] = {1, 1};
        encode(&xmap, CU_TENSOR_MAP_DATA_TYPE_BFLOAT16, 2, (void*)x, dims, strides, box, es, CU_TENSOR_MAP_INTERLEAVE_NONE,
               CU_TENSOR_MAP_SWIZZLE_128B, CU_TENSOR_MAP_L2_PROMOTION_NONE, CU_TENSOR_MAP_FLOAT_OOB_FILL_NONE);
    }
    CUtensorMap wmap;
    {
        const cuuint64_t dims[5] = {128, 2, 4, 4, 4}, strides[4] = {256, 512, 2048, 8192};
        const cuuint32_t box[5] = {64, 1, 2, 1, 2}, es[5] = {1, 1, 1, 1, 1};
        encode(&wmap, CU_TENSOR_MAP_DATA_TYPE_BFLOAT16, 5, (void*)w_mix, dims, strides, box, es, CU_TENSOR_MAP_INTERLEAVE_NONE,
               CU_TENSOR_MAP_SWIZZLE_128B, CU_TENSOR_MAP_L2_PROMOTION_NONE, CU_TENSOR_MAP_FLOAT_OOB_FILL_NONE);
    }
    const int slice = ((E + NCTA - 1) / NCTA + 3) / 4 * 4;
    const int npc   = (N + NCTA - 1) / NCTA;
    const uint32_t npc_magic = (uint32_t)((0x100000000ull + npc - 1) / npc);
    const uint32_t bin_magic = (uint32_t)((1ull << 25) / N);
    const double want = PDT * (double)E / (32.0 * N);
    const uint32_t pace = (uint32_t)((want < 1 ? 1 : want > 127 ? 127 : want) * (1 << 25));
    cudaStream_t st = cudaStreamPerThread;
    if (n_sm >= NCTA) {
        tfn_kernel<3><<<NCTA, NT, SM_TOTAL, st>>>(dst, src, scr, E, slice, N, npc, npc_magic, bin_magic, Y, ef, w_rad, cg, x, w_mix, out, pace, xmap, wmap);
    } else {
        tfn_kernel<1><<<NCTA, NT, SM_TOTAL, st>>>(dst, src, scr, E, slice, N, npc, npc_magic, bin_magic, Y, ef, w_rad, cg, x, w_mix, out, pace, xmap, wmap);
        tfn_kernel<2><<<NCTA, NT, SM_TOTAL, st>>>(dst, src, scr, E, slice, N, npc, npc_magic, bin_magic, Y, ef, w_rad, cg, x, w_mix, out, pace, xmap, wmap);
    }
}
```

```cpp
#include <cuda.h>
#include <cuda_runtime.h>
#include <cuda_bf16.h>
#include <stdint.h>

namespace {

constexpr int NCTA   = 132;
constexpr int NW     = 8;
constexpr int NT     = 2 * NW * 32;
constexpr int RA     = 5;
constexpr int SLICE  = RA * NT;
constexpr int MBC    = 48;
constexpr int MBE    = MBC - 1;
constexpr int MBW    = NCTA * MBC;
constexpr int ASTR   = MBC + 4;
constexpr int NH     = NW * 32;
constexpr int RL     = 17;
constexpr int RX     = 9;
constexpr int NG     = 24;
constexpr int KCAP   = 684;
constexpr int RCAP   = 2688;
constexpr int GK     = 48;
#define NBIN_ 128
constexpr int NBIN   = NBIN_;
constexpr int BSH    = NBIN == 256 ? 17 : 18;
constexpr int LBIN   = 128;
#define S_ 5
constexpr int S      = S_;
constexpr int SMG    = (65535 + S) / S;
constexpr int LCAP   = KCAP + NW + 4;

constexpr uint32_t sb = 1024;
constexpr int SM_RING = 0;
constexpr int RSTR    = NW * S * 1024 + 256;
constexpr int SM_REC  = SM_RING + 4 * RSTR - (S - 5) * 32768;
constexpr int SM_ZERO = SM_REC + RCAP * 16;
constexpr int SM_LIST = SM_ZERO + 128;
constexpr int SM_MISC = SM_LIST + LCAP * 16;
constexpr int SM_STATE = SM_MISC + 256;
constexpr int SM_BAR  = SM_STATE + 128;
constexpr int SM_SRC  = SM_BAR + NW * S * 8 + 96;
constexpr int SM_SEG  = SM_SRC + LCAP * 16;
constexpr int SM_TOTAL = SM_SEG + NCTA * 4;
constexpr int SM_AREC = SM_RING;
constexpr int SM_AP   = SM_AREC + (SLICE + 80) * 16;
constexpr int SM_AMB  = SM_AP + NH * 12;
constexpr int SM_AOFF = SM_AMB + (NCTA + 32) * ASTR * 4;
constexpr int SM_DUM  = SM_AOFF + 672;
constexpr int SM_BIN  = SM_DUM + NBIN * 4;
constexpr int SM_HIST = SM_BIN + NG * NBIN * 4;
constexpr int SM_KEY  = SM_HIST + 672;
constexpr int SM_LH   = SM_KEY + 128;
constexpr int SM_KSG  = SM_LH + NW * LBIN * 4;
constexpr int SM_CPY  = SM_KSG + NG * GK * 16;
constexpr int SM_DOFF = SM_CPY + NH * 16;
constexpr int SM_LT   = SM_DOFF + NH * 4;
constexpr int SM_RAWY = SM_REC;
constexpr int SM_RAWF = SM_RAWY + SLICE * 8;
static_assert((NW - 1 + 16 * RX) * MBC * 4 <= SM_AOFF - SM_AMB && SM_LT + 144 <= SM_REC && SM_RAWF + SLICE * 8 <= SM_ZERO, "temporaries must fit");
static_assert(SM_TOTAL <= 232448, "smem");
static_assert(SM_AMB % 128 == 0 && SM_LIST % 128 == 0 && SM_BAR % 128 == 0 && SM_HIST % 16 == 0 && SM_BIN % 16 == 0 && SM_MISC % 16 == 0 && SM_KSG % 16 == 0, "align");
static_assert(NCTA <= RL * NW && SM_SRC + NW * 128 - SM_REC < 65536 && LBIN == 128 && SM_SRC % 16 == 0 && SM_ZERO % 128 == 0, "layout");

struct Scratch {
    uint4    rec[NCTA * SLICE];
    uint32_t mb[NCTA * MBW];
    uint32_t ss[NCTA * SLICE];
    uint2    exc[NCTA * MBW];
    uint32_t epoch;
    uint32_t sent[2];
    uint32_t gap[61];
    uint32_t sent2[2][16];
};
__device__ __align__(128) Scratch g_scr;

#define STAMP(i)
#define STAMPT(i, th)
#define ANCHOR(i)

__device__ __forceinline__ uint32_t pack_bf16(float lo, float hi) {
    __nv_bfloat162 v = __floats2bfloat162_rn(lo, hi);
    return *reinterpret_cast<uint32_t*>(&v);
}
__device__ __forceinline__ uint4 lds128(uint32_t addr) {
    uint4 v;
    asm volatile("ld.shared.v4.u32 {%0,%1,%2,%3}, [%4];" : "=r"(v.x), "=r"(v.y), "=r"(v.z), "=r"(v.w) : "r"(addr) : "memory");
    return v;
}
__device__ __forceinline__ uint32_t movm(uint32_t v) {
    uint32_t r;
    asm volatile("movmatrix.sync.aligned.m8n8.trans.b16 %0, %1;" : "=r"(r) : "r"(v));
    return r;
}
__device__ __forceinline__ void cp16(uint32_t dst, const void* src) {
    asm volatile("cp.async.cg.shared.global [%0], [%1], 16;" ::"r"(dst), "l"(src) : "memory");
}
__device__ __forceinline__ uint4 ldg128_relaxed(const uint4* p) {
    uint4 v;
    asm volatile("ld.relaxed.gpu.global.v4.u32 {%0,%1,%2,%3}, [%4];" : "=r"(v.x), "=r"(v.y), "=r"(v.z), "=r"(v.w) : "l"(p) : "memory");
    return v;
}
__device__ __forceinline__ uint32_t atoms_inc(uint32_t addr) {
    uint32_t v;
    asm volatile("atom.shared.add.u32 %0, [%1], 1;" : "=r"(v) : "r"(addr) : "memory");
    return v;
}
__device__ __forceinline__ uint32_t lds32(uint32_t addr) {
    uint32_t v;
    asm volatile("ld.shared.u32 %0, [%1];" : "=r"(v) : "r"(addr) : "memory");
    return v;
}
__device__ __forceinline__ void sts32_if(bool p, uint32_t addr, uint32_t v) {
    asm volatile("{\n\t.reg .pred p;\n\tsetp.ne.u32 p, %2, 0;\n\t@p st.shared.u32 [%0], %1;\n\t}"
                 ::"r"(addr), "r"(v), "r"((uint32_t)p) : "memory");
}
__device__ __forceinline__ uint32_t lds32v(uint32_t addr) {
    uint32_t v;
    asm volatile("ld.volatile.shared.u32 %0, [%1];" : "=r"(v) : "r"(addr) : "memory");
    return v;
}
__device__ __forceinline__ uint32_t clock32() {
    uint32_t c;
    asm volatile("mov.u32 %0, %clock;" : "=r"(c));
    return c;
}
__device__ __forceinline__ uint32_t timer32() {
    uint32_t c;
    asm volatile("mov.u32 %0, %globaltimer_lo;" : "=r"(c));
    return c;
}
__device__ __forceinline__ uint32_t opaque(uint32_t v) {
    asm volatile("" : "+r"(v));
    return v;
}
#define HINT ""
__device__ __forceinline__ bool mbar_try(uint32_t bar, uint32_t parity) {
    uint32_t ok;
    asm volatile("{\n\t.reg .pred p;\n\t"
                 "mbarrier.try_wait.parity.shared::cta.b64 p, [%1], %2" HINT ";\n\t"
                 "selp.u32 %0, 1, 0, p;\n\t}"
                 : "=r"(ok) : "r"(bar), "r"(parity) : "memory");
    return ok;
}
__device__ __forceinline__ void mbar_wait(uint32_t bar, uint32_t parity) {
    int guard = 0;
    while (!mbar_try(bar, parity) && ++guard < (1 << 20)) {}
}
__device__ __forceinline__ void mbar_init(uint32_t bar, uint32_t count) {
    asm volatile("mbarrier.init.shared::cta.b64 [%0], %1;" ::"r"(bar), "r"(count) : "memory");
}
__device__ __forceinline__ uint32_t atoms_add(uint32_t addr, uint32_t x) {
    uint32_t v;
    asm volatile("atom.shared.add.u32 %0, [%1], %2;" : "=r"(v) : "r"(addr), "r"(x) : "memory");
    return v;
}
__device__ __forceinline__ uint2 lds64(uint32_t addr) {
    uint2 v;
    asm volatile("ld.shared.v2.u32 {%0,%1}, [%2];" : "=r"(v.x), "=r"(v.y) : "r"(addr) : "memory");
    return v;
}
__device__ __forceinline__ void sts128_if(bool p, uint32_t addr, uint4 v) {
    asm volatile("{\n\t.reg .pred p;\n\tsetp.ne.u32 p, %5, 0;\n\t@p st.shared.v4.u32 [%0], {%1,%2,%3,%4};\n\t}"
                 ::"r"(addr), "r"(v.x), "r"(v.y), "r"(v.z), "r"(v.w), "r"((uint32_t)p) : "memory");
}
__device__ __forceinline__ void scan_step(uint32_t& v, int o) {
    asm volatile("{\n\t.reg .pred p;\n\t.reg .b32 u;\n\tshfl.sync.up.b32 u|p, %0, %1, 0, 0xffffffff;\n\t@p add.u32 %0, %0, u;\n\t}" : "+r"(v) : "r"(o));
}
__device__ __forceinline__ uint32_t warp_incl_scan(uint32_t v) {
#pragma unroll
    for (int o = 1; o < 32; o <<= 1) scan_step(v, o);
    return v;
}
__device__ __forceinline__ void mma_k16v(float (&d)[4], uint32_t a0, uint32_t a1, uint32_t a2, uint32_t a3,
                                         uint32_t b0, uint32_t b1) {
    asm volatile("mma.sync.aligned.m16n8k16.row.col.f32.bf16.bf16.f32 {%0,%1,%2,%3}, {%4,%5,%6,%7}, {%8,%9}, {%0,%1,%2,%3};"
        : "+f"(d[0]), "+f"(d[1]), "+f"(d[2]), "+f"(d[3])
        : "r"(a0), "r"(a1), "r"(a2), "r"(a3), "r"(b0), "r"(b1));
}
__device__ __forceinline__ bool elect_one() {
    uint32_t ok;
    asm volatile("{\n\t.reg .pred p;\n\telect.sync _|p, 0xffffffff;\n\tselp.u32 %0, 1, 0, p;\n\t}" : "=r"(ok));
    return ok;
}
__host__ __device__ constexpr int chunk_of(int m, int g) {
    return ((m & 1) + (g & 2) + 2 * (m & 2)) * 8 + ((g ^ m) & 1) + ((m >> 2) & 1) * 2 + 4 * (((g >> 2) ^ (m >> 1)) & 1);
}
__device__ __forceinline__ uint4 lds128v(uint32_t addr) {
    uint4 v;
    asm volatile("ld.volatile.shared.v4.u32 {%0,%1,%2,%3}, [%4];" : "=r"(v.x), "=r"(v.y), "=r"(v.z), "=r"(v.w) : "r"(addr) : "memory");
    return v;
}
#define HM0(h) (0x10000u << (h))
#define MAIN_LOOP_PTX \
    "{\n" \
    ".reg .b32 v<16>, a<4>, u<4>, b<2>, c<2>, w<4>, ca0, ca1, na0, na1, ef, rx, ry, ex, ey, e0, e1, e3, gx, gy, cnt;\n" \
    ".reg .f32 z<16>, t<8>, y<4>, fz;\n" \
    ".reg .b16 h<2>;\n" \
    ".reg .pred pa, pr, p<2>, q<3>, s<2>;\n" \
    "mov.f32 fz, 0f00000000;\n" \
    "setp.ne.u32 pa, %175, 0; mov.b32 rx, 0; mov.b32 ry, 0;\n" \
    "ld.shared.v4.u32 {e0,e1,ex,e3}, [%160];\n" \
    "prmt.b32 ey, e0, e1, %176;\n" \
    "lop3.b32 u2, ey, 0xfff0, %174, 0xea; @pa ld.shared.v2.u32 {rx,ry}, [u2+%178];\n" \
    "and.b32 u2, ey, %172; setp.ne.u32 p0, u2, 0; and.b32 u2, ey, %173; setp.ne.u32 p1, u2, 0;\n" \
    "shr.u32 u2, ex, 16; add.u32 na0, %171, u2;\n" \
    "mma.sync.aligned.m16n8k8.row.col.f32.bf16.bf16.f32 {y0,y1,y2,y3}, {%169,%170}, {ry}, {fz,fz,fz,fz};\n" \
    "cvt.rn.bf16x2.f32 b0, y2, y0; cvt.rn.bf16x2.f32 b1, y3, y1;\n" \
    "selp.b32 a0, b0, 0, p0; selp.b32 a1, b0, 0, p1; selp.b32 a2, b1, 0, p0; selp.b32 a3, b1, 0, p1;\n" \
    "mma.sync.aligned.m16n8k8.row.col.f32.bf16.bf16.f32 {z0,z1,z2,z3}, {%161,%162}, {rx}, {fz,fz,fz,fz};\n" \
    "mma.sync.aligned.m16n8k8.row.col.f32.bf16.bf16.f32 {z4,z5,z6,z7}, {%163,%164}, {rx}, {fz,fz,fz,fz};\n" \
    "mma.sync.aligned.m16n8k8.row.col.f32.bf16.bf16.f32 {z8,z9,z10,z11}, {%165,%166}, {rx}, {fz,fz,fz,fz};\n" \
    "tanh.approx.f32 t0, z0; tanh.approx.f32 t1, z2;\n" \
    "fma.rn.f32 z0, z0, t0, z0; fma.rn.f32 z2, z2, t1, z2;\n" \
    "tanh.approx.f32 t2, z1; tanh.approx.f32 t3, z3;\n" \
    "fma.rn.f32 z1, z1, t2, z1; fma.rn.f32 z3, z3, t3, z3;\n" \
    "tanh.approx.f32 t4, z4; tanh.approx.f32 t5, z6;\n" \
    "fma.rn.f32 z4, z4, t4, z4; fma.rn.f32 z6, z6, t5, z6;\n" \
    "tanh.approx.f32 t6, z5; tanh.approx.f32 t7, z7;\n" \
    "ld.shared.v4.u32 {e0,e1,ex,e3}, [%160+16];\n" \
    "mov.u32 cnt, %%globaltimer_hi; st.shared.u32 [%177+32], cnt;\n" \
    "bra.uni SLOW;\n" \
    "S2:\n" \
    "prmt.b32 ey, e0, e1, %176;\n" \
    "mov.b32 ca0, na0; xor.b32 ca1, na0, 32; mov.b32 ef, rx;\n" \
    "mov.b32 {h0,h1}, z0; mov.b32 u1, {h1,h1}; mul.bf16x2 w1, v1, u1;\n" \
    "fma.rn.f32 z5, z5, t6, z5;\n" \
    "add.u32 %160, %160, 16;\n" \
    "mov.b32 {h0,h1}, z2; mov.b32 u1, {h1,h1}; mul.bf16x2 w2, v2, u1;\n" \
    "mov.b32 {h0,h1}, z0; mov.b32 u1, {h1,h1}; mul.bf16x2 w0, v0, u1;\n" \
    "and.b32 u2, ey, %172; setp.ne.u32 p0, u2, 0; and.b32 u2, ey, %173; setp.ne.u32 p1, u2, 0;\n" \
    "lop3.b32 u2, ey, 0xfff0, %174, 0xea; @pa ld.shared.v2.u32 {rx,ry}, [u2+%178];\n" \
    "or.b32 c0, a0, a1; or.b32 c1, a2, a3;\n" \
    "tanh.approx.f32 t3, z11;\n" \
    "tanh.approx.f32 t0, z8;\n" \
    "fma.rn.f32 z7, z7, t7, z7;\n" \
    "tanh.approx.f32 t2, z9;\n" \
    "fma.rn.f32 z11, z11, t3, z11;\n" \
    "ld.shared.v4.u32 {v12,v13,v14,v15}, [ca0+640];\n" \
    "fma.rn.f32 z8, z8, t0, z8;\n" \
    "tanh.approx.f32 t1, z10;\n" \
    "fma.rn.f32 z10, z10, t1, z10;\n" \
    "mov.b32 {h0,h1}, z2; mov.b32 u1, {h1,h1}; mul.bf16x2 w3, v3, u1;\n" \
    "ld.shared.v4.u32 {v0,v1,v2,v3}, [ca1+0];\n" \
    "mma.sync.aligned.m16n8k16.row.col.f32.bf16.bf16.f32 {%128,%129,%130,%131}, {w0,w2,w1,w3}, {c0,c1}, {%128,%129,%130,%131};\n" \
    "mov.b32 {h0,h1}, z3; mov.b32 u1, {h1,h1}; mul.bf16x2 w2, v6, u1;\n" \
    "mma.sync.aligned.m16n8k8.row.col.f32.bf16.bf16.f32 {z12,z13,z14,z15}, {%167,%168}, {ef}, {fz,fz,fz,fz};\n" \
    "tanh.approx.f32 t4, z12;\n" \
    "mov.b32 {h0,h1}, z1; mov.b32 u1, {h1,h1}; mul.bf16x2 w0, v4, u1;\n" \
    "mov.b32 {h0,h1}, z3; mov.b32 u1, {h1,h1}; mul.bf16x2 w3, v7, u1;\n" \
    "mov.b32 {h0,h1}, z1; mov.b32 u1, {h1,h1}; mul.bf16x2 w1, v5, u1;\n" \
    "mma.sync.aligned.m16n8k16.row.col.f32.bf16.bf16.f32 {%132,%133,%134,%135}, {w0,w2,w1,w3}, {c0,c1}, {%132,%133,%134,%135};\n" \
    "mov.b32 {h0,h1}, z6; mov.b32 u1, {h1,h1}; mul.bf16x2 w2, v10, u1;\n" \
    "mov.b32 {h0,h1}, z4; mov.b32 u1, {h1,h1}; mul.bf16x2 w1, v9, u1;\n" \
    "fma.rn.f32 z9, z9, t2, z9;\n" \
    "fma.rn.f32 z12, z12, t4, z12;\n" \
    "mov.b32 {h0,h1}, z4; mov.b32 u1, {h1,h1}; mul.bf16x2 w0, v8, u1;\n" \
    "shr.u32 u2, ex, 16; add.u32 na0, %171, u2;\n" \
    "ld.shared.v4.u32 {v4,v5,v6,v7}, [ca1+128];\n" \
    "tanh.approx.f32 t5, z14;\n" \
    "fma.rn.f32 z14, z14, t5, z14;\n" \
    "tanh.approx.f32 t6, z13;\n" \
    "mma.sync.aligned.m16n8k8.row.col.f32.bf16.bf16.f32 {z0,z1,z2,z3}, {%161,%162}, {rx}, {fz,fz,fz,fz};\n" \
    "tanh.approx.f32 t1, z2;\n" \
    "tanh.approx.f32 t0, z0;\n" \
    "tanh.approx.f32 t2, z1;\n" \
    "fma.rn.f32 z13, z13, t6, z13;\n" \
    "mov.b32 {h0,h1}, z6; mov.b32 u1, {h1,h1}; mul.bf16x2 w3, v11, u1;\n" \
    "mma.sync.aligned.m16n8k16.row.col.f32.bf16.bf16.f32 {%136,%137,%138,%139}, {w0,w2,w1,w3}, {c0,c1}, {%136,%137,%138,%139};\n" \
    "mov.b32 {h0,h1}, z5; mov.b32 u1, {h1,h1}; mul.bf16x2 w1, v13, u1;\n" \
    "mov.b32 {h0,h1}, z5; mov.b32 u1, {h1,h1}; mul.bf16x2 w0, v12, u1;\n" \
    "ld.shared.v4.u32 {v8,v9,v10,v11}, [ca1+512];\n" \
    "mov.b32 {h0,h1}, z7; mov.b32 u1, {h1,h1}; mul.bf16x2 w2, v14, u1;\n" \
    "fma.rn.f32 z0, z0, t0, z0;\n" \
    "tanh.approx.f32 t7, z15;\n" \
    "fma.rn.f32 z15, z15, t7, z15;\n" \
    "mov.b32 {h0,h1}, z7; mov.b32 u1, {h1,h1}; mul.bf16x2 w3, v15, u1;\n" \
    "mma.sync.aligned.m16n8k16.row.col.f32.bf16.bf16.f32 {%140,%141,%142,%143}, {w0,w2,w1,w3}, {c0,c1}, {%140,%141,%142,%143};\n" \
    "mov.b32 {h0,h1}, z8; mov.b32 u1, {h1,h1}; mul.bf16x2 w0, v0, u1;\n" \
    "mov.b32 {h0,h1}, z8; mov.b32 u1, {h1,h1}; mul.bf16x2 w1, v1, u1;\n" \
    "ld.shared.v4.u32 {v12,v13,v14,v15}, [ca1+640];\n" \
    "mov.b32 {h0,h1}, z10; mov.b32 u1, {h1,h1}; mul.bf16x2 w3, v3, u1;\n" \
    "fma.rn.f32 z2, z2, t1, z2;\n" \
    "fma.rn.f32 z1, z1, t2, z1;\n" \
    "and.b32 u2, ex, 1; mbarrier.try_wait.parity.shared::cta.b64 pr, [e3], u2;\n" \
    "mov.b32 {h0,h1}, z10; mov.b32 u1, {h1,h1}; mul.bf16x2 w2, v2, u1;\n" \
    "st.volatile.shared.u32 [%177], %160;\n" \
    "@pr ld.shared.v4.u32 {v0,v1,v2,v3}, [na0+0];\n" \
    "mma.sync.aligned.m16n8k16.row.col.f32.bf16.bf16.f32 {%144,%145,%146,%147}, {w0,w2,w1,w3}, {c0,c1}, {%144,%145,%146,%147};\n" \
    "mov.b32 {h0,h1}, z11; mov.b32 u1, {h1,h1}; mul.bf16x2 w3, v7, u1;\n" \
    "mma.sync.aligned.m16n8k8.row.col.f32.bf16.bf16.f32 {z4,z5,z6,z7}, {%163,%164}, {rx}, {fz,fz,fz,fz};\n" \
    "tanh.approx.f32 t4, z4;\n" \
    "tanh.approx.f32 t5, z6;\n" \
    "mov.b32 {h0,h1}, z9; mov.b32 u1, {h1,h1}; mul.bf16x2 w1, v5, u1;\n" \
    "mov.b32 {h0,h1}, z9; mov.b32 u1, {h1,h1}; mul.bf16x2 w0, v4, u1;\n" \
    "mov.b32 {h0,h1}, z11; mov.b32 u1, {h1,h1}; mul.bf16x2 w2, v6, u1;\n" \
    "mma.sync.aligned.m16n8k16.row.col.f32.bf16.bf16.f32 {%148,%149,%150,%151}, {w0,w2,w1,w3}, {c0,c1}, {%148,%149,%150,%151};\n" \
    "mov.b32 {h0,h1}, z12; mov.b32 u1, {h1,h1}; mul.bf16x2 w1, v9, u1;\n" \
    "@pr ld.shared.v4.u32 {v4,v5,v6,v7}, [na0+128];\n" \
    "mov.b32 {h0,h1}, z14; mov.b32 u1, {h1,h1}; mul.bf16x2 w2, v10, u1;\n" \
    "fma.rn.f32 z4, z4, t4, z4;\n" \
    "tanh.approx.f32 t3, z3;\n" \
    "fma.rn.f32 z3, z3, t3, z3;\n" \
    "mma.sync.aligned.m16n8k8.row.col.f32.bf16.bf16.f32 {y0,y1,y2,y3}, {%169,%170}, {ry}, {fz,fz,fz,fz};\n" \
    "tanh.approx.f32 t7, z7;\n" \
    "mma.sync.aligned.m16n8k8.row.col.f32.bf16.bf16.f32 {z8,z9,z10,z11}, {%165,%166}, {rx}, {fz,fz,fz,fz};\n" \
    "and.b32 u2, ex, 14; setp.eq.and.u32 q0, u2, 2, pr; setp.eq.and.u32 q1, u2, 4, pr; setp.eq.and.u32 q2, u2, 8, pr;\n" \
    "tanh.approx.f32 t6, z5;\n" \
    "mov.b32 {h0,h1}, z14; mov.b32 u1, {h1,h1}; mul.bf16x2 w3, v11, u1;\n" \
    "mov.b32 {h0,h1}, z12; mov.b32 u1, {h1,h1}; mul.bf16x2 w0, v8, u1;\n" \
    "@pr ld.shared.v4.u32 {v8,v9,v10,v11}, [na0+512];\n" \
    "mma.sync.aligned.m16n8k16.row.col.f32.bf16.bf16.f32 {%152,%153,%154,%155}, {w0,w2,w1,w3}, {c0,c1}, {%152,%153,%154,%155};\n" \
    "mov.b32 {h0,h1}, z13; mov.b32 u1, {h1,h1}; mul.bf16x2 w0, v12, u1;\n" \
    "mov.b32 {h0,h1}, z15; mov.b32 u1, {h1,h1}; mul.bf16x2 w3, v15, u1;\n" \
    "ld.shared.v4.u32 {e0,e1,ex,e3}, [%160+16];\n" \
    "fma.rn.f32 z6, z6, t5, z6;\n" \
    "cvt.rn.bf16x2.f32 b0, y2, y0; cvt.rn.bf16x2.f32 b1, y3, y1;\n" \
    "mov.b32 {h0,h1}, z13; mov.b32 u1, {h1,h1}; mul.bf16x2 w1, v13, u1;\n" \
    "mov.b32 {h0,h1}, z15; mov.b32 u1, {h1,h1}; mul.bf16x2 w2, v14, u1;\n" \
    "selp.b32 a0, b0, 0, p0; selp.b32 a1, b0, 0, p1; selp.b32 a2, b1, 0, p0; selp.b32 a3, b1, 0, p1;\n" \
    "mma.sync.aligned.m16n8k16.row.col.f32.bf16.bf16.f32 {%156,%157,%158,%159}, {w0,w2,w1,w3}, {c0,c1}, {%156,%157,%158,%159};\n" \
    "@q1 bra.uni S1;\n" \
    "@!q0 bra.uni D;\n" \
    "S0:\n" \
    "prmt.b32 ey, e0, e1, %176;\n" \
    "mov.b32 {h0,h1}, z0; mov.b32 u1, {h1,h1}; mul.bf16x2 v0, v0, u1;\n" \
    "add.u32 %160, %160, 16;\n" \
    "mov.b32 {h0,h1}, z2; mov.b32 u1, {h1,h1}; mul.bf16x2 v2, v2, u1;\n" \
    "mov.b32 {h0,h1}, z0; mov.b32 u1, {h1,h1}; mul.bf16x2 v1, v1, u1;\n" \
    "mma.sync.aligned.m16n8k16.row.col.f32.bf16.bf16.f32 {%0,%1,%2,%3}, {a0,a1,a2,a3}, {v0,v1}, {%0,%1,%2,%3};\n" \
    "and.b32 u2, ey, %172; setp.ne.u32 p0, u2, 0; and.b32 u2, ey, %173; setp.ne.u32 p1, u2, 0;\n" \
    "mov.b32 ca0, na0; xor.b32 ca1, na0, 32; mov.b32 ef, rx;\n" \
    "lop3.b32 u2, ey, 0xfff0, %174, 0xea; @pa ld.shared.v2.u32 {rx,ry}, [u2+%178];\n" \
    "ld.shared.v4.u32 {v12,v13,v14,v15}, [ca0+640];\n" \
    "mov.b32 {h0,h1}, z3; mov.b32 u1, {h1,h1}; mul.bf16x2 v7, v7, u1;\n" \
    "fma.rn.f32 z5, z5, t6, z5;\n" \
    "fma.rn.f32 z7, z7, t7, z7;\n" \
    "tanh.approx.f32 t2, z9;\n" \
    "tanh.approx.f32 t0, z8;\n" \
    "fma.rn.f32 z8, z8, t0, z8;\n" \
    "tanh.approx.f32 t3, z11;\n" \
    "tanh.approx.f32 t1, z10;\n" \
    "fma.rn.f32 z10, z10, t1, z10;\n" \
    "mov.b32 {h0,h1}, z2; mov.b32 u1, {h1,h1}; mul.bf16x2 v3, v3, u1;\n" \
    "mma.sync.aligned.m16n8k16.row.col.f32.bf16.bf16.f32 {%4,%5,%6,%7}, {a0,a1,a2,a3}, {v2,v3}, {%4,%5,%6,%7};\n" \
    "ld.shared.v4.u32 {v0,v1,v2,v3}, [ca1+0];\n" \
    "mov.b32 {h0,h1}, z6; mov.b32 u1, {h1,h1}; mul.bf16x2 v10, v10, u1;\n" \
    "mov.b32 {h0,h1}, z4; mov.b32 u1, {h1,h1}; mul.bf16x2 v8, v8, u1;\n" \
    "mov.b32 {h0,h1}, z1; mov.b32 u1, {h1,h1}; mul.bf16x2 v4, v4, u1;\n" \
    "mov.b32 {h0,h1}, z3; mov.b32 u1, {h1,h1}; mul.bf16x2 v6, v6, u1;\n" \
    "mma.sync.aligned.m16n8k16.row.col.f32.bf16.bf16.f32 {%12,%13,%14,%15}, {a0,a1,a2,a3}, {v6,v7}, {%12,%13,%14,%15};\n" \
    "mov.b32 {h0,h1}, z1; mov.b32 u1, {h1,h1}; mul.bf16x2 v5, v5, u1;\n" \
    "mma.sync.aligned.m16n8k16.row.col.f32.bf16.bf16.f32 {%8,%9,%10,%11}, {a0,a1,a2,a3}, {v4,v5}, {%8,%9,%10,%11};\n" \
    "ld.shared.v4.u32 {v4,v5,v6,v7}, [ca1+128];\n" \
    "fma.rn.f32 z9, z9, t2, z9;\n" \
    "mov.b32 {h0,h1}, z7; mov.b32 u1, {h1,h1}; mul.bf16x2 v15, v15, u1;\n" \
    "mma.sync.aligned.m16n8k8.row.col.f32.bf16.bf16.f32 {z12,z13,z14,z15}, {%167,%168}, {ef}, {fz,fz,fz,fz};\n" \
    "tanh.approx.f32 t5, z14;\n" \
    "tanh.approx.f32 t6, z13;\n" \
    "tanh.approx.f32 t4, z12;\n" \
    "fma.rn.f32 z12, z12, t4, z12;\n" \
    "fma.rn.f32 z13, z13, t6, z13;\n" \
    "mov.b32 {h0,h1}, z5; mov.b32 u1, {h1,h1}; mul.bf16x2 v13, v13, u1;\n" \
    "mov.b32 {h0,h1}, z4; mov.b32 u1, {h1,h1}; mul.bf16x2 v9, v9, u1;\n" \
    "mma.sync.aligned.m16n8k16.row.col.f32.bf16.bf16.f32 {%16,%17,%18,%19}, {a0,a1,a2,a3}, {v8,v9}, {%16,%17,%18,%19};\n" \
    "mov.b32 {h0,h1}, z7; mov.b32 u1, {h1,h1}; mul.bf16x2 v14, v14, u1;\n" \
    "mov.b32 {h0,h1}, z6; mov.b32 u1, {h1,h1}; mul.bf16x2 v11, v11, u1;\n" \
    "mma.sync.aligned.m16n8k16.row.col.f32.bf16.bf16.f32 {%20,%21,%22,%23}, {a0,a1,a2,a3}, {v10,v11}, {%20,%21,%22,%23};\n" \
    "ld.shared.v4.u32 {v8,v9,v10,v11}, [ca1+512];\n" \
    "mma.sync.aligned.m16n8k8.row.col.f32.bf16.bf16.f32 {z0,z1,z2,z3}, {%161,%162}, {rx}, {fz,fz,fz,fz};\n" \
    "fma.rn.f32 z14, z14, t5, z14;\n" \
    "tanh.approx.f32 t0, z0;\n" \
    "shr.u32 u2, ex, 16; add.u32 na0, %171, u2;\n" \
    "fma.rn.f32 z11, z11, t3, z11;\n" \
    "mma.sync.aligned.m16n8k16.row.col.f32.bf16.bf16.f32 {%28,%29,%30,%31}, {a0,a1,a2,a3}, {v14,v15}, {%28,%29,%30,%31};\n" \
    "mov.b32 {h0,h1}, z8; mov.b32 u1, {h1,h1}; mul.bf16x2 v0, v0, u1;\n" \
    "mov.b32 {h0,h1}, z5; mov.b32 u1, {h1,h1}; mul.bf16x2 v12, v12, u1;\n" \
    "mma.sync.aligned.m16n8k16.row.col.f32.bf16.bf16.f32 {%24,%25,%26,%27}, {a0,a1,a2,a3}, {v12,v13}, {%24,%25,%26,%27};\n" \
    "ld.shared.v4.u32 {v12,v13,v14,v15}, [ca1+640];\n" \
    "and.b32 u2, ex, 1; mbarrier.try_wait.parity.shared::cta.b64 pr, [e3], u2;\n" \
    "mov.b32 {h0,h1}, z11; mov.b32 u1, {h1,h1}; mul.bf16x2 v6, v6, u1;\n" \
    "tanh.approx.f32 t7, z15;\n" \
    "mma.sync.aligned.m16n8k8.row.col.f32.bf16.bf16.f32 {z4,z5,z6,z7}, {%163,%164}, {rx}, {fz,fz,fz,fz};\n" \
    "fma.rn.f32 z0, z0, t0, z0;\n" \
    "mov.b32 {h0,h1}, z11; mov.b32 u1, {h1,h1}; mul.bf16x2 v7, v7, u1;\n" \
    "mov.b32 {h0,h1}, z10; mov.b32 u1, {h1,h1}; mul.bf16x2 v3, v3, u1;\n" \
    "fma.rn.f32 z15, z15, t7, z15;\n" \
    "mov.b32 {h0,h1}, z8; mov.b32 u1, {h1,h1}; mul.bf16x2 v1, v1, u1;\n" \
    "mma.sync.aligned.m16n8k16.row.col.f32.bf16.bf16.f32 {%32,%33,%34,%35}, {a0,a1,a2,a3}, {v0,v1}, {%32,%33,%34,%35};\n" \
    "mov.b32 {h0,h1}, z9; mov.b32 u1, {h1,h1}; mul.bf16x2 v5, v5, u1;\n" \
    "mov.b32 {h0,h1}, z10; mov.b32 u1, {h1,h1}; mul.bf16x2 v2, v2, u1;\n" \
    "mma.sync.aligned.m16n8k16.row.col.f32.bf16.bf16.f32 {%36,%37,%38,%39}, {a0,a1,a2,a3}, {v2,v3}, {%36,%37,%38,%39};\n" \
    "tanh.approx.f32 t1, z2;\n" \
    "fma.rn.f32 z2, z2, t1, z2;\n" \
    "tanh.approx.f32 t3, z3;\n" \
    "st.volatile.shared.u32 [%177], %160;\n" \
    "@pr ld.shared.v4.u32 {v0,v1,v2,v3}, [na0+0];\n" \
    "mov.b32 {h0,h1}, z9; mov.b32 u1, {h1,h1}; mul.bf16x2 v4, v4, u1;\n" \
    "mma.sync.aligned.m16n8k16.row.col.f32.bf16.bf16.f32 {%40,%41,%42,%43}, {a0,a1,a2,a3}, {v4,v5}, {%40,%41,%42,%43};\n" \
    "fma.rn.f32 z3, z3, t3, z3;\n" \
    "tanh.approx.f32 t2, z1;\n" \
    "fma.rn.f32 z1, z1, t2, z1;\n" \
    "tanh.approx.f32 t4, z4;\n" \
    "mov.b32 {h0,h1}, z13; mov.b32 u1, {h1,h1}; mul.bf16x2 v13, v13, u1;\n" \
    "tanh.approx.f32 t7, z7;\n" \
    "tanh.approx.f32 t5, z6;\n" \
    "mov.b32 {h0,h1}, z12; mov.b32 u1, {h1,h1}; mul.bf16x2 v9, v9, u1;\n" \
    "mov.b32 {h0,h1}, z14; mov.b32 u1, {h1,h1}; mul.bf16x2 v10, v10, u1;\n" \
    "fma.rn.f32 z4, z4, t4, z4;\n" \
    "mov.b32 {h0,h1}, z12; mov.b32 u1, {h1,h1}; mul.bf16x2 v8, v8, u1;\n" \
    "mma.sync.aligned.m16n8k16.row.col.f32.bf16.bf16.f32 {%48,%49,%50,%51}, {a0,a1,a2,a3}, {v8,v9}, {%48,%49,%50,%51};\n" \
    "mma.sync.aligned.m16n8k16.row.col.f32.bf16.bf16.f32 {%44,%45,%46,%47}, {a0,a1,a2,a3}, {v6,v7}, {%44,%45,%46,%47};\n" \
    "@pr ld.shared.v4.u32 {v4,v5,v6,v7}, [na0+128];\n" \
    "fma.rn.f32 z6, z6, t5, z6;\n" \
    "mma.sync.aligned.m16n8k8.row.col.f32.bf16.bf16.f32 {z8,z9,z10,z11}, {%165,%166}, {rx}, {fz,fz,fz,fz};\n" \
    "mma.sync.aligned.m16n8k8.row.col.f32.bf16.bf16.f32 {y0,y1,y2,y3}, {%169,%170}, {ry}, {fz,fz,fz,fz};\n" \
    "mov.b32 {h0,h1}, z15; mov.b32 u1, {h1,h1}; mul.bf16x2 v14, v14, u1;\n" \
    "and.b32 u2, ex, 14; setp.eq.and.u32 q0, u2, 2, pr; setp.eq.and.u32 q1, u2, 4, pr; setp.eq.and.u32 q2, u2, 8, pr;\n" \
    "mov.b32 {h0,h1}, z14; mov.b32 u1, {h1,h1}; mul.bf16x2 v11, v11, u1;\n" \
    "mma.sync.aligned.m16n8k16.row.col.f32.bf16.bf16.f32 {%52,%53,%54,%55}, {a0,a1,a2,a3}, {v10,v11}, {%52,%53,%54,%55};\n" \
    "@pr ld.shared.v4.u32 {v8,v9,v10,v11}, [na0+512];\n" \
    "tanh.approx.f32 t6, z5;\n" \
    "mov.b32 {h0,h1}, z15; mov.b32 u1, {h1,h1}; mul.bf16x2 v15, v15, u1;\n" \
    "mma.sync.aligned.m16n8k16.row.col.f32.bf16.bf16.f32 {%60,%61,%62,%63}, {a0,a1,a2,a3}, {v14,v15}, {%60,%61,%62,%63};\n" \
    "ld.shared.v4.u32 {e0,e1,ex,e3}, [%160+16];\n" \
    "mov.b32 {h0,h1}, z13; mov.b32 u1, {h1,h1}; mul.bf16x2 v12, v12, u1;\n" \
    "mma.sync.aligned.m16n8k16.row.col.f32.bf16.bf16.f32 {%56,%57,%58,%59}, {a0,a1,a2,a3}, {v12,v13}, {%56,%57,%58,%59};\n" \
    "cvt.rn.bf16x2.f32 b0, y2, y0; cvt.rn.bf16x2.f32 b1, y3, y1;\n" \
    "selp.b32 a0, b0, 0, p0; selp.b32 a1, b0, 0, p1; selp.b32 a2, b1, 0, p0; selp.b32 a3, b1, 0, p1;\n" \
    "@!q1 bra.uni D;\n" \
    "S1:\n" \
    "prmt.b32 ey, e0, e1, %176;\n" \
    "mov.b32 {h0,h1}, z0; mov.b32 u1, {h1,h1}; mul.bf16x2 v0, v0, u1;\n" \
    "add.u32 %160, %160, 16;\n" \
    "mov.b32 {h0,h1}, z2; mov.b32 u1, {h1,h1}; mul.bf16x2 v2, v2, u1;\n" \
    "mov.b32 {h0,h1}, z0; mov.b32 u1, {h1,h1}; mul.bf16x2 v1, v1, u1;\n" \
    "mma.sync.aligned.m16n8k16.row.col.f32.bf16.bf16.f32 {%64,%65,%66,%67}, {a0,a1,a2,a3}, {v0,v1}, {%64,%65,%66,%67};\n" \
    "and.b32 u2, ey, %172; setp.ne.u32 p0, u2, 0; and.b32 u2, ey, %173; setp.ne.u32 p1, u2, 0;\n" \
    "mov.b32 ca0, na0; xor.b32 ca1, na0, 32; mov.b32 ef, rx;\n" \
    "lop3.b32 u2, ey, 0xfff0, %174, 0xea; @pa ld.shared.v2.u32 {rx,ry}, [u2+%178];\n" \
    "ld.shared.v4.u32 {v12,v13,v14,v15}, [ca0+640];\n" \
    "mov.b32 {h0,h1}, z3; mov.b32 u1, {h1,h1}; mul.bf16x2 v7, v7, u1;\n" \
    "fma.rn.f32 z5, z5, t6, z5;\n" \
    "fma.rn.f32 z7, z7, t7, z7;\n" \
    "tanh.approx.f32 t2, z9;\n" \
    "tanh.approx.f32 t0, z8;\n" \
    "fma.rn.f32 z8, z8, t0, z8;\n" \
    "tanh.approx.f32 t3, z11;\n" \
    "tanh.approx.f32 t1, z10;\n" \
    "fma.rn.f32 z10, z10, t1, z10;\n" \
    "mov.b32 {h0,h1}, z2; mov.b32 u1, {h1,h1}; mul.bf16x2 v3, v3, u1;\n" \
    "mma.sync.aligned.m16n8k16.row.col.f32.bf16.bf16.f32 {%68,%69,%70,%71}, {a0,a1,a2,a3}, {v2,v3}, {%68,%69,%70,%71};\n" \
    "ld.shared.v4.u32 {v0,v1,v2,v3}, [ca1+0];\n" \
    "mov.b32 {h0,h1}, z6; mov.b32 u1, {h1,h1}; mul.bf16x2 v10, v10, u1;\n" \
    "mov.b32 {h0,h1}, z4; mov.b32 u1, {h1,h1}; mul.bf16x2 v8, v8, u1;\n" \
    "mov.b32 {h0,h1}, z1; mov.b32 u1, {h1,h1}; mul.bf16x2 v4, v4, u1;\n" \
    "mov.b32 {h0,h1}, z3; mov.b32 u1, {h1,h1}; mul.bf16x2 v6, v6, u1;\n" \
    "mma.sync.aligned.m16n8k16.row.col.f32.bf16.bf16.f32 {%76,%77,%78,%79}, {a0,a1,a2,a3}, {v6,v7}, {%76,%77,%78,%79};\n" \
    "mov.b32 {h0,h1}, z1; mov.b32 u1, {h1,h1}; mul.bf16x2 v5, v5, u1;\n" \
    "mma.sync.aligned.m16n8k16.row.col.f32.bf16.bf16.f32 {%72,%73,%74,%75}, {a0,a1,a2,a3}, {v4,v5}, {%72,%73,%74,%75};\n" \
    "ld.shared.v4.u32 {v4,v5,v6,v7}, [ca1+128];\n" \
    "fma.rn.f32 z9, z9, t2, z9;\n" \
    "mov.b32 {h0,h1}, z7; mov.b32 u1, {h1,h1}; mul.bf16x2 v15, v15, u1;\n" \
    "mma.sync.aligned.m16n8k8.row.col.f32.bf16.bf16.f32 {z12,z13,z14,z15}, {%167,%168}, {ef}, {fz,fz,fz,fz};\n" \
    "tanh.approx.f32 t5, z14;\n" \
    "tanh.approx.f32 t6, z13;\n" \
    "tanh.approx.f32 t4, z12;\n" \
    "fma.rn.f32 z12, z12, t4, z12;\n" \
    "fma.rn.f32 z13, z13, t6, z13;\n" \
    "mov.b32 {h0,h1}, z5; mov.b32 u1, {h1,h1}; mul.bf16x2 v13, v13, u1;\n" \
    "mov.b32 {h0,h1}, z4; mov.b32 u1, {h1,h1}; mul.bf16x2 v9, v9, u1;\n" \
    "mma.sync.aligned.m16n8k16.row.col.f32.bf16.bf16.f32 {%80,%81,%82,%83}, {a0,a1,a2,a3}, {v8,v9}, {%80,%81,%82,%83};\n" \
    "mov.b32 {h0,h1}, z7; mov.b32 u1, {h1,h1}; mul.bf16x2 v14, v14, u1;\n" \
    "mov.b32 {h0,h1}, z6; mov.b32 u1, {h1,h1}; mul.bf16x2 v11, v11, u1;\n" \
    "mma.sync.aligned.m16n8k16.row.col.f32.bf16.bf16.f32 {%84,%85,%86,%87}, {a0,a1,a2,a3}, {v10,v11}, {%84,%85,%86,%87};\n" \
    "ld.shared.v4.u32 {v8,v9,v10,v11}, [ca1+512];\n" \
    "mma.sync.aligned.m16n8k8.row.col.f32.bf16.bf16.f32 {z0,z1,z2,z3}, {%161,%162}, {rx}, {fz,fz,fz,fz};\n" \
    "fma.rn.f32 z14, z14, t5, z14;\n" \
    "tanh.approx.f32 t0, z0;\n" \
    "shr.u32 u2, ex, 16; add.u32 na0, %171, u2;\n" \
    "fma.rn.f32 z11, z11, t3, z11;\n" \
    "mma.sync.aligned.m16n8k16.row.col.f32.bf16.bf16.f32 {%92,%93,%94,%95}, {a0,a1,a2,a3}, {v14,v15}, {%92,%93,%94,%95};\n" \
    "mov.b32 {h0,h1}, z8; mov.b32 u1, {h1,h1}; mul.bf16x2 v0, v0, u1;\n" \
    "mov.b32 {h0,h1}, z5; mov.b32 u1, {h1,h1}; mul.bf16x2 v12, v12, u1;\n" \
    "mma.sync.aligned.m16n8k16.row.col.f32.bf16.bf16.f32 {%88,%89,%90,%91}, {a0,a1,a2,a3}, {v12,v13}, {%88,%89,%90,%91};\n" \
    "ld.shared.v4.u32 {v12,v13,v14,v15}, [ca1+640];\n" \
    "and.b32 u2, ex, 1; mbarrier.try_wait.parity.shared::cta.b64 pr, [e3], u2;\n" \
    "mov.b32 {h0,h1}, z11; mov.b32 u1, {h1,h1}; mul.bf16x2 v6, v6, u1;\n" \
    "tanh.approx.f32 t7, z15;\n" \
    "mma.sync.aligned.m16n8k8.row.col.f32.bf16.bf16.f32 {z4,z5,z6,z7}, {%163,%164}, {rx}, {fz,fz,fz,fz};\n" \
    "fma.rn.f32 z0, z0, t0, z0;\n" \
    "mov.b32 {h0,h1}, z11; mov.b32 u1, {h1,h1}; mul.bf16x2 v7, v7, u1;\n" \
    "mov.b32 {h0,h1}, z10; mov.b32 u1, {h1,h1}; mul.bf16x2 v3, v3, u1;\n" \
    "fma.rn.f32 z15, z15, t7, z15;\n" \
    "mov.b32 {h0,h1}, z8; mov.b32 u1, {h1,h1}; mul.bf16x2 v1, v1, u1;\n" \
    "mma.sync.aligned.m16n8k16.row.col.f32.bf16.bf16.f32 {%96,%97,%98,%99}, {a0,a1,a2,a3}, {v0,v1}, {%96,%97,%98,%99};\n" \
    "mov.b32 {h0,h1}, z9; mov.b32 u1, {h1,h1}; mul.bf16x2 v5, v5, u1;\n" \
    "mov.b32 {h0,h1}, z10; mov.b32 u1, {h1,h1}; mul.bf16x2 v2, v2, u1;\n" \
    "mma.sync.aligned.m16n8k16.row.col.f32.bf16.bf16.f32 {%100,%101,%102,%103}, {a0,a1,a2,a3}, {v2,v3}, {%100,%101,%102,%103};\n" \
    "tanh.approx.f32 t1, z2;\n" \
    "fma.rn.f32 z2, z2, t1, z2;\n" \
    "tanh.approx.f32 t3, z3;\n" \
    "st.volatile.shared.u32 [%177], %160;\n" \
    "@pr ld.shared.v4.u32 {v0,v1,v2,v3}, [na0+0];\n" \
    "mov.b32 {h0,h1}, z9; mov.b32 u1, {h1,h1}; mul.bf16x2 v4, v4, u1;\n" \
    "mma.sync.aligned.m16n8k16.row.col.f32.bf16.bf16.f32 {%104,%105,%106,%107}, {a0,a1,a2,a3}, {v4,v5}, {%104,%105,%106,%107};\n" \
    "fma.rn.f32 z3, z3, t3, z3;\n" \
    "tanh.approx.f32 t2, z1;\n" \
    "fma.rn.f32 z1, z1, t2, z1;\n" \
    "tanh.approx.f32 t4, z4;\n" \
    "mov.b32 {h0,h1}, z13; mov.b32 u1, {h1,h1}; mul.bf16x2 v13, v13, u1;\n" \
    "tanh.approx.f32 t7, z7;\n" \
    "tanh.approx.f32 t5, z6;\n" \
    "mov.b32 {h0,h1}, z12; mov.b32 u1, {h1,h1}; mul.bf16x2 v9, v9, u1;\n" \
    "mov.b32 {h0,h1}, z14; mov.b32 u1, {h1,h1}; mul.bf16x2 v10, v10, u1;\n" \
    "fma.rn.f32 z4, z4, t4, z4;\n" \
    "mov.b32 {h0,h1}, z12; mov.b32 u1, {h1,h1}; mul.bf16x2 v8, v8, u1;\n" \
    "mma.sync.aligned.m16n8k16.row.col.f32.bf16.bf16.f32 {%112,%113,%114,%115}, {a0,a1,a2,a3}, {v8,v9}, {%112,%113,%114,%115};\n" \
    "mma.sync.aligned.m16n8k16.row.col.f32.bf16.bf16.f32 {%108,%109,%110,%111}, {a0,a1,a2,a3}, {v6,v7}, {%108,%109,%110,%111};\n" \
    "@pr ld.shared.v4.u32 {v4,v5,v6,v7}, [na0+128];\n" \
    "fma.rn.f32 z6, z6, t5, z6;\n" \
    "mma.sync.aligned.m16n8k8.row.col.f32.bf16.bf16.f32 {z8,z9,z10,z11}, {%165,%166}, {rx}, {fz,fz,fz,fz};\n" \
    "mma.sync.aligned.m16n8k8.row.col.f32.bf16.bf16.f32 {y0,y1,y2,y3}, {%169,%170}, {ry}, {fz,fz,fz,fz};\n" \
    "mov.b32 {h0,h1}, z15; mov.b32 u1, {h1,h1}; mul.bf16x2 v14, v14, u1;\n" \
    "and.b32 u2, ex, 14; setp.eq.and.u32 q0, u2, 2, pr; setp.eq.and.u32 q1, u2, 4, pr; setp.eq.and.u32 q2, u2, 8, pr;\n" \
    "mov.b32 {h0,h1}, z14; mov.b32 u1, {h1,h1}; mul.bf16x2 v11, v11, u1;\n" \
    "mma.sync.aligned.m16n8k16.row.col.f32.bf16.bf16.f32 {%116,%117,%118,%119}, {a0,a1,a2,a3}, {v10,v11}, {%116,%117,%118,%119};\n" \
    "@pr ld.shared.v4.u32 {v8,v9,v10,v11}, [na0+512];\n" \
    "tanh.approx.f32 t6, z5;\n" \
    "mov.b32 {h0,h1}, z15; mov.b32 u1, {h1,h1}; mul.bf16x2 v15, v15, u1;\n" \
    "mma.sync.aligned.m16n8k16.row.col.f32.bf16.bf16.f32 {%124,%125,%126,%127}, {a0,a1,a2,a3}, {v14,v15}, {%124,%125,%126,%127};\n" \
    "ld.shared.v4.u32 {e0,e1,ex,e3}, [%160+16];\n" \
    "mov.b32 {h0,h1}, z13; mov.b32 u1, {h1,h1}; mul.bf16x2 v12, v12, u1;\n" \
    "mma.sync.aligned.m16n8k16.row.col.f32.bf16.bf16.f32 {%120,%121,%122,%123}, {a0,a1,a2,a3}, {v12,v13}, {%120,%121,%122,%123};\n" \
    "cvt.rn.bf16x2.f32 b0, y2, y0; cvt.rn.bf16x2.f32 b1, y3, y1;\n" \
    "selp.b32 a0, b0, 0, p0; selp.b32 a1, b0, 0, p1; selp.b32 a2, b1, 0, p0; selp.b32 a3, b1, 0, p1;\n" \
    "D:\n" \
    "@q0 bra.uni S0;\n" \
    "@q2 bra.uni S2;\n" \
    "@q1 bra.uni S1;\n" \
    "SLOW:\n" \
    "ld.shared.v2.u32 {gx,gy}, [%160+8];\n" \
    "and.b32 u2, gx, 1; and.b32 gx, gx, 14; setp.eq.u32 q0, gx, 2; setp.eq.u32 q1, gx, 4; setp.eq.u32 q2, gx, 8;\n" \
    "@q0 bra.uni W0;\n" \
    "@q1 bra.uni W1;\n" \
    "@!q2 bra.uni DONE;\n" \
    "W2:\n" \
    "mbarrier.try_wait.parity.shared::cta.b64 pr, [gy], u2;\n" \
    "@!pr bra.uni X2;\n" \
    "ld.shared.v4.u32 {v0,v1,v2,v3}, [na0+0];\n" \
    "ld.shared.v4.u32 {v4,v5,v6,v7}, [na0+128];\n" \
    "ld.shared.v4.u32 {v8,v9,v10,v11}, [na0+512];\n" \
    "bra.uni S2;\n" \
    "X2:\n" \
    "mov.u32 cnt, %%globaltimer_hi; ld.shared.u32 gx, [%177+32]; sub.u32 cnt, cnt, gx; setp.lt.u32 pr, cnt, 2;\n" \
    "@pr bra.uni W2;\n" \
    "bra.uni DONE;\n" \
    "W0:\n" \
    "mbarrier.try_wait.parity.shared::cta.b64 pr, [gy], u2;\n" \
    "@!pr bra.uni X0;\n" \
    "ld.shared.v4.u32 {v0,v1,v2,v3}, [na0+0];\n" \
    "ld.shared.v4.u32 {v4,v5,v6,v7}, [na0+128];\n" \
    "ld.shared.v4.u32 {v8,v9,v10,v11}, [na0+512];\n" \
    "bra.uni S0;\n" \
    "X0:\n" \
    "mov.u32 cnt, %%globaltimer_hi; ld.shared.u32 gx, [%177+32]; sub.u32 cnt, cnt, gx; setp.lt.u32 pr, cnt, 2;\n" \
    "@pr bra.uni W0;\n" \
    "bra.uni DONE;\n" \
    "W1:\n" \
    "mbarrier.try_wait.parity.shared::cta.b64 pr, [gy], u2;\n" \
    "@!pr bra.uni X1;\n" \
    "ld.shared.v4.u32 {v0,v1,v2,v3}, [na0+0];\n" \
    "ld.shared.v4.u32 {v4,v5,v6,v7}, [na0+128];\n" \
    "ld.shared.v4.u32 {v8,v9,v10,v11}, [na0+512];\n" \
    "bra.uni S1;\n" \
    "X1:\n" \
    "mov.u32 cnt, %%globaltimer_hi; ld.shared.u32 gx, [%177+32]; sub.u32 cnt, cnt, gx; setp.lt.u32 pr, cnt, 2;\n" \
    "@pr bra.uni W1;\n" \
    "bra.uni DONE;\n" \
    "DONE:\n" \
    "mov.b32 u2, z0; xor.b32 %160, %160, u2;\n" \
    "mov.b32 u2, z2; xor.b32 %160, %160, u2;\n" \
    "mov.b32 u2, z1; xor.b32 %160, %160, u2;\n" \
    "mov.b32 u2, z3; xor.b32 %160, %160, u2;\n" \
    "mov.b32 u2, z4; xor.b32 %160, %160, u2;\n" \
    "mov.b32 u2, z6; xor.b32 %160, %160, u2;\n" \
    "}\n" \
    ""
#define MAIN_LOOP_ACC(A) \
    "+f"(A[0][0]), "+f"(A[0][1]), "+f"(A[0][2]), "+f"(A[0][3]), "+f"(A[1][0]), "+f"(A[1][1]), "+f"(A[1][2]), "+f"(A[1][3]), \
    "+f"(A[2][0]), "+f"(A[2][1]), "+f"(A[2][2]), "+f"(A[2][3]), "+f"(A[3][0]), "+f"(A[3][1]), "+f"(A[3][2]), "+f"(A[3][3]), \
    "+f"(A[4][0]), "+f"(A[4][1]), "+f"(A[4][2]), "+f"(A[4][3]), "+f"(A[5][0]), "+f"(A[5][1]), "+f"(A[5][2]), "+f"(A[5][3]), \
    "+f"(A[6][0]), "+f"(A[6][1]), "+f"(A[6][2]), "+f"(A[6][3]), "+f"(A[7][0]), "+f"(A[7][1]), "+f"(A[7][2]), "+f"(A[7][3]), \
    "+f"(A[8][0]), "+f"(A[8][1]), "+f"(A[8][2]), "+f"(A[8][3]), "+f"(A[9][0]), "+f"(A[9][1]), "+f"(A[9][2]), "+f"(A[9][3]), \
    "+f"(A[10][0]), "+f"(A[10][1]), "+f"(A[10][2]), "+f"(A[10][3]), "+f"(A[11][0]), "+f"(A[11][1]), "+f"(A[11][2]), "+f"(A[11][3]), \
    "+f"(A[12][0]), "+f"(A[12][1]), "+f"(A[12][2]), "+f"(A[12][3]), "+f"(A[13][0]), "+f"(A[13][1]), "+f"(A[13][2]), "+f"(A[13][3]), \
    "+f"(A[14][0]), "+f"(A[14][1]), "+f"(A[14][2]), "+f"(A[14][3]), "+f"(A[15][0]), "+f"(A[15][1]), "+f"(A[15][2]), "+f"(A[15][3]), \
    "+f"(A[16][0]), "+f"(A[16][1]), "+f"(A[16][2]), "+f"(A[16][3]), "+f"(A[17][0]), "+f"(A[17][1]), "+f"(A[17][2]), "+f"(A[17][3]), \
    "+f"(A[18][0]), "+f"(A[18][1]), "+f"(A[18][2]), "+f"(A[18][3]), "+f"(A[19][0]), "+f"(A[19][1]), "+f"(A[19][2]), "+f"(A[19][3]), \
    "+f"(A[20][0]), "+f"(A[20][1]), "+f"(A[20][2]), "+f"(A[20][3]), "+f"(A[21][0]), "+f"(A[21][1]), "+f"(A[21][2]), "+f"(A[21][3]), \
    "+f"(A[22][0]), "+f"(A[22][1]), "+f"(A[22][2]), "+f"(A[22][3]), "+f"(A[23][0]), "+f"(A[23][1]), "+f"(A[23][2]), "+f"(A[23][3]), \
    "+f"(A[24][0]), "+f"(A[24][1]), "+f"(A[24][2]), "+f"(A[24][3]), "+f"(A[25][0]), "+f"(A[25][1]), "+f"(A[25][2]), "+f"(A[25][3]), \
    "+f"(A[26][0]), "+f"(A[26][1]), "+f"(A[26][2]), "+f"(A[26][3]), "+f"(A[27][0]), "+f"(A[27][1]), "+f"(A[27][2]), "+f"(A[27][3]), \
    "+f"(A[28][0]), "+f"(A[28][1]), "+f"(A[28][2]), "+f"(A[28][3]), "+f"(A[29][0]), "+f"(A[29][1]), "+f"(A[29][2]), "+f"(A[29][3]), \
    "+f"(A[30][0]), "+f"(A[30][1]), "+f"(A[30][2]), "+f"(A[30][3]), "+f"(A[31][0]), "+f"(A[31][1]), "+f"(A[31][2]), "+f"(A[31][3]), \
    "+f"(A[32][0]), "+f"(A[32][1]), "+f"(A[32][2]), "+f"(A[32][3]), "+f"(A[33][0]), "+f"(A[33][1]), "+f"(A[33][2]), "+f"(A[33][3]), \
    "+f"(A[34][0]), "+f"(A[34][1]), "+f"(A[34][2]), "+f"(A[34][3]), "+f"(A[35][0]), "+f"(A[35][1]), "+f"(A[35][2]), "+f"(A[35][3]), \
    "+f"(A[36][0]), "+f"(A[36][1]), "+f"(A[36][2]), "+f"(A[36][3]), "+f"(A[37][0]), "+f"(A[37][1]), "+f"(A[37][2]), "+f"(A[37][3]), \
    "+f"(A[38][0]), "+f"(A[38][1]), "+f"(A[38][2]), "+f"(A[38][3]), "+f"(A[39][0]), "+f"(A[39][1]), "+f"(A[39][2]), "+f"(A[39][3])
#define PRODUCER_PTX \
    "{\n" \
    ".reg .b32 r<4>, d, b, c, t, w, n; .reg .b64 a; .reg .pred p, q;\n" \
    "mov.b32 n, 0;\n" \
    "TOP:\n" \
    "ld.shared.v4.u32 {r0,r1,r2,r3}, [%0+%16];\n" \
    "ld.shared.u16 t, [%0+72]; setp.ge.u32 q, %0, %10;\n" \
    "mov.u32 c, %%globaltimer_lo; sub.s32 c, c, %11; sub.s32 c, c, t; setp.ge.s32 p, c, 0;\n" \
    "@p bra.uni G0;\n" \
    "T0:\n" \
    "nanosleep.u32 64;\n" \
    "mov.u32 c, %%globaltimer_lo; sub.s32 c, c, %11; sub.s32 c, c, t; setp.lt.s32 p, c, 0;\n" \
    "@p bra.uni T0;\n" \
    "G0:\n" \
    "ld.volatile.shared.u32 w, [%9]; setp.lt.or.u32 p, w, %0, q;\n" \
    "@p bra.uni W0;\n" \
    "add.u32 b, %3, 0;\n" \
    "mbarrier.arrive.expect_tx.shared::cta.b64 _, [b], %12;\n" \
    "add.u32 d, %2, 0*%15+1024;\n" \
    "cp.async.bulk.tensor.2d.shared::cluster.global.tile.mbarrier::complete_tx::bytes [d], [%4, {%5, r0}], [b];\n" \
    "add.u32 d, %2, 1*%15+1024;\n" \
    "cp.async.bulk.tensor.2d.shared::cluster.global.tile.mbarrier::complete_tx::bytes [d], [%4, {%6, r1}], [b];\n" \
    "add.u32 d, %2, 2*%15+1024;\n" \
    "cp.async.bulk.tensor.2d.shared::cluster.global.tile.mbarrier::complete_tx::bytes [d], [%4, {%7, r2}], [b];\n" \
    "add.u32 d, %2, 3*%15+1024;\n" \
    "cp.async.bulk.tensor.2d.shared::cluster.global.tile.mbarrier::complete_tx::bytes [d], [%4, {%8, r3}], [b];\n" \
    "add.u32 %0, %0, 16;\n" \
    "ld.shared.v4.u32 {r0,r1,r2,r3}, [%0+%16];\n" \
    "ld.shared.u16 t, [%0+72]; setp.ge.u32 q, %0, %10;\n" \
    "mov.u32 c, %%globaltimer_lo; sub.s32 c, c, %11; sub.s32 c, c, t; setp.ge.s32 p, c, 0;\n" \
    "@p bra.uni G1;\n" \
    "T1:\n" \
    "nanosleep.u32 64;\n" \
    "mov.u32 c, %%globaltimer_lo; sub.s32 c, c, %11; sub.s32 c, c, t; setp.lt.s32 p, c, 0;\n" \
    "@p bra.uni T1;\n" \
    "G1:\n" \
    "ld.volatile.shared.u32 w, [%9]; setp.lt.or.u32 p, w, %0, q;\n" \
    "@p bra.uni W1;\n" \
    "add.u32 b, %3, 8;\n" \
    "mbarrier.arrive.expect_tx.shared::cta.b64 _, [b], %12;\n" \
    "add.u32 d, %2, 0*%15+2048;\n" \
    "cp.async.bulk.tensor.2d.shared::cluster.global.tile.mbarrier::complete_tx::bytes [d], [%4, {%5, r0}], [b];\n" \
    "add.u32 d, %2, 1*%15+2048;\n" \
    "cp.async.bulk.tensor.2d.shared::cluster.global.tile.mbarrier::complete_tx::bytes [d], [%4, {%6, r1}], [b];\n" \
    "add.u32 d, %2, 2*%15+2048;\n" \
    "cp.async.bulk.tensor.2d.shared::cluster.global.tile.mbarrier::complete_tx::bytes [d], [%4, {%7, r2}], [b];\n" \
    "add.u32 d, %2, 3*%15+2048;\n" \
    "cp.async.bulk.tensor.2d.shared::cluster.global.tile.mbarrier::complete_tx::bytes [d], [%4, {%8, r3}], [b];\n" \
    "add.u32 %0, %0, 16;\n" \
    "ld.shared.v4.u32 {r0,r1,r2,r3}, [%0+%16];\n" \
    "ld.shared.u16 t, [%0+72]; setp.ge.u32 q, %0, %10;\n" \
    "mov.u32 c, %%globaltimer_lo; sub.s32 c, c, %11; sub.s32 c, c, t; setp.ge.s32 p, c, 0;\n" \
    "@p bra.uni G2;\n" \
    "T2:\n" \
    "nanosleep.u32 64;\n" \
    "mov.u32 c, %%globaltimer_lo; sub.s32 c, c, %11; sub.s32 c, c, t; setp.lt.s32 p, c, 0;\n" \
    "@p bra.uni T2;\n" \
    "G2:\n" \
    "ld.volatile.shared.u32 w, [%9]; setp.lt.or.u32 p, w, %0, q;\n" \
    "@p bra.uni W2;\n" \
    "add.u32 b, %3, 16;\n" \
    "mbarrier.arrive.expect_tx.shared::cta.b64 _, [b], %12;\n" \
    "add.u32 d, %2, 0*%15+3072;\n" \
    "cp.async.bulk.tensor.2d.shared::cluster.global.tile.mbarrier::complete_tx::bytes [d], [%4, {%5, r0}], [b];\n" \
    "add.u32 d, %2, 1*%15+3072;\n" \
    "cp.async.bulk.tensor.2d.shared::cluster.global.tile.mbarrier::complete_tx::bytes [d], [%4, {%6, r1}], [b];\n" \
    "add.u32 d, %2, 2*%15+3072;\n" \
    "cp.async.bulk.tensor.2d.shared::cluster.global.tile.mbarrier::complete_tx::bytes [d], [%4, {%7, r2}], [b];\n" \
    "add.u32 d, %2, 3*%15+3072;\n" \
    "cp.async.bulk.tensor.2d.shared::cluster.global.tile.mbarrier::complete_tx::bytes [d], [%4, {%8, r3}], [b];\n" \
    "add.u32 %0, %0, 16;\n" \
    "ld.shared.v4.u32 {r0,r1,r2,r3}, [%0+%16];\n" \
    "ld.shared.u16 t, [%0+72]; setp.ge.u32 q, %0, %10;\n" \
    "mov.u32 c, %%globaltimer_lo; sub.s32 c, c, %11; sub.s32 c, c, t; setp.ge.s32 p, c, 0;\n" \
    "@p bra.uni G3;\n" \
    "T3:\n" \
    "nanosleep.u32 64;\n" \
    "mov.u32 c, %%globaltimer_lo; sub.s32 c, c, %11; sub.s32 c, c, t; setp.lt.s32 p, c, 0;\n" \
    "@p bra.uni T3;\n" \
    "G3:\n" \
    "ld.volatile.shared.u32 w, [%9]; setp.lt.or.u32 p, w, %0, q;\n" \
    "@p bra.uni W3;\n" \
    "add.u32 b, %3, 24;\n" \
    "mbarrier.arrive.expect_tx.shared::cta.b64 _, [b], %12;\n" \
    "add.u32 d, %2, 0*%15+4096;\n" \
    "cp.async.bulk.tensor.2d.shared::cluster.global.tile.mbarrier::complete_tx::bytes [d], [%4, {%5, r0}], [b];\n" \
    "add.u32 d, %2, 1*%15+4096;\n" \
    "cp.async.bulk.tensor.2d.shared::cluster.global.tile.mbarrier::complete_tx::bytes [d], [%4, {%6, r1}], [b];\n" \
    "add.u32 d, %2, 2*%15+4096;\n" \
    "cp.async.bulk.tensor.2d.shared::cluster.global.tile.mbarrier::complete_tx::bytes [d], [%4, {%7, r2}], [b];\n" \
    "add.u32 d, %2, 3*%15+4096;\n" \
    "cp.async.bulk.tensor.2d.shared::cluster.global.tile.mbarrier::complete_tx::bytes [d], [%4, {%8, r3}], [b];\n" \
    "add.u32 %0, %0, 16;\n" \
    "ld.shared.v4.u32 {r0,r1,r2,r3}, [%0+%16];\n" \
    "ld.shared.u16 t, [%0+72]; setp.ge.u32 q, %0, %10;\n" \
    "mov.u32 c, %%globaltimer_lo; sub.s32 c, c, %11; sub.s32 c, c, t; setp.ge.s32 p, c, 0;\n" \
    "@p bra.uni G4;\n" \
    "T4:\n" \
    "nanosleep.u32 64;\n" \
    "mov.u32 c, %%globaltimer_lo; sub.s32 c, c, %11; sub.s32 c, c, t; setp.lt.s32 p, c, 0;\n" \
    "@p bra.uni T4;\n" \
    "G4:\n" \
    "ld.volatile.shared.u32 w, [%9]; setp.lt.or.u32 p, w, %0, q;\n" \
    "@p bra.uni W4;\n" \
    "add.u32 b, %3, 32;\n" \
    "mbarrier.arrive.expect_tx.shared::cta.b64 _, [b], %12;\n" \
    "add.u32 d, %2, 0*%15+5120;\n" \
    "cp.async.bulk.tensor.2d.shared::cluster.global.tile.mbarrier::complete_tx::bytes [d], [%4, {%5, r0}], [b];\n" \
    "add.u32 d, %2, 1*%15+5120;\n" \
    "cp.async.bulk.tensor.2d.shared::cluster.global.tile.mbarrier::complete_tx::bytes [d], [%4, {%6, r1}], [b];\n" \
    "add.u32 d, %2, 2*%15+5120;\n" \
    "cp.async.bulk.tensor.2d.shared::cluster.global.tile.mbarrier::complete_tx::bytes [d], [%4, {%7, r2}], [b];\n" \
    "add.u32 d, %2, 3*%15+5120;\n" \
    "cp.async.bulk.tensor.2d.shared::cluster.global.tile.mbarrier::complete_tx::bytes [d], [%4, {%8, r3}], [b];\n" \
    "add.u32 %0, %0, 16;\n" \
    "shr.u32 c, r0, 3; add.u32 c, c, %17; setp.lt.u32 p, c, %1;\n" \
    "@p bra.uni TOP;\n" \
    "sub.s32 c, %14, %1; min.s32 c, c, %18; setp.gt.s32 p, c, 0; shl.b32 c, c, 10; mad.wide.u32 a, %1, 1024, %13;\n" \
    "@p cp.async.bulk.prefetch.L2.global [a], c;\n" \
    "add.u32 %1, %1, %19;\n" \
    "bra.uni TOP;\n" \
    "W0:\n" \
    "add.u32 n, n, 1; setp.lt.and.u32 p, n, 0x1000000, !q;\n" \
    "@p bra.uni G0;\n" \
    "bra.uni END;\n" \
    "W1:\n" \
    "add.u32 n, n, 1; setp.lt.and.u32 p, n, 0x1000000, !q;\n" \
    "@p bra.uni G1;\n" \
    "bra.uni END;\n" \
    "W2:\n" \
    "add.u32 n, n, 1; setp.lt.and.u32 p, n, 0x1000000, !q;\n" \
    "@p bra.uni G2;\n" \
    "bra.uni END;\n" \
    "W3:\n" \
    "add.u32 n, n, 1; setp.lt.and.u32 p, n, 0x1000000, !q;\n" \
    "@p bra.uni G3;\n" \
    "bra.uni END;\n" \
    "W4:\n" \
    "add.u32 n, n, 1; setp.lt.and.u32 p, n, 0x1000000, !q;\n" \
    "@p bra.uni G4;\n" \
    "bra.uni END;\n" \
    "END:\n" \
    "}\n" \
    ""

__device__ __forceinline__ void wgmma_n64(float (&d)[32], const uint32_t (&a)[4], uint64_t desc, int acc) {
    asm volatile("{\n\t.reg .pred p;\n\tsetp.ne.u32 p, %37, 0;\n\t"
        "wgmma.mma_async.sync.aligned.m64n64k16.f32.bf16.bf16 {%0,%1,%2,%3,%4,%5,%6,%7,%8,%9,%10,%11,%12,%13,%14,%15,"
        "%16,%17,%18,%19,%20,%21,%22,%23,%24,%25,%26,%27,%28,%29,%30,%31}, {%32,%33,%34,%35}, %36, p, 1, 1, 1;\n\t}"
        : "+f"(d[0]), "+f"(d[1]), "+f"(d[2]), "+f"(d[3]), "+f"(d[4]), "+f"(d[5]), "+f"(d[6]), "+f"(d[7]),
          "+f"(d[8]), "+f"(d[9]), "+f"(d[10]), "+f"(d[11]), "+f"(d[12]), "+f"(d[13]), "+f"(d[14]), "+f"(d[15]),
          "+f"(d[16]), "+f"(d[17]), "+f"(d[18]), "+f"(d[19]), "+f"(d[20]), "+f"(d[21]), "+f"(d[22]), "+f"(d[23]),
          "+f"(d[24]), "+f"(d[25]), "+f"(d[26]), "+f"(d[27]), "+f"(d[28]), "+f"(d[29]), "+f"(d[30]), "+f"(d[31])
        : "r"(a[0]), "r"(a[1]), "r"(a[2]), "r"(a[3]), "l"(desc), "r"(acc));
}

#define YFP 1
#define ORD 1
#define ZC 40
#define PW 1
#define WN 9
#define FEN 0
#define PT1 1000
#define PT0 1850
#define PDT 36.8
#define NSLEEP 64
#define PFA 1400
#define PFR 8
#define PF0 1
#define PF1 1
template <int ID, int COUNT> __device__ __forceinline__ void bar_sync() { asm volatile("bar.sync %0, %1;" ::"n"(ID), "n"(COUNT) : "memory"); }
template <int ID, int COUNT> __device__ __forceinline__ void bar_arrive() { asm volatile("bar.arrive %0, %1;" ::"n"(ID), "n"(COUNT) : "memory"); }
__device__ __forceinline__ void await(const uint32_t* p, uint32_t n) {
    uint32_t v;
    int guard = 0;
    do asm volatile("ld.relaxed.gpu.global.u32 %0, [%1];" : "=r"(v) : "l"(p) : "memory");
    while (__any_sync(0xffffffffu, v < n) && ++guard < (1 << 20));
}
template <int BYTES>
__device__ __forceinline__ void fill(uint32_t addr, uint4 v, int tid) {
#pragma unroll
    for (int r = 0; r < (BYTES / 16 + NT - 1) / NT; r++)
        sts128_if((r + 1) * NT <= BYTES / 16 || r * NT + tid < BYTES / 16, addr + (r * NT + tid) * 16, v);
}

__device__ __forceinline__ uint32_t group_cap(uint32_t key, int lane) {
    return __reduce_add_sync(0xffffffffu, min(key >> 5, GK)) > KCAP ? KCAP / NG : lane < 16 ? GK : 128 - 2 * GK;
}
template <int NR>
__device__ __forceinline__ void build_list(uint4 lt, uint32_t len, int wl, int lane, int N, uint32_t bin_magic, uint32_t pace) {
    const uint32_t n0 = lt.x >> 5, n01 = n0 + (lt.y >> 5), lh = sb + SM_LH + wl * (LBIN * 4);
    const uint32_t o0 = (lt.x & 31) * GK, o1 = (lt.y & 31) * GK - n0, o2 = (lt.z & 31) * GK - n01;
    uint4 w[NR], e[NR];
    uint32_t p[NR], ba[NR];
#pragma unroll
    for (int j = 0; j < NR; j++) {
        const uint32_t i = j * 32 + lane;
        w[j] = lds128(sb + SM_KSG + (i + (i < n0 ? o0 : i < n01 ? o1 : o2)) * 16);
        e[j].z = i < n0 ? 2 : i < n01 ? 4 : 8;
    }
#pragma unroll
    for (int j = 0; j < NR; j++) {
        const uint32_t key = min(((w[j].x & 0x1fff8) + (w[j].y & 0x1fff8) + (w[j].z & 0x1fff8) + (w[j].w & 0x1fff8)) >> 2, N * 8 - 8);
        ba[j] = j * 32 + lane < len ? lh + (key * bin_magic >> 21) * 4 : sb + SM_DUM + lane * 4;
        e[j].z |= min(__umulhi(key, pace), 0xffff) & 0xfff0;
    }
#pragma unroll
    for (int j = 0; j < NR; j++) p[j] = atoms_inc(ba[j]);
    __syncwarp();
    const uint4 u = lds128(lh + lane * 16);
#pragma unroll
    for (int j = 0; j < NR; j++) {
        e[j].x = (__byte_perm(w[j].x, w[j].y, 0x7632) & 0xfff0fff0u) | 1u << (w[j].x & 3) | 0x10000u << (w[j].y & 3);
        e[j].y = (__byte_perm(w[j].z, w[j].w, 0x7632) & 0xfff0fff0u) | 1u << (w[j].z & 3) | 0x10000u << (w[j].w & 3);
        asm volatile("" : "+r"(e[j].x), "+r"(e[j].y), "+r"(e[j].z));
    }
    const uint32_t sum = u.x + u.y + u.z + u.w, ex = warp_incl_scan(sum) - sum;
    sts128_if(true, lh + lane * 16, make_uint4(ex, ex + u.x, ex + u.x + u.y, ex + u.x + u.y + u.z));
    __syncwarp();
#pragma unroll
    for (int j = 0; j < NR; j++) p[j] += lds32(ba[j]);
#pragma unroll
    for (int j = 0; j < NR; j++) {
        const uint32_t turn = (p[j] * SMG) >> 16, slot = p[j] - turn * S;
        sts128_if(p[j] < len, sb + SM_SRC + (lt.w + p[j]) * 16, make_uint4(w[j].x & 0x1fff8, w[j].y & 0x1fff8, w[j].z & 0x1fff8, w[j].w & 0x1fff8));
        sts128_if(p[j] < len, sb + SM_LIST + (lt.w + p[j]) * 16,
                  make_uint4(e[j].x, e[j].y, e[j].z | (turn & 1) | slot << 26, sb + SM_BAR + (wl * S + slot) * 8));
    }
}
__device__ __forceinline__ bool next_excess(const Scratch* scr, const __nv_bfloat16* x, uint32_t va0) {
    uint32_t tid, cta;
    asm volatile("mov.u32 %0, %tid.x;" : "=r"(tid));
    asm volatile("mov.u32 %0, %ctaid.x;" : "=r"(cta));
    const int lane = tid & 31, wl = tid >> 5;
    const uint32_t bar_w = sb + SM_BAR + NW * S * 8, own = sb + SM_SRC + wl * 128, st = sb + SM_STATE + wl * 16;
    const uint32_t grp = lds32(sb + SM_MISC + 64 + wl * 4);
    uint4 c = lds128(st);
    __syncwarp();
    for (; c.x <= NCTA; c.x++, c.y = 0) {
        if (c.y == 0 && c.z == 0)
            c.x += __reduce_min_sync(0xffffffffu, c.x + lane >= NCTA || (lds32(sb + SM_SEG + min(c.x + lane, NCTA - 1) * 4) >> 12) > MBE ? lane : 31);
        const uint32_t loc = lds32(sb + SM_SEG + min(c.x, NCTA - 1) * 4);
        const int n = c.x < NCTA ? (int)(loc >> 12) - MBE : lds32(sb + SM_MISC + 12);
        for (; (int)c.y < n; c.y += 32, c.z = 0) {
            uint2 u = make_uint2(0xffffffffu, c.x * SLICE + (loc & 0xfff) + MBE + c.y + lane);
            if ((int)c.y + lane < n) {
                if (c.x < NCTA) u.x = __ldcg(scr->ss + u.y);
                else u = __ldcg(scr->exc + cta * MBW + c.y + lane);
            }
            const uint32_t gw = (u.x >> 25 & 31) - 1, ja = gw == (grp & 31) ? 1 : gw == (grp >> 5 & 31) ? 2 : gw == grp >> 10 ? 3 : 0;
            const unsigned todo = __ballot_sync(0xffffffffu, ja) & ~c.z;
            if (!todo) continue;
            const uint32_t jf = __shfl_sync(0xffffffffu, ja, __ffs(todo) - 1);
            const unsigned m = todo & __ballot_sync(0xffffffffu, ja == jf);
            const uint32_t from = __fns(m, 0, (lane & 3) + 1);
            const bool pad = from > 31;
            c.z |= __reduce_or_sync(0xffffffffu, pad ? 0 : 1u << from);
            if (!(todo & ~c.z)) { c.y += 32; c.z = 0; }
            u.x = __shfl_sync(0xffffffffu, u.x, pad ? __ffs(m) - 1 : from);
            u.y = __shfl_sync(0xffffffffu, u.y, from);
            const uint32_t slot = (lds32(sb + SM_MISC + 32 + wl * 4) / 64 + 1) % S;
#pragma unroll 1
            for (int k = 0; k < 8; k++)
                cp16((va0 ^ (k & 4) * 8) + slot * 1024 + (k & 1) * 128 + (k & 2) * 256,
                     reinterpret_cast<const uint4*>(x) + (size_t)(u.x >> 3 & 0x3fff) * 64 + chunk_of(k, lane >> 2));
            mbar_wait(bar_w, 0);
            if (lane < 4) {
                if (!pad) cp16(own + 64 + lane * 16, scr->rec + u.y);
                asm volatile("st.shared.u16 [%0], %1;" ::"r"(own + lane * 2),
                             "h"((uint16_t)(((pad ? sb + SM_ZERO : own + 64 + lane * 16) - sb - SM_REC) | 1u << (u.x & 3))) : "memory");
                sts32_if(lane == 0, own + 8, 1u << jf | slot << 26);
                sts32_if(lane == 0, own + 12, bar_w);
                sts128_if(lane == 0, own + 16, make_uint4(0, 0, 0, bar_w));
                sts128_if(lane == 0, st, c);
            }
            asm volatile("cp.async.wait_all;" ::: "memory");
            __syncwarp();
            return true;
        }
    }
    return false;
}

template <int MODE>
__global__ void __launch_bounds__(NT, 1)
tfn_kernel(const int* __restrict__ dst, const int* __restrict__ src, Scratch* scr, int E, int slice,
           int N, int npc, uint32_t npc_magic, uint32_t bin_magic, const uint2* __restrict__ Y, const uint2* __restrict__ ef,
           const __nv_bfloat16* __restrict__ w_rad, const __nv_bfloat16* __restrict__ cg, const __nv_bfloat16* __restrict__ x,
           const __nv_bfloat16* __restrict__ w_mix, __nv_bfloat16* __restrict__ out, uint32_t pace,
           const __grid_constant__ CUtensorMap xmap, const __grid_constant__ CUtensorMap wmap) {
    extern __shared__ __align__(1024) uint8_t smem[];
    const int tid = threadIdx.x, lane = tid & 31, warp = __shfl_sync(0xffffffffu, tid >> 5, 0);
    const int cta = blockIdx.x;
    const uint32_t bar_w = sb + SM_BAR + NW * S * 8, bar_raw = bar_w + 8, bar_rec = bar_w + 16, bar_mb = bar_w + 24;
    auto prefetch_x = [&](int chunk) {
        const int row = (chunk * NCTA + cta) * PFR;
        if (row < N)
            asm volatile("cp.async.bulk.prefetch.L2.global [%0], %1;" ::"l"(x + (size_t)row * 512), "r"(min(PFR, N - row) * 1024));
    };
    const int g = lane >> 2, t = lane & 3;
    uint32_t wz[4][2], wt[2];
    auto weights = [&]() {
            const uint32_t* wr = reinterpret_cast<const uint32_t*>(w_rad) + (t & 1) * 128;
            const uint16_t* cp = reinterpret_cast<const uint16_t*>(cg) + (t >> 1) * 32 + (t & 1) * 8 + (g & 3);
            const __nv_bfloat162 half = __floats2bfloat162_rn(0.5f, 0.5f);
#pragma unroll
            for (int j = 0; j < 4; j++) {
                uint32_t u0 = __ldg(wr + chunk_of(2 * j + (t >> 1), g)), u1 = __ldg(wr + chunk_of(2 * j + (t >> 1), g) + 64);
                const __nv_bfloat162 h0 = __hmul2(*reinterpret_cast<__nv_bfloat162*>(&u0), half);
                const __nv_bfloat162 h1 = __hmul2(*reinterpret_cast<__nv_bfloat162*>(&u1), half);
                u0 = *reinterpret_cast<const uint32_t*>(&h0);
                u1 = *reinterpret_cast<const uint32_t*>(&h1);
                wz[j][0] = __byte_perm(u0, u1, 0x5410);
                wz[j][1] = __byte_perm(u0, u1, 0x7632);
            }
            wt[0] = __ldg(cp) | ((uint32_t)__ldg(cp + 4) << 16);
            wt[1] = __ldg(cp + 16) | ((uint32_t)__ldg(cp + 20) << 16);
            sts32_if((wz[0][0] ^ wz[0][1] ^ wz[1][0] ^ wz[1][1] ^ wz[2][0] ^ wz[2][1] ^ wz[3][0] ^ wz[3][1] ^ wt[0] ^ wt[1]) == 1,
                     sb + SM_ZERO + 96, 0);
    };

    const int e0 = cta * slice, ne = min(E - e0, slice);
    uint32_t a_d[RA], a_s[RA];
    uint32_t tag = 0;
    if (MODE & 1) {
        const int q = min(e0 / 4 + tid, (E - 1) >> 2), e = min(e0 + 4 * NT + tid, E - 1);
        const int4 d4 = __ldcs(reinterpret_cast<const int4*>(dst) + q);
        a_d[4] = __ldcs(dst + e);
        const int4 s4 = __ldcs(reinterpret_cast<const int4*>(src) + q);
        a_s[4] = __ldcs(src + e);
        a_d[0] = d4.x; a_d[1] = d4.y; a_d[2] = d4.z; a_d[3] = d4.w;
        a_s[0] = s4.x; a_s[1] = s4.y; a_s[2] = s4.z; a_s[3] = s4.w;
    }
    if (MODE == 3) asm volatile("ld.relaxed.gpu.global.u32 %0, [%1];" : "=r"(tag) : "l"(&scr->epoch) : "memory");
    auto load_raw = [&]() {
        const int bytes = max((ne + 1) >> 1, 0) * 16;
        asm volatile("mbarrier.arrive.expect_tx.shared::cta.b64 _, [%0], %1;" ::"r"(bar_raw), "r"(2 * bytes) : "memory");
        if (bytes > 0) {
            asm volatile("cp.async.bulk.shared::cluster.global.mbarrier::complete_tx::bytes [%0], [%1], %2, [%3];"
                         ::"r"(sb + SM_RAWY), "l"(Y + e0), "r"(bytes), "r"(bar_raw) : "memory");
            asm volatile("cp.async.bulk.shared::cluster.global.mbarrier::complete_tx::bytes [%0], [%1], %2, [%3];"
                         ::"r"(sb + SM_RAWF), "l"(ef + e0), "r"(bytes), "r"(bar_raw) : "memory");
        }
    };
    auto send = [&](bool p, uint32_t* gp, uint4 v) {
        asm volatile("{\n\t.reg .pred p;\n\tsetp.ne.u32 p, %5, 0;\n\t@p st.relaxed.gpu.global.v4.u32 [%0], {%1,%2,%3,%4};\n\t}"
                     ::"l"(gp), "r"(v.x), "r"(v.y), "r"(v.z), "r"(v.w), "r"((uint32_t)p) : "memory");
    };
    uint32_t mc[3];
    auto prewrite = [&](uint4 empty) {
#pragma unroll
        for (int r = 0; r < 3; r++) {
            const uint32_t i = r * NT + tid, c = i < 4 * NCTA ? i >> 2 : ((i - 4 * NCTA) * 10923) >> 16, j = i < 4 * NCTA ? (i & 3) + 2 : i - 4 * NCTA - c * 6 + 6;
            mc[r] = c << 8 | j;
            if (r > 0) send(c < NCTA && j >= 6, scr->mb + c * MBW + cta * MBC + j * 4, empty);
        }
    };
    if ((uint32_t)__cvta_generic_to_shared(smem) != sb) __trap();
    if (elect_one()) {
#pragma unroll
        for (int i = 0; i < S; i++)
            if (warp >= NW) mbar_init(sb + SM_BAR + ((warp - NW) * S + i) * 8, 1);
        if (warp == 0) {
            mbar_init(bar_w, NW);
            mbar_init(bar_raw, 1);
            mbar_init(bar_rec, NW);
            mbar_init(bar_mb, 1);
        }
        asm volatile("fence.mbarrier_init.release.cluster;" ::: "memory");
    }
    fill<SM_KSG - SM_BIN>(sb + SM_BIN, make_uint4(0, 0, 0, 0), tid);
    if (MODE & 1) {
        const uint32_t em = lane << (BSH + 2);
        const uint4 empty = make_uint4(em, em + (1 << BSH), em + (2 << BSH), em + (3 << BSH));
        if (PW == 0) prewrite(empty);
        fill<NCTA * ASTR * 4>(sb + SM_AMB, empty, tid);
    }
    sts32_if(tid < 32, sb + SM_AOFF + (NCTA + tid) * 4, SLICE);
    sts32_if(tid < 128, sb + SM_DUM + tid * 4, 0x10000);
    if (MODE & 2) {
        const uint32_t pad = RCAP << 20 | N << 3;
        fill<SM_BAR - SM_ZERO>(sb + SM_ZERO, make_uint4(0, 0, 0, 0), tid);
        fill<NG * GK * 16>(sb + SM_KSG, make_uint4(pad, pad, pad, pad), tid);
    }
    if ((MODE & 1) && PW == 1) {
        const uint32_t em = lane << (BSH + 2);
        prewrite(make_uint4(em, em + (1 << BSH), em + (2 << BSH), em + (3 << BSH)));
    }
    __syncthreads();
    STAMP(15);
    if (warp == 13 && (MODE & 2) && elect_one()) {
        asm volatile("cp.async.bulk.prefetch.L2.global [%0], 1024;" ::"l"(w_rad));
        asm volatile("cp.async.bulk.prefetch.L2.global [%0], 128;" ::"l"(cg));
        asm volatile("prefetch.tensormap [%0];" ::"l"(&xmap) : "memory");
        asm volatile("prefetch.tensormap [%0];" ::"l"(&wmap) : "memory");
    }
    if (MODE & 1) {
        if (YFP == 1 && warp == 14 && elect_one()) load_raw();
        const uint32_t z = lds32(sb + SM_KEY + lane * 4);
        tag = ((tag + z) & 1) + 1;
        const uint32_t tg = tag << 30;
        uint32_t cc[RA], rk[RA];
#pragma unroll
        for (int r = 0; r < RA; r++) {
            cc[r] = (r < 4 ? 4 * tid + r : 4 * NT + tid) < ne ? __umulhi(a_d[r], npc_magic + z) : NCTA + lane;
            rk[r] = atoms_inc(sb + SM_HIST + cc[r] * 4);
        }
        if (YFP == 2 && tid == 0) load_raw();
#pragma unroll
        for (int r = 0; r < RA; r++) {
            const uint32_t l = a_d[r] - cc[r] * npc;
            a_s[r] = (tg + ((l < 64 ? (l >> 2) + 1 : (l >> 1) - 15) << 25)) | ((a_s[r] * (bin_magic + z)) & ((NBIN - 1) << BSH)) | a_s[r] * (8 + z) | (l & (l < 64 ? 3 : 1));
            sts32_if(true, sb + SM_AMB + (cc[r] * ASTR + min(rk[r], MBE) + 1) * 4, a_s[r]);
        }
        STAMP(1);
        __syncthreads();
        STAMP(28);
        if (YFP == 3 && warp == 14 && elect_one()) load_raw();
        uint32_t hh[3];
#pragma unroll
        for (int r = 1; r < 3; r++) hh[r] = lds32(sb + SM_HIST + min(mc[r] >> 8, NCTA + 33) * 4);
#pragma unroll
        for (int r = 0; r < 3; r++) {
            const uint32_t c = mc[r] >> 8, j = mc[r] & 15;
            const bool used = r == 0 || j < 6 || (c < NCTA && hh[r] >= (j & 14) * 4);
            if (r == 0 || __any_sync(0xffffffffu, used))
                send(used, scr->mb + c * MBW + cta * MBC + j * 4, lds128(sb + SM_AMB + min(c, NCTA) * (ASTR * 4) + j * 16));
        }
        if (warp >= 7) {
            const uint32_t c = (tid - 7 * 32) >> 1, h = !(tid & 1) && c < NCTA ? lds32(sb + SM_HIST + c * 4) : 0;
            uint4 v = lds128(sb + SM_AMB + c * (ASTR * 4) + (tid & 1) * 16);
            const uint32_t inc = warp_incl_scan(h);
            const uint32_t off = __shfl_sync(0xffffffffu, atoms_add(sb + SM_HIST + 135 * 4 + lane * 4, lane == 31 ? inc : 0), 31) + inc - h;
            if (!(tid & 1)) v.x = tg | h << 12 | off;
            send(c < NCTA, scr->mb + c * MBW + cta * MBC + (tid & 1) * 4, v);
            sts32_if(!(tid & 1) && c < NCTA, sb + SM_AOFF + c * 4, off);
        }
        STAMP(2);
        __syncthreads();
        if (MODE == 3 && tid == NT - 1) asm volatile("red.relaxed.gpu.global.add.u32 [%0], 1;" ::"l"(scr->sent + (tag & 1)) : "memory");
        if (YFP == 4 && warp == 6 && elect_one()) load_raw();
        uint32_t ap[2 * RA];
#pragma unroll
        for (int r = 0; r < RA; r++) ap[r] = rk[r] + lds32(sb + SM_AOFF + cc[r] * 4);
        if (__builtin_expect(max(max(max(rk[0], rk[1]), max(rk[2], rk[3])), rk[4]) >= MBE, 0)) {
#pragma unroll
            for (int r = 0; r < RA; r++)
                if (rk[r] >= MBE && cc[r] < NCTA) __stcg(scr->ss + cta * SLICE + ap[r], a_s[r]);
            __threadfence();
        }
        if (warp >= NW) {
            asm volatile("st.shared.v2.u32 [%0], {%1, %2};" ::"r"(sb + SM_AP + (tid - NH) * 8), "r"(ap[0] | ap[1] << 16), "r"(ap[2] | ap[3] << 16) : "memory");
            sts32_if(true, sb + SM_AP + NH * 8 + (tid - NH) * 4, ap[4]);
            bar_arrive<1, NT>();
        } else {
            bar_sync<1, NT>();
            const uint2 u = lds64(sb + SM_AP + tid * 8);
            ap[5] = u.x & 0xffff; ap[6] = u.x >> 16; ap[7] = u.y & 0xffff; ap[8] = u.y >> 16;
            ap[9] = lds32(sb + SM_AP + NH * 8 + tid * 4);
            const bool sw = lane & 4;
            mbar_wait(bar_raw, 0);
            STAMP(10);
#pragma unroll
            for (int hh = 0; hh < 2; hh++) {
                const uint32_t a = sb + SM_RAWY + (hh * NH + tid) * 32 + (lane & 4) * 4, b = sb + SM_RAWY + (4 * NT + hh * NH + tid) * 8;
                const uint4 y0 = lds128(a), f0 = lds128(a + SLICE * 8), y1 = lds128(a ^ 16), f1 = lds128((a ^ 16) + SLICE * 8);
                const uint2 y2 = lds64(b), f2 = lds64(b + SLICE * 8);
                const uint32_t* q = ap + hh * RA;
                sts128_if(true, sb + SM_AREC + (sw ? q[2] : q[0]) * 16, make_uint4(f0.x, y0.x, f0.y, y0.y));
                sts128_if(true, sb + SM_AREC + (sw ? q[3] : q[1]) * 16, make_uint4(f0.z, y0.z, f0.w, y0.w));
                sts128_if(true, sb + SM_AREC + (sw ? q[0] : q[2]) * 16, make_uint4(f1.x, y1.x, f1.y, y1.y));
                sts128_if(true, sb + SM_AREC + (sw ? q[1] : q[3]) * 16, make_uint4(f1.z, y1.z, f1.w, y1.w));
                sts128_if(true, sb + SM_AREC + q[4] * 16, make_uint4(f2.x, y2.x, f2.y, y2.y));
            }
            asm volatile("fence.proxy.async.shared::cta;" ::: "memory");
            bar_sync<7, NH>();
            STAMP(25);
            if (MODE == 3 && ORD && warp == NW - 1) bar_sync<9, 64>();
            if (warp == NW - 1 && lane == 0 && ne > 0)
                asm volatile("cp.async.bulk.global.shared::cta.bulk_group [%0], [%1], %2;"
                             ::"l"(scr->rec + cta * SLICE), "r"(sb + SM_AREC), "r"(ne * 16) : "memory");
            uint32_t tm = 0;
            if (MODE == 3 && warp == NW - 1) {
                mbar_wait(bar_mb, 0);
                tm = timer32();
            }
            if (MODE == 3) weights();
            if (warp == NW - 1) {
                asm volatile("cp.async.bulk.commit_group;" ::: "memory");
                asm volatile("cp.async.bulk.wait_group 0;" ::: "memory");
                STAMPT(26, NH - 32);
                if (MODE == 3) {
                    if (lane == 0) {
                        asm volatile("red.relaxed.gpu.global.max.u32 [%0], %1;" ::"l"(scr->sent2[tag & 1] + 8), "r"(max(tm + PT0, timer32() + PT1)) : "memory");
                        asm volatile("red.relaxed.gpu.global.or.b32 [%0], %1;" ::"l"(scr->sent2[tag & 1] + (cta & 7)), "r"(1u << (cta >> 3)) : "memory");
                    }
                    uint32_t v;
                    asm volatile("ld.relaxed.gpu.global.u32 %0, [%1];" : "=r"(v) : "l"(scr->sent2[tag & 1] + (lane & 15)) : "memory");
                    sts32_if(lane < NW, sb + SM_MISC + 96 + lane * 4, v);
                }
            }
        }
    } else {
        tag = 1;
    }
    if (!(MODE & 2)) return;
    const int wl = warp & (NW - 1);
    const uint32_t ring = sb + SM_RING + wl * (S * 1024);
    const uint32_t bars = sb + SM_BAR + wl * (S * 8);
    const uint32_t pos = bar_w + 32 + wl * 4;

    if (warp >= NW) {
        uint32_t ss[RL + RX], rk[RL + RX];
        const uint32_t sl = wl + 8 * lane, empty = lane << BSH;
        if (wl == 0) {
            if (MODE == 3) await(scr->sent + (tag & 1), NCTA);
            STAMPT(11, NH);
            if (elect_one()) {
                asm volatile("mbarrier.arrive.expect_tx.shared::cta.b64 _, [%0], %1;" ::"r"(bar_mb), "n"(MBW * 4) : "memory");
                asm volatile("cp.async.bulk.shared::cluster.global.mbarrier::complete_tx::bytes [%0], [%1], %2, [%3];"
                             ::"r"(sb + SM_AMB), "l"(scr->mb + cta * MBW), "n"(MBW * 4), "r"(bar_mb) : "memory");
            }
            if (MODE == 3 && ORD) bar_arrive<9, 64>();
            if (MODE != 3) sts32_if(true, sb + SM_MISC + 4, timer32() + PT0);
        }
        mbar_wait(bar_mb, 0);
        STAMPT(3, NH);
        uint32_t loc, cnt;
        bool late;
        for (int guard = 0;; guard++) {
            loc = lds32(sb + SM_AMB + min(sl, NCTA - 1) * (MBC * 4));
#pragma unroll
            for (int r = 0; r < RL; r++) ss[r] = lds32(sb + SM_AMB + ((wl + 8 * r) * MBC + lane + 1) * 4);
            if (wl + 8 * (RL - 1) >= NCTA) ss[RL - 1] = empty;
            cnt = sl < NCTA ? loc >> 12 & 0xfff : 0;
            late = __any_sync(0xffffffffu, cnt > 32);
            uint32_t any = ~loc >> 30 & tag ? 0xffffffffu : 0, got = -min(cnt, MBE) * tag;
#pragma unroll
            for (int r = 0; r < RL; r++) { any |= ss[r]; got += ss[r] >> 30; }
            if (__builtin_expect(late, 0)) {
#pragma unroll
                for (int q = 0; q < RX; q++) {
                    const uint32_t from = 2 * q + (lane >> 4), rnk = 32 + (lane & 15);
                    ss[RL + q] = lds32(sb + SM_AMB + ((wl + 8 * from) * MBC + rnk + 1) * 4);
                    if (rnk >= min(__shfl_sync(0xffffffffu, cnt, from), MBE)) ss[RL + q] = empty;
                    any |= ss[RL + q];
                    got += ss[RL + q] >> 30;
                }
            }
            if (!(__reduce_add_sync(0xffffffffu, got) | __any_sync(0xffffffffu, any >> 30 & (3 - tag))) || guard == 1 << 20) break;
#pragma unroll 1
            for (int r = wl; r < NCTA; r += 8)
                if (lane < MBC / 4)
                    sts128_if(true, sb + SM_AMB + (r * MBC + lane * 4) * 4, ldg128_relaxed(reinterpret_cast<const uint4*>(scr->mb + cta * MBW + r * MBC) + lane));
            __syncwarp();
        }
        STAMPT(4, NH);
        auto bin_of = [&](uint32_t w) { return sb + SM_DUM + (w >> (BSH - 2) & (NBIN * 128 - 4)); };
#pragma unroll
        for (int r = 0; r < RL; r++) rk[r] = atoms_add(bin_of(ss[r]), 4);
        if (__builtin_expect(late, 0)) {
#pragma unroll
            for (int r = RL; r < RL + RX; r++) rk[r] = atoms_add(bin_of(ss[r]), 4);
            sts32_if(cnt > MBE, sb + SM_MISC + 8, 1);
        }
        STAMPT(5, NH);
        bar_sync<3, NH>();
        uint32_t dof;
        {
            constexpr int Q = NBIN / 128;
            const uint32_t a = sb + SM_BIN + wl * (NBIN * 12) + lane * (16 * Q), sw = Q == 2 ? (lane & 4) * 4 : 0;
            uint4 u[3][Q];
            uint32_t sum[3], s0[3];
#pragma unroll
            for (int j = 0; j < 3; j++) {
#pragma unroll
                for (int q = 0; q < Q; q++) u[j][q] = lds128(a + j * (NBIN * 4) + (sw ^ q * 16));
                s0[j] = sum[j] = u[j][0].x + u[j][0].y + u[j][0].z + u[j][0].w;
                if (Q == 2) sum[j] += u[j][1].x + u[j][1].y + u[j][1].z + u[j][1].w;
            }
            uint32_t i01 = sum[0] | sum[1] << 16, i2 = sum[2] | min(cnt, MBE) << 16;
#pragma unroll
            for (int o = 1; o < 32; o <<= 1) {
                scan_step(i01, o);
                scan_step(i2, o);
            }
            dof = atoms_add(sb + SM_MISC - 124 + lane * 4, lane == 31 ? i2 >> 16 : 0);
            const uint32_t inc[3] = {i01 & 0xffff, i01 >> 16, i2 & 0xffff};
#pragma unroll
            for (int j = 0; j < 3; j++) {
#pragma unroll
                for (int q = 0; q < Q; q++) {
                    const uint32_t p = (3 * wl + j) * (GK * 16) + inc[j] - (q == 0 ? (sw ? s0[j] : sum[j]) : (sw ? sum[j] : sum[j] - s0[j]));
                    const uint4 v = u[j][q];
                    sts128_if(true, a + j * (NBIN * 4) + (sw ^ q * 16), make_uint4(p, p + v.x, p + v.x + v.y, p + v.x + v.y + v.z));
                }
                sts32_if(lane == 31, sb + SM_KEY + (3 * wl + j) * 4, (inc[j] + 12) >> 4 << 5 | (3 * wl + j));
            }
            dof = __shfl_sync(0xffffffffu, dof, 31) + (i2 >> 16) - min(cnt, MBE);
            sts32_if(sl < NCTA, sb + SM_SEG + sl * 4, loc & 0xffffff);
            sts32_if(true, sb + SM_DOFF + (tid - NH) * 4, dof << 20);
            const uint64_t from = reinterpret_cast<uint64_t>(scr->rec + sl * SLICE + (loc & 0xfff));
            sts128_if(true, sb + SM_CPY + (tid - NH) * 16,
                      make_uint4((uint32_t)from, (uint32_t)(from >> 32), sb + SM_REC + dof * 16, min(min(cnt, MBE), RCAP - min(dof, RCAP)) * 16));
        }
        STAMPT(12, NH);
        bar_arrive<4, NT - 32>();
        bar_arrive<6, NH + 32>();
        bar_sync<3, NH>();
        const uint32_t key = lds32(sb + SM_KEY + lane * 4), nrec = lds32(sb + SM_MISC);
        uint32_t d20[RL + 3];
#pragma unroll
        for (int r = 0; r < RL; r += 4) {
            const uint4 v = lds128(sb + SM_DOFF + wl * 128 + r * 4);
            d20[r] = v.x; d20[r + 1] = v.y; d20[r + 2] = v.z; d20[r + 3] = v.w;
        }
#pragma unroll
        for (int r = 0; r < RL; r++) rk[r] += lds32(bin_of(ss[r]));
        const uint32_t cap = group_cap(key, lane);
        const uint32_t lim = __any_sync(0xffffffffu, (key >> 5) > cap || nrec > RCAP) ? 0 : 0x20000;
#pragma unroll
        for (int r = 0; r < RL; r++) {
            uint32_t v;
            asm("lop3.b32 %0, %1, 0x1ffff, %2, 0xea;" : "=r"(v) : "r"(ss[r]), "r"(lane << 20));
            sts32_if(rk[r] < lim, sb + SM_KSG + rk[r], v + d20[r]);
        }
        if (__builtin_expect(late, 0)) {
#pragma unroll
            for (int r = RL; r < RL + RX; r++) rk[r] += lds32(bin_of(ss[r]));
#pragma unroll
            for (int r = RL; r < RL + RX; r++)
                sts32_if(rk[r] < lim, sb + SM_KSG + rk[r],
                         (__shfl_sync(0xffffffffu, dof, 2 * (r - RL) + (lane >> 4)) + 32 + (lane & 15)) << 20 | (ss[r] & 0x1ffffu));
        }
        if (__builtin_expect(lim == 0, 0)) {
            const uint32_t tmp = sb + SM_AMB + (wl * MBC + lane) * 4;
#pragma unroll 1
            for (int part = 0; part < (late ? 4 : 3); part++) {
#pragma unroll
                for (int r = 0; r < RL + RX; r++)
                    if (r / 8 == part) {
                        sts32_if(true, tmp + (r & 7) * (16 * MBC * 4), r < RL || late ? ss[r] : 0);
                        sts32_if(true, tmp + ((r & 7) * 2 + 1) * (8 * MBC * 4), r < RL || late ? rk[r] : 0x20000);
                    }
#pragma unroll 1
                for (int r = part * 8; r < min(part * 8 + 8, RL + RX); r++) {
                    const uint32_t w = lds32(tmp + (r & 7) * (16 * MBC * 4)), p = lds32(tmp + ((r & 7) * 2 + 1) * (8 * MBC * 4));
                    const uint32_t rnk = r < RL ? lane : 32 + (lane & 15), from = r < RL ? r : 2 * (r - RL) + (lane >> 4), gw = (w >> 25 & 31) - 1;
                    const uint32_t ri = __shfl_sync(0xffffffffu, dof, from) + rnk, gi = __shfl_sync(0xffffffffu, loc & 0xfff, from) + rnk;
                    const bool fits = p - gw * (GK * 16) < __shfl_sync(0xffffffffu, cap, gw) * 16;
                    if (p < 0x20000) {
                        sts32_if(fits, sb + SM_KSG + p, min(ri, RCAP) << 20 | (w & 0x1ffffu));
                        if (!fits || ri >= RCAP) __stcg(scr->exc + cta * MBW + atoms_inc(sb + SM_MISC + 12), make_uint2(w, (wl + 8 * from) * SLICE + gi));
                    }
                }
            }
        }
        STAMPT(13, NH);
        bar_sync<8, NH + 32>();
        STAMPT(31, NH);
        const uint4 lt = lds128(sb + SM_LT + wl * 16);
        const uint32_t lb = lt.w, len = (lt.x >> 5) + (lt.y >> 5) + (lt.z >> 5), le = lb + len;
        if (__builtin_expect(len <= 96, 1)) build_list<3>(lt, len, wl, lane, N, bin_magic, pace);
        else build_list<4>(lt, len, wl, lane, N, bin_magic, pace);
        STAMPT(27, NH);
        if (FEN) asm volatile("fence.proxy.async.shared::cta;" ::: "memory");
        bar_arrive<2, NT>();
        bar_sync<5, NT>();
        STAMPT(6, NH);
        asm volatile("setmaxnreg.dec.sync.aligned.u32 24;");
        const uint32_t z = lds32(sb + SM_ZERO + (lane & 3) * 4);
        const uint32_t bytes = opaque(4096 + z);
        if (elect_one()) {
            const uint4 z0 = lds128v(sb + SM_ZERO);
            uint32_t ka = sb + SM_LIST + lb * 16 - 16 * (S - 1);
            if (wl < PF1) prefetch_x(PF0 + wl);
            int row = ((PF0 + PF1 + wl) * NCTA + cta) * PFR;
            asm volatile(PRODUCER_PTX : "+r"(ka), "+r"(row)
                : "r"(ring - 1024 + lds32v(sb + SM_ZERO)), "r"(bars), "l"(reinterpret_cast<uint64_t>(&xmap) + lds32v(sb + SM_ZERO)),
                  "r"(z0.x), "r"(z0.y), "r"(z0.z), "r"(z0.w), "r"(pos), "r"(ka + len * 16), "r"(lds32v(sb + SM_MISC + 4)), "r"(bytes),
                  "l"(x), "r"(N), "n"(RSTR), "n"(SM_SRC - SM_LIST + 16 * (S - 1)), "n"(PFA), "n"(PFR), "n"(NW * NCTA * PFR) : "memory");
            const uint32_t d = ring + (len - ((len * SMG) >> 16) * S) * 1024;
            STAMPT(20, NW * 32);
            for (int guard = 0; lds32v(pos) + 16 * (S - 1) < sb + SM_LIST + le * 16 && guard < (1 << 20); guard++) __nanosleep(NSLEEP);
            asm volatile("mbarrier.arrive.expect_tx.shared::cta.b64 _, [%0], 4096;" ::"r"(bar_w) : "memory");
#pragma unroll
            for (uint32_t r = 0; r < 8; r++)
                asm volatile("cp.async.bulk.tensor.5d.shared::cluster.global.tile.mbarrier::complete_tx::bytes [%0], [%1, {%2, %3, %4, %5, %6}], [%7];"
                             ::"r"(d + (r >> 1) * RSTR + (r & 1) * 512), "l"(&wmap), "r"((r >> 2) * 64), "r"((r >> 1) & 1),
                               "r"((wl >> 1) & 2), "r"(((r ^ (wl >> 1)) & 1) + (wl & 1) * 2), "r"(wl & 2), "r"(bar_w) : "memory");
            STAMPT(21, NW * 32);
        }
        return;
    }

    {
        if (MODE == 2) weights();
        if (warp == NW - 1) bar_sync<6, NH + 32>();
        else bar_sync<4, NT - 32>();
        if (warp == 0) {
            const uint32_t key = lds32(sb + SM_KEY + lane * 4);
            int rank = 0;
#pragma unroll
            for (int j = 0; j < 4; j++) {
                const uint4 o = lds128(sb + SM_KEY + (lane & 16) * 4 + j * 16);
                rank += ((key - o.x) >> 31) + ((key - o.y) >> 31) + ((key - o.z) >> 31) + ((key - o.w) >> 31);
            }
            const int n2 = 2 * __popc(__ballot_sync(0xffffffffu, key < 32) & 0xff0000);
            const int other = (rank < n2 ? n2 - 1 : 15 + n2) - rank;
            const int li = lane >= 16 ? 7 - rank : min(rank, other) - (rank < n2 ? 0 : n2 / 2);
            sts32_if(lane < NG, sb + SM_LT + (li < 4 ? li : 11 - li) * 16 + (lane >= 16 ? 8 : rank < other ? 0 : 4), min(key >> 5, group_cap(key, lane)) << 5 | lane);
            __syncwarp();
            const uint4 lt = lds128(sb + SM_LT + (lane & 7) * 16);
            const uint32_t len = (lt.x >> 5) + (lt.y >> 5) + (lt.z >> 5);
            uint32_t le = len + 1;
#pragma unroll
            for (int o = 1; o < 8; o <<= 1) scan_step(le, o);
            le -= 1;
            sts32_if(lane < NW, sb + SM_LT + lane * 16 + 12, le - len);
            bar_arrive<8, NH + 32>();
            if (lane < NW) {
                sts32_if(true, sb + SM_LIST + le * 16 + 12, bar_rec);
                sts32_if(true, bar_w + 32 + lane * 4, sb + SM_LIST + (le - len) * 16);
                sts32_if(true, sb + SM_MISC + 32 + lane * 4, (lane * S + len - ((len * SMG) >> 16) * S) * 64);
                sts32_if(true, sb + SM_MISC + 64 + lane * 4, (lt.x & 31) | (lt.y & 31) << 5 | (lt.z & 31) << 10);
            }
        }
        const uint4 cp = lds128(sb + SM_CPY + tid * 16);
        const uint32_t total = __reduce_add_sync(0xffffffffu, cp.w);
        if (FEN) asm volatile("fence.proxy.async.shared::cta;" ::: "memory");
        if (MODE != 3 || warp != NW - 1) bar_arrive<5, NT>();
        if (lane == 0) asm volatile("mbarrier.arrive.expect_tx.shared::cta.b64 _, [%0], %1;" ::"r"(bar_rec), "r"(total) : "memory");
        if (warp >= 2 && warp < 2 + PF0 && lane == 0) prefetch_x(warp - 2);
        if (MODE == 3 && cta == 0 && tid == 64) {
            scr->epoch = tag;
            scr->sent[~tag & 1] = 0;
            for (int i = 0; i < 9; i++) scr->sent2[~tag & 1][i] = 0;
        }
        STAMP(22);
        const uint32_t all = (1u << (NCTA - wl + 7) / 8) - 1;
        uint32_t done = 0;
        bool watch = MODE == 3 && warp == NW - 1;
        for (int guard = 0; (done != all || watch) && guard < (1 << 22); guard++) {
            uint32_t m = all, v;
            if (watch) asm volatile("ld.relaxed.gpu.global.u32 %0, [%1];" : "=r"(v) : "l"(scr->sent2[tag & 1] + (lane & 15)) : "memory");
            if (MODE == 3) m = lds32v(sb + SM_MISC + 96 + wl * 4);
            if (m != done) {
                asm volatile("fence.proxy.async.global;" ::: "memory");
                uint32_t now = m & ~done;
                if (watch) now &= __ballot_sync(0xffffffffu, __popc(now & ((1u << lane) - 1)) < WN);
                if ((now >> lane & 1) && cp.w)
                    asm volatile("cp.async.bulk.shared::cluster.global.mbarrier::complete_tx::bytes [%0], [%1], %2, [%3];"
                                 ::"r"(cp.z), "l"((uint64_t)cp.y << 32 | cp.x), "r"(cp.w), "r"(bar_rec) : "memory");
                done |= now;
            } else if (!watch) {
                __nanosleep(20);
            }
            if (watch) {
                sts32_if(lane < NW, sb + SM_MISC + 96 + lane * 4, v);
                if (__all_sync(0xffffffffu, lane >= NW || v == (1u << (NCTA - lane + 7) / 8) - 1)) {
                    sts32_if(lane == NW, sb + SM_MISC + 4, v);
                    bar_arrive<5, NT>();
                    watch = false;
                    STAMPT(24, NH - 32);
                }
                __syncwarp();
            }
        }
        if (watch) bar_arrive<5, NT>();
        STAMP(23);
        if (tid == 0 && cta < 128) asm volatile("cp.async.bulk.prefetch.L2.global [%0], 256;" ::"l"(w_mix + cta * 128));
        bar_sync<2, NT>();
        asm volatile("setmaxnreg.inc.sync.aligned.u32 232;" ::: "memory");
        STAMP(14);
    }

    float acc[40][4];
    const uint32_t z = lds32(sb + SM_ZERO + t * 4);
    const float zero = __uint_as_float(z);
#pragma unroll
    for (int j = 0; j < 40; j++) acc[j][0] = acc[j][1] = acc[j][2] = acc[j][3] = j < ZC ? 0.f : zero;
    const bool bact = (g & 1) == (t >> 1);
    mbar_wait(bar_rec, 0);
    STAMP(9);
    {
        auto keep = [&](uint32_t v) { return __shfl_sync(0xffffffffu, v + z, lane); };
        const uint32_t va0 = keep(ring + t * RSTR + (g & 2) * 128 + (g & 1) * 16 + ((((g >> 1) & 2) ^ ((((g >> 1) & 1) + t) & 3)) << 5));
        const uint32_t hm0 = keep(HM0(g >> 2)), hm1 = keep(0x40000u << (g >> 2)), sel = keep(0x1010u + (g >> 1) * 0x22 + t * 0x2200);
        const uint32_t rl = keep(bact ? (t & 1) * 8 : SM_ZERO - SM_REC), rm = keep(bact ? 0xfff0u : 0u);
        uint32_t lp = keep(lds32(pos));
        for (;;) {
        asm volatile(MAIN_LOOP_PTX : MAIN_LOOP_ACC(acc), "+r"(lp)
            : "r"(wz[0][0]), "r"(wz[0][1]), "r"(wz[1][0]), "r"(wz[1][1]), "r"(wz[2][0]), "r"(wz[2][1]), "r"(wz[3][0]), "r"(wz[3][1]),
              "r"(wt[0]), "r"(wt[1]), "r"(va0), "r"(hm0), "r"(hm1), "r"(rl), "r"(rm), "r"(sel), "r"(pos), "n"(sb + SM_REC)
            : "memory");
            sts32_if(true, sb + SM_ZERO + 96, lp);
            const uint2 left = lds64(sb + SM_MISC + 8);
            if (__builtin_expect(!(left.x | left.y), 1)) break;
            if (!next_excess(scr, x, va0)) break;
            lp = sb + SM_SRC + wl * 128 + (sel & 1);
        }
    }
    STAMP(7);
    const uint32_t grp = lds32(sb + SM_MISC + 64 + wl * 4);

    uint32_t aq[3][8][4];
    auto pack = [&](int j) {
#pragma unroll
        for (int m = 0; m < 8; m++) {
            if (j < 2) {
#pragma unroll
                for (int q = 0; q < 4; q++) {
                    const float* a = acc[16 * j + 2 * m + (q >> 1)] + (q & 1) * 2;
                    asm volatile("cvt.rn.bf16x2.f32 %0, %1, %2;" : "=r"(aq[j][m][q]) : "f"(a[~m & 1]), "f"(a[m & 1]));
                }
            } else {
                aq[2][m][0] = movm(pack_bf16(acc[32 + m][0], acc[32 + m][1]));
                aq[2][m][2] = movm(pack_bf16(acc[32 + m][2], acc[32 + m][3]));
                if (m & 1) {
                    aq[2][m][0] = __byte_perm(aq[2][m][0], 0, 0x1032);
                    aq[2][m][2] = __byte_perm(aq[2][m][2], 0, 0x1032);
                }
                aq[2][m][1] = aq[2][m][3] = 0;
#pragma unroll
                for (int q = 0; q < 4; q++) asm volatile("" : "+r"(aq[2][m][q]));
            }
        }
    };
    pack(0);
    STAMP(16);
    mbar_wait(bar_w, 0);
    STAMP(17);
    const uint4 ws0 = lds128(sb + SM_MISC + 32), ws1 = lds128(sb + SM_MISC + 48);
    const uint32_t ws[8] = {ws0.x, ws0.y, ws0.z, ws0.w, ws1.x, ws1.y, ws1.z, ws1.w};
    const uint64_t wdesc = ((sb + SM_RING) >> 4) | ((uint64_t)(2 * RSTR >> 4) << 16) | ((uint64_t)(RSTR >> 4) << 32) | (1ull << 62);
    const int nloc = min(npc, N - cta * npc);
    uint32_t ln;
    asm volatile("mov.u32 %0, %laneid;" : "=r"(ln));
    const bool odd = ln & 1;
    const int hi = ln >> 1 & 1;
    uint2* op = reinterpret_cast<uint2*>(out) + (size_t)(cta * npc) * 128 + (ln >> 2) + (ln & 1) * 8;
    float d[2][32];
    auto mix = [&](int job) {
        asm volatile("wgmma.fence.sync.aligned;" ::: "memory");
#pragma unroll
        for (int m = 0; m < 8; m++) wgmma_n64(d[job & 1], aq[job >> 1][m], wdesc + ws[m] + (job & 1) * (2 * RSTR >> 4), m);
        asm volatile("wgmma.commit_group.sync.aligned;" ::: "memory");
    };
    mix(0);
    if (nloc > NCTA) __trap();
    pack(1);
    pack(2);
#pragma unroll
    for (int job = 0; job < 6; job++) {
        if (nloc + 2 * job + 1 > NCTA) __trap();
        asm volatile("wgmma.wait_group.sync.aligned 0;" ::: "memory");
        if (job == 0) STAMP(18);
        if (job == 4) STAMP(19);
        float (&dd)[32] = d[job & 1];
#pragma unroll
        for (int k = 0; k < 32; k++) asm volatile("" : "+f"(dd[k]));
        if (job < 5) mix(job + 1);
        if (job > 0 && nloc + 2 * job + 2 > NCTA) __trap();
#pragma unroll
        for (int h = 0; h < (job < 4 ? 2 : 1); h++) {
            const int gj = grp >> (5 * (job >> 1)) & 31;
            const int l = job < 4 ? gj * 4 + 2 * h + hi : gj * 2 + 32 + hi;
            const bool ok = l < nloc;
#pragma unroll
            for (int j = 0; j < 8; j += 2) {
                const uint32_t p0 = movm(pack_bf16(dd[4 * j + 2 * h], dd[4 * j + 2 * h + 1])), p1 = movm(pack_bf16(dd[4 * j + 4 + 2 * h], dd[4 * j + 5 + 2 * h]));
                const uint32_t rv = __shfl_xor_sync(0xffffffffu, odd ? p0 : p1, 1);
                if (ok) op[l * 128 + (job & 1) * 64 + j * 8] = odd ? make_uint2(rv, p1) : make_uint2(p0, rv);
            }
        }
    }
    __syncwarp();
    ANCHOR(1);
}

}

extern "C" void kernel_launch(void* const* d_in, const int* in_sizes, int n_in, void* d_out, int out_size) {
    const __nv_bfloat16* x     = (const __nv_bfloat16*)d_in[0];
    const int*           src   = (const int*)d_in[1];
    const int*           dst   = (const int*)d_in[2];
    const uint2*         Y     = (const uint2*)d_in[3];
    const uint2*         ef    = (const uint2*)d_in[4];
    const __nv_bfloat16* w_rad = (const __nv_bfloat16*)d_in[5];
    const __nv_bfloat16* cg    = (const __nv_bfloat16*)d_in[6];
    const __nv_bfloat16* w_mix = (const __nv_bfloat16*)d_in[7];
    __nv_bfloat16*       out   = (__nv_bfloat16*)d_out;
    const int N = in_sizes[0] / 512;
    const int E = in_sizes[1];

    static int n_sm = 0;
    static Scratch* scr = nullptr;
    static decltype(&cuTensorMapEncodeTiled) encode = nullptr;
    if (n_sm == 0) {
        cudaDriverEntryPointQueryResult qr;
        cudaGetDriverEntryPoint("cuTensorMapEncodeTiled", (void**)&encode, cudaEnableDefault, &qr);
        cudaGetSymbolAddress((void**)&scr, g_scr);
        int dev = 0;
        cudaGetDevice(&dev);
        cudaDeviceGetAttribute(&n_sm, cudaDevAttrMultiProcessorCount, dev);
        cudaFuncSetAttribute(tfn_kernel<1>, cudaFuncAttributeMaxDynamicSharedMemorySize, SM_TOTAL);
        cudaFuncSetAttribute(tfn_kernel<2>, cudaFuncAttributeMaxDynamicSharedMemorySize, SM_TOTAL);
        cudaFuncSetAttribute(tfn_kernel<3>, cudaFuncAttributeMaxDynamicSharedMemorySize, SM_TOTAL);
    }
    CUtensorMap xmap;
    {
        const cuuint64_t dims[2] = {64, (cuuint64_t)N * 8}, strides[1] = {128};
        const cuuint32_t box[2] = {64, 8}, es[2] = {1, 1};
        encode(&xmap, CU_TENSOR_MAP_DATA_TYPE_BFLOAT16, 2, (void*)x, dims, strides, box, es, CU_TENSOR_MAP_INTERLEAVE_NONE,
               CU_TENSOR_MAP_SWIZZLE_128B, CU_TENSOR_MAP_L2_PROMOTION_NONE, CU_TENSOR_MAP_FLOAT_OOB_FILL_NONE);
    }
    CUtensorMap wmap;
    {
        const cuuint64_t dims[5] = {128, 2, 4, 4, 4}, strides[4] = {256, 512, 2048, 8192};
        const cuuint32_t box[5] = {64, 1, 2, 1, 2}, es[5] = {1, 1, 1, 1, 1};
        encode(&wmap, CU_TENSOR_MAP_DATA_TYPE_BFLOAT16, 5, (void*)w_mix, dims, strides, box, es, CU_TENSOR_MAP_INTERLEAVE_NONE,
               CU_TENSOR_MAP_SWIZZLE_128B, CU_TENSOR_MAP_L2_PROMOTION_NONE, CU_TENSOR_MAP_FLOAT_OOB_FILL_NONE);
    }
    const int slice = ((E + NCTA - 1) / NCTA + 3) / 4 * 4;
    const int npc   = (N + NCTA - 1) / NCTA;
    const uint32_t npc_magic = (uint32_t)((0x100000000ull + npc - 1) / npc);
    const uint32_t bin_magic = (uint32_t)((1ull << 25) / N);
    const double want = PDT * (double)E / (32.0 * N);
    const uint32_t pace = (uint32_t)((want < 1 ? 1 : want > 127 ? 127 : want) * (1 << 25));
    cudaStream_t st = cudaStreamPerThread;
    if (n_sm >= NCTA) {
        tfn_kernel<3><<<NCTA, NT, SM_TOTAL, st>>>(dst, src, scr, E, slice, N, npc, npc_magic, bin_magic, Y, ef, w_rad, cg, x, w_mix, out, pace, xmap, wmap);
    } else {
        tfn_kernel<1><<<NCTA, NT, SM_TOTAL, st>>>(dst, src, scr, E, slice, N, npc, npc_magic, bin_magic, Y, ef, w_rad, cg, x, w_mix, out, pace, xmap, wmap);
        tfn_kernel<2><<<NCTA, NT, SM_TOTAL, st>>>(dst, src, scr, E, slice, N, npc, npc_magic, bin_magic, Y, ef, w_rad, cg, x, w_mix, out, pace, xmap, wmap);
    }
}
```

```cpp
#include <cuda.h>
#include <cuda_runtime.h>
#include <cuda_bf16.h>
#include <stdint.h>

namespace {

constexpr int NCTA   = 132;
constexpr int NW     = 8;
constexpr int NT     = 2 * NW * 32;
constexpr int RA     = 5;
constexpr int SLICE  = RA * NT;
constexpr int MBC    = 48;
constexpr int MBE    = MBC - 1;
constexpr int MBW    = NCTA * MBC;
constexpr int ASTR   = MBC + 4;
constexpr int NH     = NW * 32;
constexpr int RL     = 17;
constexpr int NG     = 24;
constexpr int KCAP   = 684;
constexpr int RCAP   = 2688;
constexpr int GK     = 48;
#define NBIN_ 128
constexpr int NBIN   = NBIN_;
constexpr int BSH    = NBIN == 256 ? 17 : 18;
constexpr int LBIN   = 128;
#define S_ 5
constexpr int S      = S_;
constexpr int SMG    = (65535 + S) / S;
constexpr int LCAP   = KCAP + NW + 4;

constexpr uint32_t sb = 1024;
constexpr int SM_RING = 0;
constexpr int RSTR    = NW * S * 1024 + 256;
constexpr int SM_REC  = SM_RING + 4 * RSTR - (S - 5) * 32768;
constexpr int SM_ZERO = SM_REC + RCAP * 16;
constexpr int SM_LIST = SM_ZERO + 128;
constexpr int SM_MISC = SM_LIST + LCAP * 16;
constexpr int SM_STATE = SM_MISC + 256;
constexpr int SM_BAR  = SM_STATE + 128;
constexpr int SM_SRC  = SM_BAR + NW * S * 8 + 96;
constexpr int SM_SEG  = SM_SRC + LCAP * 16;
constexpr int SM_TOTAL = SM_SEG + NCTA * 4;
constexpr int SM_AREC = SM_RING;
constexpr int SM_AP   = SM_AREC + (SLICE + 80) * 16;
constexpr int SM_AMB  = SM_AP + NH * 12;
constexpr int SM_AOFF = SM_AMB + (NCTA + 32) * ASTR * 4;
constexpr int SM_DUM  = SM_AOFF + 672;
constexpr int SM_BIN  = SM_DUM + NBIN * 4;
constexpr int SM_HIST = SM_BIN + NG * NBIN * 4;
constexpr int SM_KEY  = SM_HIST + 672;
constexpr int SM_LH   = SM_KEY + 128;
constexpr int SM_KSG  = SM_LH + NW * LBIN * 4;
constexpr int SM_CPY  = SM_KSG + NG * GK * 16;
constexpr int SM_DOFF = SM_CPY + NH * 16;
constexpr int SM_LT   = SM_DOFF + NH * 4;
constexpr int SM_RAWY = SM_REC;
constexpr int SM_RAWF = SM_RAWY + SLICE * 8;
static_assert(NW * (RL + 1) * MBC * 4 <= SM_AOFF - SM_AMB && SM_LT + 144 <= SM_REC && SM_RAWF + SLICE * 8 <= SM_ZERO, "temporaries must fit");
static_assert(SM_TOTAL <= 232448, "smem");
static_assert(SM_AMB % 128 == 0 && SM_LIST % 128 == 0 && SM_BAR % 128 == 0 && SM_HIST % 16 == 0 && SM_BIN % 16 == 0 && SM_MISC % 16 == 0 && SM_KSG % 16 == 0, "align");
static_assert(NCTA <= RL * NW && SM_SRC + NW * 128 - SM_REC < 65536 && LBIN == 128 && SM_SRC % 16 == 0 && SM_ZERO % 128 == 0, "layout");

struct Scratch {
    uint4    rec[NCTA * SLICE];
    uint32_t mb[NCTA * MBW];
    uint32_t ss[NCTA * SLICE];
    uint2    exc[NCTA * MBW];
    uint32_t epoch;
    uint32_t sent[2];
    uint32_t gap[61];
    uint32_t sent2[2][16];
};
__device__ __align__(128) Scratch g_scr;

#define STAMP(i)
#define STAMPT(i, th)
#define ANCHOR(i)

__device__ __forceinline__ uint32_t pack_bf16(float lo, float hi) {
    __nv_bfloat162 v = __floats2bfloat162_rn(lo, hi);
    return *reinterpret_cast<uint32_t*>(&v);
}
__device__ __forceinline__ uint4 lds128(uint32_t addr) {
    uint4 v;
    asm volatile("ld.shared.v4.u32 {%0,%1,%2,%3}, [%4];" : "=r"(v.x), "=r"(v.y), "=r"(v.z), "=r"(v.w) : "r"(addr) : "memory");
    return v;
}
__device__ __forceinline__ uint32_t movm(uint32_t v) {
    uint32_t r;
    asm volatile("movmatrix.sync.aligned.m8n8.trans.b16 %0, %1;" : "=r"(r) : "r"(v));
    return r;
}
__device__ __forceinline__ void cp16(uint32_t dst, const void* src) {
    asm volatile("cp.async.cg.shared.global [%0], [%1], 16;" ::"r"(dst), "l"(src) : "memory");
}
__device__ __forceinline__ uint4 ldg128_relaxed(const uint4* p) {
    uint4 v;
    asm volatile("ld.relaxed.gpu.global.v4.u32 {%0,%1,%2,%3}, [%4];" : "=r"(v.x), "=r"(v.y), "=r"(v.z), "=r"(v.w) : "l"(p) : "memory");
    return v;
}
__device__ __forceinline__ uint32_t atoms_inc(uint32_t addr) {
    uint32_t v;
    asm volatile("atom.shared.add.u32 %0, [%1], 1;" : "=r"(v) : "r"(addr) : "memory");
    return v;
}
__device__ __forceinline__ uint32_t lds32(uint32_t addr) {
    uint32_t v;
    asm volatile("ld.shared.u32 %0, [%1];" : "=r"(v) : "r"(addr) : "memory");
    return v;
}
__device__ __forceinline__ void sts32_if(bool p, uint32_t addr, uint32_t v) {
    asm volatile("{\n\t.reg .pred p;\n\tsetp.ne.u32 p, %2, 0;\n\t@p st.shared.u32 [%0], %1;\n\t}"
                 ::"r"(addr), "r"(v), "r"((uint32_t)p) : "memory");
}
__device__ __forceinline__ uint32_t lds32v(uint32_t addr) {
    uint32_t v;
    asm volatile("ld.volatile.shared.u32 %0, [%1];" : "=r"(v) : "r"(addr) : "memory");
    return v;
}
__device__ __forceinline__ uint32_t clock32() {
    uint32_t c;
    asm volatile("mov.u32 %0, %clock;" : "=r"(c));
    return c;
}
__device__ __forceinline__ uint32_t timer32() {
    uint32_t c;
    asm volatile("mov.u32 %0, %globaltimer_lo;" : "=r"(c));
    return c;
}
__device__ __forceinline__ uint32_t opaque(uint32_t v) {
    asm volatile("" : "+r"(v));
    return v;
}
__device__ __forceinline__ void mbar_wait(uint32_t bar, uint32_t parity) {
    asm volatile("{\n\t.reg .pred p;\n\t.reg .b32 n;\n\tmov.b32 n, 0;\n"
                 "AGAIN:\n\tmbarrier.try_wait.parity.shared::cta.b64 p, [%0], %1;\n\t@p bra.uni THERE;\n\t"
                 "add.u32 n, n, 1;\n\tsetp.lt.u32 p, n, 1048576;\n\t@p bra.uni AGAIN;\n"
                 "THERE:\n\t}" ::"r"(bar), "r"(parity) : "memory");
}
__device__ __forceinline__ void mbar_init(uint32_t bar, uint32_t count) {
    asm volatile("mbarrier.init.shared::cta.b64 [%0], %1;" ::"r"(bar), "r"(count) : "memory");
}
__device__ __forceinline__ uint32_t atoms_add(uint32_t addr, uint32_t x) {
    uint32_t v;
    asm volatile("atom.shared.add.u32 %0, [%1], %2;" : "=r"(v) : "r"(addr), "r"(x) : "memory");
    return v;
}
__device__ __forceinline__ uint2 lds64(uint32_t addr) {
    uint2 v;
    asm volatile("ld.shared.v2.u32 {%0,%1}, [%2];" : "=r"(v.x), "=r"(v.y) : "r"(addr) : "memory");
    return v;
}
__device__ __forceinline__ void sts128_if(bool p, uint32_t addr, uint4 v) {
    asm volatile("{\n\t.reg .pred p;\n\tsetp.ne.u32 p, %5, 0;\n\t@p st.shared.v4.u32 [%0], {%1,%2,%3,%4};\n\t}"
                 ::"r"(addr), "r"(v.x), "r"(v.y), "r"(v.z), "r"(v.w), "r"((uint32_t)p) : "memory");
}
__device__ __forceinline__ void scan_step(uint32_t& v, int o) {
    asm volatile("{\n\t.reg .pred p;\n\t.reg .b32 u;\n\tshfl.sync.up.b32 u|p, %0, %1, 0, 0xffffffff;\n\t@p add.u32 %0, %0, u;\n\t}" : "+r"(v) : "r"(o));
}
__device__ __forceinline__ uint32_t warp_incl_scan(uint32_t v) {
#pragma unroll
    for (int o = 1; o < 32; o <<= 1) scan_step(v, o);
    return v;
}
__device__ __forceinline__ void mma_k16v(float (&d)[4], uint32_t a0, uint32_t a1, uint32_t a2, uint32_t a3,
                                         uint32_t b0, uint32_t b1) {
    asm volatile("mma.sync.aligned.m16n8k16.row.col.f32.bf16.bf16.f32 {%0,%1,%2,%3}, {%4,%5,%6,%7}, {%8,%9}, {%0,%1,%2,%3};"
        : "+f"(d[0]), "+f"(d[1]), "+f"(d[2]), "+f"(d[3])
        : "r"(a0), "r"(a1), "r"(a2), "r"(a3), "r"(b0), "r"(b1));
}
__device__ __forceinline__ bool elect_one() {
    uint32_t ok;
    asm volatile("{\n\t.reg .pred p;\n\telect.sync _|p, 0xffffffff;\n\tselp.u32 %0, 1, 0, p;\n\t}" : "=r"(ok));
    return ok;
}
__host__ __device__ constexpr int chunk_of(int m, int g) {
    return ((m & 1) + (g & 2) + 2 * (m & 2)) * 8 + ((g ^ m) & 1) + ((m >> 2) & 1) * 2 + 4 * (((g >> 2) ^ (m >> 1)) & 1);
}
__device__ __forceinline__ uint4 lds128v(uint32_t addr) {
    uint4 v;
    asm volatile("ld.volatile.shared.v4.u32 {%0,%1,%2,%3}, [%4];" : "=r"(v.x), "=r"(v.y), "=r"(v.z), "=r"(v.w) : "r"(addr) : "memory");
    return v;
}
#define HM0(h) (0x10000u << (h))
#define MAIN_LOOP_PTX \
    "{\n" \
    ".reg .b32 v<16>, a<4>, u<4>, b<2>, c<2>, w<4>, ca0, ca1, na0, na1, ef, rx, ry, ex, ey, e0, e1, e3, gx, gy, cnt;\n" \
    ".reg .f32 z<16>, t<8>, y<4>, fz;\n" \
    ".reg .b16 h<2>;\n" \
    ".reg .pred pa, pr, p<2>, q<3>, s<2>;\n" \
    "mov.f32 fz, 0f00000000;\n" \
    "setp.ne.u32 pa, %175, 0; mov.b32 rx, 0; mov.b32 ry, 0;\n" \
    "ld.shared.v4.u32 {e0,e1,ex,e3}, [%160];\n" \
    "prmt.b32 ey, e0, e1, %176;\n" \
    "lop3.b32 u2, ey, 0xfff0, %174, 0xea; @pa ld.shared.v2.u32 {rx,ry}, [u2+%178];\n" \
    "and.b32 u2, ey, %172; setp.ne.u32 p0, u2, 0; and.b32 u2, ey, %173; setp.ne.u32 p1, u2, 0;\n" \
    "shr.u32 u2, ex, 16; add.u32 na0, %171, u2;\n" \
    "mma.sync.aligned.m16n8k8.row.col.f32.bf16.bf16.f32 {y0,y1,y2,y3}, {%169,%170}, {ry}, {fz,fz,fz,fz};\n" \
    "cvt.rn.bf16x2.f32 b0, y2, y0; cvt.rn.bf16x2.f32 b1, y3, y1;\n" \
    "selp.b32 a0, b0, 0, p0; selp.b32 a1, b0, 0, p1; selp.b32 a2, b1, 0, p0; selp.b32 a3, b1, 0, p1;\n" \
    "mma.sync.aligned.m16n8k8.row.col.f32.bf16.bf16.f32 {z0,z1,z2,z3}, {%161,%162}, {rx}, {fz,fz,fz,fz};\n" \
    "mma.sync.aligned.m16n8k8.row.col.f32.bf16.bf16.f32 {z4,z5,z6,z7}, {%163,%164}, {rx}, {fz,fz,fz,fz};\n" \
    "mma.sync.aligned.m16n8k8.row.col.f32.bf16.bf16.f32 {z8,z9,z10,z11}, {%165,%166}, {rx}, {fz,fz,fz,fz};\n" \
    "tanh.approx.f32 t0, z0; tanh.approx.f32 t1, z2;\n" \
    "fma.rn.f32 z0, z0, t0, z0; fma.rn.f32 z2, z2, t1, z2;\n" \
    "tanh.approx.f32 t2, z1; tanh.approx.f32 t3, z3;\n" \
    "fma.rn.f32 z1, z1, t2, z1; fma.rn.f32 z3, z3, t3, z3;\n" \
    "tanh.approx.f32 t4, z4; tanh.approx.f32 t5, z6;\n" \
    "fma.rn.f32 z4, z4, t4, z4; fma.rn.f32 z6, z6, t5, z6;\n" \
    "tanh.approx.f32 t6, z5; tanh.approx.f32 t7, z7;\n" \
    "ld.shared.v4.u32 {e0,e1,ex,e3}, [%160+16];\n" \
    "mov.u32 cnt, %%globaltimer_hi; st.shared.u32 [%177+32], cnt;\n" \
    "bra.uni SLOW;\n" \
    "S2:\n" \
    "add.u32 %160, %160, 16;\n" \
    "mov.b32 ca0, na0; xor.b32 ca1, na0, 32; mov.b32 ef, rx;\n" \
    "or.b32 c0, a0, a1; or.b32 c1, a2, a3;\n" \
    "prmt.b32 ey, e0, e1, %176;\n" \
    "and.b32 u2, ey, %172; setp.ne.u32 p0, u2, 0; and.b32 u2, ey, %173; setp.ne.u32 p1, u2, 0;\n" \
    "lop3.b32 u2, ey, 0xfff0, %174, 0xea; @pa ld.shared.v2.u32 {rx,ry}, [u2+%178];\n" \
    "tanh.approx.f32 t0, z8;\n" \
    "mov.b32 {h0,h1}, z0; mov.b32 u1, {h1,h1}; mul.bf16x2 w1, v1, u1;\n" \
    "fma.rn.f32 z5, z5, t6, z5;\n" \
    "ld.shared.v4.u32 {v12,v13,v14,v15}, [ca0+640];\n" \
    "tanh.approx.f32 t1, z10;\n" \
    "mov.b32 {h0,h1}, z0; mov.b32 u1, {h1,h1}; mul.bf16x2 w0, v0, u1;\n" \
    "mov.b32 {h0,h1}, z2; mov.b32 u1, {h1,h1}; mul.bf16x2 w3, v3, u1;\n" \
    "fma.rn.f32 z7, z7, t7, z7;\n" \
    "mov.b32 {h0,h1}, z2; mov.b32 u1, {h1,h1}; mul.bf16x2 w2, v2, u1;\n" \
    "tanh.approx.f32 t2, z9;\n" \
    "fma.rn.f32 z8, z8, t0, z8;\n" \
    "mma.sync.aligned.m16n8k16.row.col.f32.bf16.bf16.f32 {%128,%129,%130,%131}, {w0,w2,w1,w3}, {c0,c1}, {%128,%129,%130,%131};\n" \
    "ld.shared.v4.u32 {v0,v1,v2,v3}, [ca1+0];\n" \
    "mov.b32 {h0,h1}, z1; mov.b32 u1, {h1,h1}; mul.bf16x2 w1, v5, u1;\n" \
    "fma.rn.f32 z10, z10, t1, z10;\n" \
    "mov.b32 {h0,h1}, z3; mov.b32 u1, {h1,h1}; mul.bf16x2 w2, v6, u1;\n" \
    "mov.b32 {h0,h1}, z3; mov.b32 u1, {h1,h1}; mul.bf16x2 w3, v7, u1;\n" \
    "tanh.approx.f32 t3, z11;\n" \
    "mov.b32 {h0,h1}, z1; mov.b32 u1, {h1,h1}; mul.bf16x2 w0, v4, u1;\n" \
    "mma.sync.aligned.m16n8k16.row.col.f32.bf16.bf16.f32 {%132,%133,%134,%135}, {w0,w2,w1,w3}, {c0,c1}, {%132,%133,%134,%135};\n" \
    "mma.sync.aligned.m16n8k8.row.col.f32.bf16.bf16.f32 {z12,z13,z14,z15}, {%167,%168}, {ef}, {fz,fz,fz,fz};\n" \
    "tanh.approx.f32 t4, z12;\n" \
    "tanh.approx.f32 t5, z14;\n" \
    "ld.shared.v4.u32 {v4,v5,v6,v7}, [ca1+128];\n" \
    "mov.b32 {h0,h1}, z4; mov.b32 u1, {h1,h1}; mul.bf16x2 w0, v8, u1;\n" \
    "fma.rn.f32 z9, z9, t2, z9;\n" \
    "mov.b32 {h0,h1}, z6; mov.b32 u1, {h1,h1}; mul.bf16x2 w2, v10, u1;\n" \
    "mov.b32 {h0,h1}, z6; mov.b32 u1, {h1,h1}; mul.bf16x2 w3, v11, u1;\n" \
    "mov.b32 {h0,h1}, z4; mov.b32 u1, {h1,h1}; mul.bf16x2 w1, v9, u1;\n" \
    "fma.rn.f32 z11, z11, t3, z11;\n" \
    "mma.sync.aligned.m16n8k16.row.col.f32.bf16.bf16.f32 {%136,%137,%138,%139}, {w0,w2,w1,w3}, {c0,c1}, {%136,%137,%138,%139};\n" \
    "tanh.approx.f32 t6, z13;\n" \
    "fma.rn.f32 z12, z12, t4, z12;\n" \
    "mov.b32 {h0,h1}, z5; mov.b32 u1, {h1,h1}; mul.bf16x2 w0, v12, u1;\n" \
    "tanh.approx.f32 t7, z15;\n" \
    "fma.rn.f32 z14, z14, t5, z14;\n" \
    "ld.shared.v4.u32 {v8,v9,v10,v11}, [ca1+512];\n" \
    "mov.b32 {h0,h1}, z5; mov.b32 u1, {h1,h1}; mul.bf16x2 w1, v13, u1;\n" \
    "mov.b32 {h0,h1}, z7; mov.b32 u1, {h1,h1}; mul.bf16x2 w3, v15, u1;\n" \
    "mov.b32 {h0,h1}, z7; mov.b32 u1, {h1,h1}; mul.bf16x2 w2, v14, u1;\n" \
    "mma.sync.aligned.m16n8k16.row.col.f32.bf16.bf16.f32 {%140,%141,%142,%143}, {w0,w2,w1,w3}, {c0,c1}, {%140,%141,%142,%143};\n" \
    "shr.u32 u2, ex, 16; add.u32 na0, %171, u2;\n" \
    "mma.sync.aligned.m16n8k8.row.col.f32.bf16.bf16.f32 {z0,z1,z2,z3}, {%161,%162}, {rx}, {fz,fz,fz,fz};\n" \
    "tanh.approx.f32 t0, z0;\n" \
    "ld.shared.v4.u32 {v12,v13,v14,v15}, [ca1+640];\n" \
    "mov.b32 {h0,h1}, z8; mov.b32 u1, {h1,h1}; mul.bf16x2 w1, v1, u1;\n" \
    "fma.rn.f32 z15, z15, t7, z15;\n" \
    "fma.rn.f32 z13, z13, t6, z13;\n" \
    "mov.b32 {h0,h1}, z10; mov.b32 u1, {h1,h1}; mul.bf16x2 w3, v3, u1;\n" \
    "mov.b32 {h0,h1}, z8; mov.b32 u1, {h1,h1}; mul.bf16x2 w0, v0, u1;\n" \
    "tanh.approx.f32 t1, z2;\n" \
    "and.b32 u2, ex, 1; mbarrier.try_wait.parity.shared::cta.b64 pr, [e3], u2;\n" \
    "mov.b32 {h0,h1}, z10; mov.b32 u1, {h1,h1}; mul.bf16x2 w2, v2, u1;\n" \
    "mma.sync.aligned.m16n8k16.row.col.f32.bf16.bf16.f32 {%144,%145,%146,%147}, {w0,w2,w1,w3}, {c0,c1}, {%144,%145,%146,%147};\n" \
    "mov.b32 {h0,h1}, z9; mov.b32 u1, {h1,h1}; mul.bf16x2 w0, v4, u1;\n" \
    "tanh.approx.f32 t2, z1;\n" \
    "st.volatile.shared.u32 [%177], %160;\n" \
    "@pr ld.shared.v4.u32 {v0,v1,v2,v3}, [na0+0];\n" \
    "mov.b32 {h0,h1}, z9; mov.b32 u1, {h1,h1}; mul.bf16x2 w1, v5, u1;\n" \
    "fma.rn.f32 z0, z0, t0, z0;\n" \
    "tanh.approx.f32 t3, z3;\n" \
    "fma.rn.f32 z2, z2, t1, z2;\n" \
    "mov.b32 {h0,h1}, z11; mov.b32 u1, {h1,h1}; mul.bf16x2 w3, v7, u1;\n" \
    "mov.b32 {h0,h1}, z11; mov.b32 u1, {h1,h1}; mul.bf16x2 w2, v6, u1;\n" \
    "mma.sync.aligned.m16n8k16.row.col.f32.bf16.bf16.f32 {%148,%149,%150,%151}, {w0,w2,w1,w3}, {c0,c1}, {%148,%149,%150,%151};\n" \
    "mma.sync.aligned.m16n8k8.row.col.f32.bf16.bf16.f32 {z4,z5,z6,z7}, {%163,%164}, {rx}, {fz,fz,fz,fz};\n" \
    "tanh.approx.f32 t4, z4;\n" \
    "@pr ld.shared.v4.u32 {v4,v5,v6,v7}, [na0+128];\n" \
    "mov.b32 {h0,h1}, z12; mov.b32 u1, {h1,h1}; mul.bf16x2 w0, v8, u1;\n" \
    "tanh.approx.f32 t5, z6;\n" \
    "mov.b32 {h0,h1}, z12; mov.b32 u1, {h1,h1}; mul.bf16x2 w1, v9, u1;\n" \
    "fma.rn.f32 z1, z1, t2, z1;\n" \
    "mov.b32 {h0,h1}, z14; mov.b32 u1, {h1,h1}; mul.bf16x2 w3, v11, u1;\n" \
    "fma.rn.f32 z3, z3, t3, z3;\n" \
    "fma.rn.f32 z4, z4, t4, z4;\n" \
    "tanh.approx.f32 t6, z5;\n" \
    "mov.b32 {h0,h1}, z14; mov.b32 u1, {h1,h1}; mul.bf16x2 w2, v10, u1;\n" \
    "@pr ld.shared.v4.u32 {v8,v9,v10,v11}, [na0+512];\n" \
    "mma.sync.aligned.m16n8k16.row.col.f32.bf16.bf16.f32 {%152,%153,%154,%155}, {w0,w2,w1,w3}, {c0,c1}, {%152,%153,%154,%155};\n" \
    "mov.b32 {h0,h1}, z13; mov.b32 u1, {h1,h1}; mul.bf16x2 w0, v12, u1;\n" \
    "tanh.approx.f32 t7, z7;\n" \
    "mov.b32 {h0,h1}, z15; mov.b32 u1, {h1,h1}; mul.bf16x2 w3, v15, u1;\n" \
    "mov.b32 {h0,h1}, z13; mov.b32 u1, {h1,h1}; mul.bf16x2 w1, v13, u1;\n" \
    "fma.rn.f32 z6, z6, t5, z6;\n" \
    "mma.sync.aligned.m16n8k8.row.col.f32.bf16.bf16.f32 {y0,y1,y2,y3}, {%169,%170}, {ry}, {fz,fz,fz,fz};\n" \
    "mma.sync.aligned.m16n8k8.row.col.f32.bf16.bf16.f32 {z8,z9,z10,z11}, {%165,%166}, {rx}, {fz,fz,fz,fz};\n" \
    "and.b32 u2, ex, 14; setp.eq.and.u32 q0, u2, 2, pr; setp.eq.and.u32 q1, u2, 4, pr; setp.eq.and.u32 q2, u2, 8, pr;\n" \
    "mov.b32 {h0,h1}, z15; mov.b32 u1, {h1,h1}; mul.bf16x2 w2, v14, u1;\n" \
    "mma.sync.aligned.m16n8k16.row.col.f32.bf16.bf16.f32 {%156,%157,%158,%159}, {w0,w2,w1,w3}, {c0,c1}, {%156,%157,%158,%159};\n" \
    "ld.shared.v4.u32 {e0,e1,ex,e3}, [%160+16];\n" \
    "cvt.rn.bf16x2.f32 b0, y2, y0; cvt.rn.bf16x2.f32 b1, y3, y1;\n" \
    "selp.b32 a0, b0, 0, p0; selp.b32 a1, b0, 0, p1; selp.b32 a2, b1, 0, p0; selp.b32 a3, b1, 0, p1;\n" \
    "@q1 bra.uni S1;\n" \
    "@!q0 bra.uni D;\n" \
    "S0:\n" \
    "add.u32 %160, %160, 16;\n" \
    "mov.b32 ca0, na0; xor.b32 ca1, na0, 32; mov.b32 ef, rx;\n" \
    "prmt.b32 ey, e0, e1, %176;\n" \
    "and.b32 u2, ey, %172; setp.ne.u32 p0, u2, 0; and.b32 u2, ey, %173; setp.ne.u32 p1, u2, 0;\n" \
    "fma.rn.f32 z5, z5, t6, z5;\n" \
    "lop3.b32 u2, ey, 0xfff0, %174, 0xea; @pa ld.shared.v2.u32 {rx,ry}, [u2+%178];\n" \
    "mov.b32 {h0,h1}, z0; mov.b32 u1, {h1,h1}; mul.bf16x2 v0, v0, u1;\n" \
    "tanh.approx.f32 t0, z8;\n" \
    "tanh.approx.f32 t1, z10;\n" \
    "ld.shared.v4.u32 {v12,v13,v14,v15}, [ca0+640];\n" \
    "mov.b32 {h0,h1}, z0; mov.b32 u1, {h1,h1}; mul.bf16x2 v1, v1, u1;\n" \
    "mov.b32 {h0,h1}, z2; mov.b32 u1, {h1,h1}; mul.bf16x2 v2, v2, u1;\n" \
    "mma.sync.aligned.m16n8k16.row.col.f32.bf16.bf16.f32 {%0,%1,%2,%3}, {a0,a1,a2,a3}, {v0,v1}, {%0,%1,%2,%3};\n" \
    "fma.rn.f32 z7, z7, t7, z7;\n" \
    "mov.b32 {h0,h1}, z2; mov.b32 u1, {h1,h1}; mul.bf16x2 v3, v3, u1;\n" \
    "fma.rn.f32 z8, z8, t0, z8;\n" \
    "mma.sync.aligned.m16n8k16.row.col.f32.bf16.bf16.f32 {%4,%5,%6,%7}, {a0,a1,a2,a3}, {v2,v3}, {%4,%5,%6,%7};\n" \
    "ld.shared.v4.u32 {v0,v1,v2,v3}, [ca1+0];\n" \
    "tanh.approx.f32 t2, z9;\n" \
    "fma.rn.f32 z10, z10, t1, z10;\n" \
    "mov.b32 {h0,h1}, z1; mov.b32 u1, {h1,h1}; mul.bf16x2 v5, v5, u1;\n" \
    "mov.b32 {h0,h1}, z3; mov.b32 u1, {h1,h1}; mul.bf16x2 v6, v6, u1;\n" \
    "tanh.approx.f32 t3, z11;\n" \
    "mov.b32 {h0,h1}, z1; mov.b32 u1, {h1,h1}; mul.bf16x2 v4, v4, u1;\n" \
    "mma.sync.aligned.m16n8k16.row.col.f32.bf16.bf16.f32 {%8,%9,%10,%11}, {a0,a1,a2,a3}, {v4,v5}, {%8,%9,%10,%11};\n" \
    "mov.b32 {h0,h1}, z3; mov.b32 u1, {h1,h1}; mul.bf16x2 v7, v7, u1;\n" \
    "mma.sync.aligned.m16n8k16.row.col.f32.bf16.bf16.f32 {%12,%13,%14,%15}, {a0,a1,a2,a3}, {v6,v7}, {%12,%13,%14,%15};\n" \
    "ld.shared.v4.u32 {v4,v5,v6,v7}, [ca1+128];\n" \
    "mma.sync.aligned.m16n8k8.row.col.f32.bf16.bf16.f32 {z12,z13,z14,z15}, {%167,%168}, {ef}, {fz,fz,fz,fz};\n" \
    "tanh.approx.f32 t4, z12;\n" \
    "mov.b32 {h0,h1}, z6; mov.b32 u1, {h1,h1}; mul.bf16x2 v11, v11, u1;\n" \
    "mov.b32 {h0,h1}, z4; mov.b32 u1, {h1,h1}; mul.bf16x2 v8, v8, u1;\n" \
    "fma.rn.f32 z9, z9, t2, z9;\n" \
    "mov.b32 {h0,h1}, z4; mov.b32 u1, {h1,h1}; mul.bf16x2 v9, v9, u1;\n" \
    "mma.sync.aligned.m16n8k16.row.col.f32.bf16.bf16.f32 {%16,%17,%18,%19}, {a0,a1,a2,a3}, {v8,v9}, {%16,%17,%18,%19};\n" \
    "fma.rn.f32 z11, z11, t3, z11;\n" \
    "mov.b32 {h0,h1}, z6; mov.b32 u1, {h1,h1}; mul.bf16x2 v10, v10, u1;\n" \
    "mma.sync.aligned.m16n8k16.row.col.f32.bf16.bf16.f32 {%20,%21,%22,%23}, {a0,a1,a2,a3}, {v10,v11}, {%20,%21,%22,%23};\n" \
    "ld.shared.v4.u32 {v8,v9,v10,v11}, [ca1+512];\n" \
    "tanh.approx.f32 t5, z14;\n" \
    "mov.b32 {h0,h1}, z5; mov.b32 u1, {h1,h1}; mul.bf16x2 v12, v12, u1;\n" \
    "fma.rn.f32 z12, z12, t4, z12;\n" \
    "tanh.approx.f32 t6, z13;\n" \
    "mov.b32 {h0,h1}, z7; mov.b32 u1, {h1,h1}; mul.bf16x2 v15, v15, u1;\n" \
    "mov.b32 {h0,h1}, z7; mov.b32 u1, {h1,h1}; mul.bf16x2 v14, v14, u1;\n" \
    "tanh.approx.f32 t7, z15;\n" \
    "mma.sync.aligned.m16n8k8.row.col.f32.bf16.bf16.f32 {z0,z1,z2,z3}, {%161,%162}, {rx}, {fz,fz,fz,fz};\n" \
    "mov.b32 {h0,h1}, z5; mov.b32 u1, {h1,h1}; mul.bf16x2 v13, v13, u1;\n" \
    "mma.sync.aligned.m16n8k16.row.col.f32.bf16.bf16.f32 {%24,%25,%26,%27}, {a0,a1,a2,a3}, {v12,v13}, {%24,%25,%26,%27};\n" \
    "mma.sync.aligned.m16n8k16.row.col.f32.bf16.bf16.f32 {%28,%29,%30,%31}, {a0,a1,a2,a3}, {v14,v15}, {%28,%29,%30,%31};\n" \
    "fma.rn.f32 z14, z14, t5, z14;\n" \
    "ld.shared.v4.u32 {v12,v13,v14,v15}, [ca1+640];\n" \
    "tanh.approx.f32 t0, z0;\n" \
    "shr.u32 u2, ex, 16; add.u32 na0, %171, u2;\n" \
    "fma.rn.f32 z15, z15, t7, z15;\n" \
    "fma.rn.f32 z13, z13, t6, z13;\n" \
    "mov.b32 {h0,h1}, z10; mov.b32 u1, {h1,h1}; mul.bf16x2 v3, v3, u1;\n" \
    "mov.b32 {h0,h1}, z8; mov.b32 u1, {h1,h1}; mul.bf16x2 v0, v0, u1;\n" \
    "mov.b32 {h0,h1}, z8; mov.b32 u1, {h1,h1}; mul.bf16x2 v1, v1, u1;\n" \
    "mma.sync.aligned.m16n8k16.row.col.f32.bf16.bf16.f32 {%32,%33,%34,%35}, {a0,a1,a2,a3}, {v0,v1}, {%32,%33,%34,%35};\n" \
    "tanh.approx.f32 t1, z2;\n" \
    "mov.b32 {h0,h1}, z10; mov.b32 u1, {h1,h1}; mul.bf16x2 v2, v2, u1;\n" \
    "mma.sync.aligned.m16n8k16.row.col.f32.bf16.bf16.f32 {%36,%37,%38,%39}, {a0,a1,a2,a3}, {v2,v3}, {%36,%37,%38,%39};\n" \
    "and.b32 u2, ex, 1; mbarrier.try_wait.parity.shared::cta.b64 pr, [e3], u2;\n" \
    "st.volatile.shared.u32 [%177], %160;\n" \
    "@pr ld.shared.v4.u32 {v0,v1,v2,v3}, [na0+0];\n" \
    "fma.rn.f32 z0, z0, t0, z0;\n" \
    "tanh.approx.f32 t3, z3;\n" \
    "tanh.approx.f32 t2, z1;\n" \
    "fma.rn.f32 z2, z2, t1, z2;\n" \
    "mov.b32 {h0,h1}, z9; mov.b32 u1, {h1,h1}; mul.bf16x2 v4, v4, u1;\n" \
    "mov.b32 {h0,h1}, z9; mov.b32 u1, {h1,h1}; mul.bf16x2 v5, v5, u1;\n" \
    "mov.b32 {h0,h1}, z11; mov.b32 u1, {h1,h1}; mul.bf16x2 v6, v6, u1;\n" \
    "mma.sync.aligned.m16n8k16.row.col.f32.bf16.bf16.f32 {%40,%41,%42,%43}, {a0,a1,a2,a3}, {v4,v5}, {%40,%41,%42,%43};\n" \
    "mov.b32 {h0,h1}, z11; mov.b32 u1, {h1,h1}; mul.bf16x2 v7, v7, u1;\n" \
    "mma.sync.aligned.m16n8k16.row.col.f32.bf16.bf16.f32 {%44,%45,%46,%47}, {a0,a1,a2,a3}, {v6,v7}, {%44,%45,%46,%47};\n" \
    "mov.b32 {h0,h1}, z12; mov.b32 u1, {h1,h1}; mul.bf16x2 v8, v8, u1;\n" \
    "fma.rn.f32 z1, z1, t2, z1;\n" \
    "mma.sync.aligned.m16n8k8.row.col.f32.bf16.bf16.f32 {z4,z5,z6,z7}, {%163,%164}, {rx}, {fz,fz,fz,fz};\n" \
    "tanh.approx.f32 t4, z4;\n" \
    "@pr ld.shared.v4.u32 {v4,v5,v6,v7}, [na0+128];\n" \
    "tanh.approx.f32 t5, z6;\n" \
    "mov.b32 {h0,h1}, z12; mov.b32 u1, {h1,h1}; mul.bf16x2 v9, v9, u1;\n" \
    "mma.sync.aligned.m16n8k16.row.col.f32.bf16.bf16.f32 {%48,%49,%50,%51}, {a0,a1,a2,a3}, {v8,v9}, {%48,%49,%50,%51};\n" \
    "mov.b32 {h0,h1}, z14; mov.b32 u1, {h1,h1}; mul.bf16x2 v11, v11, u1;\n" \
    "fma.rn.f32 z3, z3, t3, z3;\n" \
    "mov.b32 {h0,h1}, z14; mov.b32 u1, {h1,h1}; mul.bf16x2 v10, v10, u1;\n" \
    "fma.rn.f32 z4, z4, t4, z4;\n" \
    "mma.sync.aligned.m16n8k16.row.col.f32.bf16.bf16.f32 {%52,%53,%54,%55}, {a0,a1,a2,a3}, {v10,v11}, {%52,%53,%54,%55};\n" \
    "@pr ld.shared.v4.u32 {v8,v9,v10,v11}, [na0+512];\n" \
    "mov.b32 {h0,h1}, z13; mov.b32 u1, {h1,h1}; mul.bf16x2 v12, v12, u1;\n" \
    "tanh.approx.f32 t6, z5;\n" \
    "mov.b32 {h0,h1}, z13; mov.b32 u1, {h1,h1}; mul.bf16x2 v13, v13, u1;\n" \
    "mma.sync.aligned.m16n8k16.row.col.f32.bf16.bf16.f32 {%56,%57,%58,%59}, {a0,a1,a2,a3}, {v12,v13}, {%56,%57,%58,%59};\n" \
    "fma.rn.f32 z6, z6, t5, z6;\n" \
    "mov.b32 {h0,h1}, z15; mov.b32 u1, {h1,h1}; mul.bf16x2 v15, v15, u1;\n" \
    "tanh.approx.f32 t7, z7;\n" \
    "mov.b32 {h0,h1}, z15; mov.b32 u1, {h1,h1}; mul.bf16x2 v14, v14, u1;\n" \
    "mma.sync.aligned.m16n8k16.row.col.f32.bf16.bf16.f32 {%60,%61,%62,%63}, {a0,a1,a2,a3}, {v14,v15}, {%60,%61,%62,%63};\n" \
    "mma.sync.aligned.m16n8k8.row.col.f32.bf16.bf16.f32 {z8,z9,z10,z11}, {%165,%166}, {rx}, {fz,fz,fz,fz};\n" \
    "mma.sync.aligned.m16n8k8.row.col.f32.bf16.bf16.f32 {y0,y1,y2,y3}, {%169,%170}, {ry}, {fz,fz,fz,fz};\n" \
    "and.b32 u2, ex, 14; setp.eq.and.u32 q0, u2, 2, pr; setp.eq.and.u32 q1, u2, 4, pr; setp.eq.and.u32 q2, u2, 8, pr;\n" \
    "ld.shared.v4.u32 {e0,e1,ex,e3}, [%160+16];\n" \
    "cvt.rn.bf16x2.f32 b0, y2, y0; cvt.rn.bf16x2.f32 b1, y3, y1;\n" \
    "selp.b32 a0, b0, 0, p0; selp.b32 a1, b0, 0, p1; selp.b32 a2, b1, 0, p0; selp.b32 a3, b1, 0, p1;\n" \
    "@!q1 bra.uni D;\n" \
    "S1:\n" \
    "add.u32 %160, %160, 16;\n" \
    "mov.b32 ca0, na0; xor.b32 ca1, na0, 32; mov.b32 ef, rx;\n" \
    "prmt.b32 ey, e0, e1, %176;\n" \
    "and.b32 u2, ey, %172; setp.ne.u32 p0, u2, 0; and.b32 u2, ey, %173; setp.ne.u32 p1, u2, 0;\n" \
    "fma.rn.f32 z5, z5, t6, z5;\n" \
    "lop3.b32 u2, ey, 0xfff0, %174, 0xea; @pa ld.shared.v2.u32 {rx,ry}, [u2+%178];\n" \
    "mov.b32 {h0,h1}, z0; mov.b32 u1, {h1,h1}; mul.bf16x2 v0, v0, u1;\n" \
    "tanh.approx.f32 t0, z8;\n" \
    "tanh.approx.f32 t1, z10;\n" \
    "ld.shared.v4.u32 {v12,v13,v14,v15}, [ca0+640];\n" \
    "mov.b32 {h0,h1}, z0; mov.b32 u1, {h1,h1}; mul.bf16x2 v1, v1, u1;\n" \
    "mov.b32 {h0,h1}, z2; mov.b32 u1, {h1,h1}; mul.bf16x2 v2, v2, u1;\n" \
    "mma.sync.aligned.m16n8k16.row.col.f32.bf16.bf16.f32 {%64,%65,%66,%67}, {a0,a1,a2,a3}, {v0,v1}, {%64,%65,%66,%67};\n" \
    "fma.rn.f32 z7, z7, t7, z7;\n" \
    "mov.b32 {h0,h1}, z2; mov.b32 u1, {h1,h1}; mul.bf16x2 v3, v3, u1;\n" \
    "fma.rn.f32 z8, z8, t0, z8;\n" \
    "mma.sync.aligned.m16n8k16.row.col.f32.bf16.bf16.f32 {%68,%69,%70,%71}, {a0,a1,a2,a3}, {v2,v3}, {%68,%69,%70,%71};\n" \
    "ld.shared.v4.u32 {v0,v1,v2,v3}, [ca1+0];\n" \
    "tanh.approx.f32 t2, z9;\n" \
    "fma.rn.f32 z10, z10, t1, z10;\n" \
    "mov.b32 {h0,h1}, z1; mov.b32 u1, {h1,h1}; mul.bf16x2 v5, v5, u1;\n" \
    "mov.b32 {h0,h1}, z3; mov.b32 u1, {h1,h1}; mul.bf16x2 v6, v6, u1;\n" \
    "tanh.approx.f32 t3, z11;\n" \
    "mov.b32 {h0,h1}, z1; mov.b32 u1, {h1,h1}; mul.bf16x2 v4, v4, u1;\n" \
    "mma.sync.aligned.m16n8k16.row.col.f32.bf16.bf16.f32 {%72,%73,%74,%75}, {a0,a1,a2,a3}, {v4,v5}, {%72,%73,%74,%75};\n" \
    "mov.b32 {h0,h1}, z3; mov.b32 u1, {h1,h1}; mul.bf16x2 v7, v7, u1;\n" \
    "mma.sync.aligned.m16n8k16.row.col.f32.bf16.bf16.f32 {%76,%77,%78,%79}, {a0,a1,a2,a3}, {v6,v7}, {%76,%77,%78,%79};\n" \
    "ld.shared.v4.u32 {v4,v5,v6,v7}, [ca1+128];\n" \
    "mma.sync.aligned.m16n8k8.row.col.f32.bf16.bf16.f32 {z12,z13,z14,z15}, {%167,%168}, {ef}, {fz,fz,fz,fz};\n" \
    "tanh.approx.f32 t4, z12;\n" \
    "mov.b32 {h0,h1}, z6; mov.b32 u1, {h1,h1}; mul.bf16x2 v11, v11, u1;\n" \
    "mov.b32 {h0,h1}, z4; mov.b32 u1, {h1,h1}; mul.bf16x2 v8, v8, u1;\n" \
    "fma.rn.f32 z9, z9, t2, z9;\n" \
    "mov.b32 {h0,h1}, z4; mov.b32 u1, {h1,h1}; mul.bf16x2 v9, v9, u1;\n" \
    "mma.sync.aligned.m16n8k16.row.col.f32.bf16.bf16.f32 {%80,%81,%82,%83}, {a0,a1,a2,a3}, {v8,v9}, {%80,%81,%82,%83};\n" \
    "fma.rn.f32 z11, z11, t3, z11;\n" \
    "mov.b32 {h0,h1}, z6; mov.b32 u1, {h1,h1}; mul.bf16x2 v10, v10, u1;\n" \
    "mma.sync.aligned.m16n8k16.row.col.f32.bf16.bf16.f32 {%84,%85,%86,%87}, {a0,a1,a2,a3}, {v10,v11}, {%84,%85,%86,%87};\n" \
    "ld.shared.v4.u32 {v8,v9,v10,v11}, [ca1+512];\n" \
    "tanh.approx.f32 t5, z14;\n" \
    "mov.b32 {h0,h1}, z5; mov.b32 u1, {h1,h1}; mul.bf16x2 v12, v12, u1;\n" \
    "fma.rn.f32 z12, z12, t4, z12;\n" \
    "tanh.approx.f32 t6, z13;\n" \
    "mov.b32 {h0,h1}, z7; mov.b32 u1, {h1,h1}; mul.bf16x2 v15, v15, u1;\n" \
    "mov.b32 {h0,h1}, z7; mov.b32 u1, {h1,h1}; mul.bf16x2 v14, v14, u1;\n" \
    "tanh.approx.f32 t7, z15;\n" \
    "mma.sync.aligned.m16n8k8.row.col.f32.bf16.bf16.f32 {z0,z1,z2,z3}, {%161,%162}, {rx}, {fz,fz,fz,fz};\n" \
    "mov.b32 {h0,h1}, z5; mov.b32 u1, {h1,h1}; mul.bf16x2 v13, v13, u1;\n" \
    "mma.sync.aligned.m16n8k16.row.col.f32.bf16.bf16.f32 {%88,%89,%90,%91}, {a0,a1,a2,a3}, {v12,v13}, {%88,%89,%90,%91};\n" \
    "mma.sync.aligned.m16n8k16.row.col.f32.bf16.bf16.f32 {%92,%93,%94,%95}, {a0,a1,a2,a3}, {v14,v15}, {%92,%93,%94,%95};\n" \
    "fma.rn.f32 z14, z14, t5, z14;\n" \
    "ld.shared.v4.u32 {v12,v13,v14,v15}, [ca1+640];\n" \
    "tanh.approx.f32 t0, z0;\n" \
    "shr.u32 u2, ex, 16; add.u32 na0, %171, u2;\n" \
    "fma.rn.f32 z15, z15, t7, z15;\n" \
    "fma.rn.f32 z13, z13, t6, z13;\n" \
    "mov.b32 {h0,h1}, z10; mov.b32 u1, {h1,h1}; mul.bf16x2 v3, v3, u1;\n" \
    "mov.b32 {h0,h1}, z8; mov.b32 u1, {h1,h1}; mul.bf16x2 v0, v0, u1;\n" \
    "mov.b32 {h0,h1}, z8; mov.b32 u1, {h1,h1}; mul.bf16x2 v1, v1, u1;\n" \
    "mma.sync.aligned.m16n8k16.row.col.f32.bf16.bf16.f32 {%96,%97,%98,%99}, {a0,a1,a2,a3}, {v0,v1}, {%96,%97,%98,%99};\n" \
    "tanh.approx.f32 t1, z2;\n" \
    "mov.b32 {h0,h1}, z10; mov.b32 u1, {h1,h1}; mul.bf16x2 v2, v2, u1;\n" \
    "mma.sync.aligned.m16n8k16.row.col.f32.bf16.bf16.f32 {%100,%101,%102,%103}, {a0,a1,a2,a3}, {v2,v3}, {%100,%101,%102,%103};\n" \
    "and.b32 u2, ex, 1; mbarrier.try_wait.parity.shared::cta.b64 pr, [e3], u2;\n" \
    "st.volatile.shared.u32 [%177], %160;\n" \
    "@pr ld.shared.v4.u32 {v0,v1,v2,v3}, [na0+0];\n" \
    "fma.rn.f32 z0, z0, t0, z0;\n" \
    "tanh.approx.f32 t3, z3;\n" \
    "tanh.approx.f32 t2, z1;\n" \
    "fma.rn.f32 z2, z2, t1, z2;\n" \
    "mov.b32 {h0,h1}, z9; mov.b32 u1, {h1,h1}; mul.bf16x2 v4, v4, u1;\n" \
    "mov.b32 {h0,h1}, z9; mov.b32 u1, {h1,h1}; mul.bf16x2 v5, v5, u1;\n" \
    "mov.b32 {h0,h1}, z11; mov.b32 u1, {h1,h1}; mul.bf16x2 v6, v6, u1;\n" \
    "mma.sync.aligned.m16n8k16.row.col.f32.bf16.bf16.f32 {%104,%105,%106,%107}, {a0,a1,a2,a3}, {v4,v5}, {%104,%105,%106,%107};\n" \
    "mov.b32 {h0,h1}, z11; mov.b32 u1, {h1,h1}; mul.bf16x2 v7, v7, u1;\n" \
    "mma.sync.aligned.m16n8k16.row.col.f32.bf16.bf16.f32 {%108,%109,%110,%111}, {a0,a1,a2,a3}, {v6,v7}, {%108,%109,%110,%111};\n" \
    "mov.b32 {h0,h1}, z12; mov.b32 u1, {h1,h1}; mul.bf16x2 v8, v8, u1;\n" \
    "fma.rn.f32 z1, z1, t2, z1;\n" \
    "mma.sync.aligned.m16n8k8.row.col.f32.bf16.bf16.f32 {z4,z5,z6,z7}, {%163,%164}, {rx}, {fz,fz,fz,fz};\n" \
    "tanh.approx.f32 t4, z4;\n" \
    "@pr ld.shared.v4.u32 {v4,v5,v6,v7}, [na0+128];\n" \
    "tanh.approx.f32 t5, z6;\n" \
    "mov.b32 {h0,h1}, z12; mov.b32 u1, {h1,h1}; mul.bf16x2 v9, v9, u1;\n" \
    "mma.sync.aligned.m16n8k16.row.col.f32.bf16.bf16.f32 {%112,%113,%114,%115}, {a0,a1,a2,a3}, {v8,v9}, {%112,%113,%114,%115};\n" \
    "mov.b32 {h0,h1}, z14; mov.b32 u1, {h1,h1}; mul.bf16x2 v11, v11, u1;\n" \
    "fma.rn.f32 z3, z3, t3, z3;\n" \
    "mov.b32 {h0,h1}, z14; mov.b32 u1, {h1,h1}; mul.bf16x2 v10, v10, u1;\n" \
    "fma.rn.f32 z4, z4, t4, z4;\n" \
    "mma.sync.aligned.m16n8k16.row.col.f32.bf16.bf16.f32 {%116,%117,%118,%119}, {a0,a1,a2,a3}, {v10,v11}, {%116,%117,%118,%119};\n" \
    "@pr ld.shared.v4.u32 {v8,v9,v10,v11}, [na0+512];\n" \
    "mov.b32 {h0,h1}, z13; mov.b32 u1, {h1,h1}; mul.bf16x2 v12, v12, u1;\n" \
    "tanh.approx.f32 t6, z5;\n" \
    "mov.b32 {h0,h1}, z13; mov.b32 u1, {h1,h1}; mul.bf16x2 v13, v13, u1;\n" \
    "mma.sync.aligned.m16n8k16.row.col.f32.bf16.bf16.f32 {%120,%121,%122,%123}, {a0,a1,a2,a3}, {v12,v13}, {%120,%121,%122,%123};\n" \
    "fma.rn.f32 z6, z6, t5, z6;\n" \
    "mov.b32 {h0,h1}, z15; mov.b32 u1, {h1,h1}; mul.bf16x2 v15, v15, u1;\n" \
    "tanh.approx.f32 t7, z7;\n" \
    "mov.b32 {h0,h1}, z15; mov.b32 u1, {h1,h1}; mul.bf16x2 v14, v14, u1;\n" \
    "mma.sync.aligned.m16n8k16.row.col.f32.bf16.bf16.f32 {%124,%125,%126,%127}, {a0,a1,a2,a3}, {v14,v15}, {%124,%125,%126,%127};\n" \
    "mma.sync.aligned.m16n8k8.row.col.f32.bf16.bf16.f32 {z8,z9,z10,z11}, {%165,%166}, {rx}, {fz,fz,fz,fz};\n" \
    "mma.sync.aligned.m16n8k8.row.col.f32.bf16.bf16.f32 {y0,y1,y2,y3}, {%169,%170}, {ry}, {fz,fz,fz,fz};\n" \
    "and.b32 u2, ex, 14; setp.eq.and.u32 q0, u2, 2, pr; setp.eq.and.u32 q1, u2, 4, pr; setp.eq.and.u32 q2, u2, 8, pr;\n" \
    "ld.shared.v4.u32 {e0,e1,ex,e3}, [%160+16];\n" \
    "cvt.rn.bf16x2.f32 b0, y2, y0; cvt.rn.bf16x2.f32 b1, y3, y1;\n" \
    "selp.b32 a0, b0, 0, p0; selp.b32 a1, b0, 0, p1; selp.b32 a2, b1, 0, p0; selp.b32 a3, b1, 0, p1;\n" \
    "D:\n" \
    "@q0 bra.uni S0;\n" \
    "@q2 bra.uni S2;\n" \
    "@q1 bra.uni S1;\n" \
    "SLOW:\n" \
    "ld.shared.v2.u32 {gx,gy}, [%160+8];\n" \
    "and.b32 u2, gx, 1; and.b32 gx, gx, 14; setp.eq.u32 q0, gx, 2; setp.eq.u32 q1, gx, 4; setp.eq.u32 q2, gx, 8;\n" \
    "setp.eq.u32 pr, gx, 0;\n" \
    "@pr bra.uni DONE;\n" \
    "XW:\n" \
    "mov.u32 cnt, %%globaltimer_hi; ld.shared.u32 gx, [%177+32]; sub.u32 cnt, cnt, gx;\n" \
    "mbarrier.try_wait.parity.shared::cta.b64 pr, [gy], u2;\n" \
    "setp.lt.and.u32 pr, cnt, 2, !pr;\n" \
    "@pr bra.uni XW;\n" \
    "ld.shared.v4.u32 {v0,v1,v2,v3}, [na0+0];\n" \
    "ld.shared.v4.u32 {v4,v5,v6,v7}, [na0+128];\n" \
    "ld.shared.v4.u32 {v8,v9,v10,v11}, [na0+512];\n" \
    "@q0 bra.uni S0;\n" \
    "@q1 bra.uni S1;\n" \
    "bra.uni S2;\n" \
    "DONE:\n" \
    "mov.b32 u2, z0; xor.b32 %160, %160, u2;\n" \
    "mov.b32 u2, z2; xor.b32 %160, %160, u2;\n" \
    "mov.b32 u2, z1; xor.b32 %160, %160, u2;\n" \
    "mov.b32 u2, z3; xor.b32 %160, %160, u2;\n" \
    "mov.b32 u2, z4; xor.b32 %160, %160, u2;\n" \
    "mov.b32 u2, z6; xor.b32 %160, %160, u2;\n" \
    "}\n" \
    ""
#define MAIN_LOOP_ACC(A) \
    "+f"(A[0][0]), "+f"(A[0][1]), "+f"(A[0][2]), "+f"(A[0][3]), "+f"(A[1][0]), "+f"(A[1][1]), "+f"(A[1][2]), "+f"(A[1][3]), \
    "+f"(A[2][0]), "+f"(A[2][1]), "+f"(A[2][2]), "+f"(A[2][3]), "+f"(A[3][0]), "+f"(A[3][1]), "+f"(A[3][2]), "+f"(A[3][3]), \
    "+f"(A[4][0]), "+f"(A[4][1]), "+f"(A[4][2]), "+f"(A[4][3]), "+f"(A[5][0]), "+f"(A[5][1]), "+f"(A[5][2]), "+f"(A[5][3]), \
    "+f"(A[6][0]), "+f"(A[6][1]), "+f"(A[6][2]), "+f"(A[6][3]), "+f"(A[7][0]), "+f"(A[7][1]), "+f"(A[7][2]), "+f"(A[7][3]), \
    "+f"(A[8][0]), "+f"(A[8][1]), "+f"(A[8][2]), "+f"(A[8][3]), "+f"(A[9][0]), "+f"(A[9][1]), "+f"(A[9][2]), "+f"(A[9][3]), \
    "+f"(A[10][0]), "+f"(A[10][1]), "+f"(A[10][2]), "+f"(A[10][3]), "+f"(A[11][0]), "+f"(A[11][1]), "+f"(A[11][2]), "+f"(A[11][3]), \
    "+f"(A[12][0]), "+f"(A[12][1]), "+f"(A[12][2]), "+f"(A[12][3]), "+f"(A[13][0]), "+f"(A[13][1]), "+f"(A[13][2]), "+f"(A[13][3]), \
    "+f"(A[14][0]), "+f"(A[14][1]), "+f"(A[14][2]), "+f"(A[14][3]), "+f"(A[15][0]), "+f"(A[15][1]), "+f"(A[15][2]), "+f"(A[15][3]), \
    "+f"(A[16][0]), "+f"(A[16][1]), "+f"(A[16][2]), "+f"(A[16][3]), "+f"(A[17][0]), "+f"(A[17][1]), "+f"(A[17][2]), "+f"(A[17][3]), \
    "+f"(A[18][0]), "+f"(A[18][1]), "+f"(A[18][2]), "+f"(A[18][3]), "+f"(A[19][0]), "+f"(A[19][1]), "+f"(A[19][2]), "+f"(A[19][3]), \
    "+f"(A[20][0]), "+f"(A[20][1]), "+f"(A[20][2]), "+f"(A[20][3]), "+f"(A[21][0]), "+f"(A[21][1]), "+f"(A[21][2]), "+f"(A[21][3]), \
    "+f"(A[22][0]), "+f"(A[22][1]), "+f"(A[22][2]), "+f"(A[22][3]), "+f"(A[23][0]), "+f"(A[23][1]), "+f"(A[23][2]), "+f"(A[23][3]), \
    "+f"(A[24][0]), "+f"(A[24][1]), "+f"(A[24][2]), "+f"(A[24][3]), "+f"(A[25][0]), "+f"(A[25][1]), "+f"(A[25][2]), "+f"(A[25][3]), \
    "+f"(A[26][0]), "+f"(A[26][1]), "+f"(A[26][2]), "+f"(A[26][3]), "+f"(A[27][0]), "+f"(A[27][1]), "+f"(A[27][2]), "+f"(A[27][3]), \
    "+f"(A[28][0]), "+f"(A[28][1]), "+f"(A[28][2]), "+f"(A[28][3]), "+f"(A[29][0]), "+f"(A[29][1]), "+f"(A[29][2]), "+f"(A[29][3]), \
    "+f"(A[30][0]), "+f"(A[30][1]), "+f"(A[30][2]), "+f"(A[30][3]), "+f"(A[31][0]), "+f"(A[31][1]), "+f"(A[31][2]), "+f"(A[31][3]), \
    "+f"(A[32][0]), "+f"(A[32][1]), "+f"(A[32][2]), "+f"(A[32][3]), "+f"(A[33][0]), "+f"(A[33][1]), "+f"(A[33][2]), "+f"(A[33][3]), \
    "+f"(A[34][0]), "+f"(A[34][1]), "+f"(A[34][2]), "+f"(A[34][3]), "+f"(A[35][0]), "+f"(A[35][1]), "+f"(A[35][2]), "+f"(A[35][3]), \
    "+f"(A[36][0]), "+f"(A[36][1]), "+f"(A[36][2]), "+f"(A[36][3]), "+f"(A[37][0]), "+f"(A[37][1]), "+f"(A[37][2]), "+f"(A[37][3]), \
    "+f"(A[38][0]), "+f"(A[38][1]), "+f"(A[38][2]), "+f"(A[38][3]), "+f"(A[39][0]), "+f"(A[39][1]), "+f"(A[39][2]), "+f"(A[39][3])
#define PRODUCER_PTX \
    "{\n" \
    ".reg .b32 r<4>, d, c, t, w, n, bb, dd, kw, cc; .reg .b64 a; .reg .pred p;\n" \
    "mov.b32 n, 0; mov.b32 r0, 0; mov.u32 cc, %%globaltimer_lo; sub.s32 cc, cc, %11;\n" \
    "bra.uni TURN;\n" \
    "TOP:\n" \
    "ld.shared.v4.u32 {r0,r1,r2,r3}, [%0+%16];\n" \
    "ld.shared.u16 t, [%0+72];\n" \
    "mov.u32 c, %%globaltimer_lo; sub.s32 c, c, %11; sub.s32 c, c, t; setp.ge.s32 p, c, 0;\n" \
    "@p bra.uni G;\n" \
    "T:\n" \
    "nanosleep.u32 64;\n" \
    "mov.u32 c, %%globaltimer_lo; sub.s32 c, c, %11; sub.s32 c, c, t; setp.lt.s32 p, c, 0;\n" \
    "@p bra.uni T;\n" \
    "G:\n" \
    "ld.volatile.shared.u32 w, [%9]; setp.lt.u32 p, w, %0;\n" \
    "@p bra.uni W;\n" \
    "mbarrier.arrive.expect_tx.shared::cta.b64 _, [bb], %12;\n" \
    "add.u32 d, dd, 0*%15;\n" \
    "cp.async.bulk.tensor.2d.shared::cluster.global.tile.mbarrier::complete_tx::bytes [d], [%4, {%5, r0}], [bb];\n" \
    "add.u32 d, dd, 1*%15;\n" \
    "cp.async.bulk.tensor.2d.shared::cluster.global.tile.mbarrier::complete_tx::bytes [d], [%4, {%6, r1}], [bb];\n" \
    "add.u32 d, dd, 2*%15;\n" \
    "cp.async.bulk.tensor.2d.shared::cluster.global.tile.mbarrier::complete_tx::bytes [d], [%4, {%7, r2}], [bb];\n" \
    "add.u32 d, dd, 3*%15;\n" \
    "cp.async.bulk.tensor.2d.shared::cluster.global.tile.mbarrier::complete_tx::bytes [d], [%4, {%8, r3}], [bb];\n" \
    "add.u32 %0, %0, 16; add.u32 bb, bb, 8; add.u32 dd, dd, 1024; setp.ne.u32 p, %0, kw;\n" \
    "@p bra.uni TOP;\n" \
    "TURN:\n" \
    "setp.ge.u32 p, %0, %10;\n" \
    "@p bra.uni END;\n" \
    "mov.b32 bb, %3; mov.b32 dd, %2; add.u32 kw, %0, 80; min.u32 kw, kw, %10;\n" \
    "shr.u32 c, r0, 3; add.u32 c, c, %17; setp.lt.u32 p, c, %1;\n" \
    "@p bra.uni TOP;\n" \
    "sub.s32 c, %14, %1; min.s32 c, c, %18; setp.gt.s32 p, c, 0; shl.b32 c, c, 10; mad.wide.u32 a, %1, 1024, %13;\n" \
    "@p cp.async.bulk.prefetch.L2.global [a], c;\n" \
    "add.u32 %1, %1, %19;\n" \
    "bra.uni TOP;\n" \
    "W:\n" \
    "add.u32 n, n, 1; setp.lt.u32 p, n, 0x1000000;\n" \
    "@p bra.uni G;\n" \
    "END:\n" \
    "}\n" \
    ""

__device__ __forceinline__ void wgmma_n64(float (&d)[32], const uint32_t (&a)[4], uint64_t desc, int acc) {
    asm volatile("{\n\t.reg .pred p;\n\tsetp.ne.u32 p, %37, 0;\n\t"
        "wgmma.mma_async.sync.aligned.m64n64k16.f32.bf16.bf16 {%0,%1,%2,%3,%4,%5,%6,%7,%8,%9,%10,%11,%12,%13,%14,%15,"
        "%16,%17,%18,%19,%20,%21,%22,%23,%24,%25,%26,%27,%28,%29,%30,%31}, {%32,%33,%34,%35}, %36, p, 1, 1, 1;\n\t}"
        : "+f"(d[0]), "+f"(d[1]), "+f"(d[2]), "+f"(d[3]), "+f"(d[4]), "+f"(d[5]), "+f"(d[6]), "+f"(d[7]),
          "+f"(d[8]), "+f"(d[9]), "+f"(d[10]), "+f"(d[11]), "+f"(d[12]), "+f"(d[13]), "+f"(d[14]), "+f"(d[15]),
          "+f"(d[16]), "+f"(d[17]), "+f"(d[18]), "+f"(d[19]), "+f"(d[20]), "+f"(d[21]), "+f"(d[22]), "+f"(d[23]),
          "+f"(d[24]), "+f"(d[25]), "+f"(d[26]), "+f"(d[27]), "+f"(d[28]), "+f"(d[29]), "+f"(d[30]), "+f"(d[31])
        : "r"(a[0]), "r"(a[1]), "r"(a[2]), "r"(a[3]), "l"(desc), "r"(acc));
}

#define YFQ 1
#define YFP 1
#define PW 0
#define WN 9
#define PLD 1
#define PSU 0
#define PT1 1020
#define PT0 1720
#define PDT 36.2
#define NSLEEP 64
#define PFA 1400
#define PFR 8
#define PF0 1
#define PF1 0
template <int ID, int COUNT> __device__ __forceinline__ void bar_sync() { asm volatile("bar.sync %0, %1;" ::"n"(ID), "n"(COUNT) : "memory"); }
template <int ID, int COUNT> __device__ __forceinline__ void bar_arrive() { asm volatile("bar.arrive %0, %1;" ::"n"(ID), "n"(COUNT) : "memory"); }
template <int BYTES>
__device__ __forceinline__ void fill(uint32_t addr, uint4 v, int tid) {
#pragma unroll
    for (int r = 0; r < (BYTES / 16 + NT - 1) / NT; r++)
        sts128_if((r + 1) * NT <= BYTES / 16 || r * NT + tid < BYTES / 16, addr + (r * NT + tid) * 16, v);
}

__device__ __forceinline__ uint32_t group_cap(uint32_t key, int lane) {
    return __reduce_add_sync(0xffffffffu, min(key >> 5, GK)) > KCAP ? KCAP / NG : lane < 16 ? GK : 128 - 2 * GK;
}
template <int NR>
__device__ __forceinline__ void build_list(uint4 lt, uint32_t len, int wl, int lane, int N, uint32_t bin_magic, uint32_t pace) {
    const uint32_t n0 = lt.x >> 5, n01 = n0 + (lt.y >> 5), lh = sb + SM_LH + wl * (LBIN * 4);
    const uint32_t o0 = (lt.x & 31) * GK, o1 = (lt.y & 31) * GK - n0, o2 = (lt.z & 31) * GK - n01;
    uint4 w[NR], e[NR];
    uint32_t p[NR], ba[NR];
#pragma unroll
    for (int j = 0; j < NR; j++) {
        const uint32_t i = j * 32 + lane;
        w[j] = lds128(sb + SM_KSG + (i + (i < n0 ? o0 : i < n01 ? o1 : o2)) * 16);
        e[j].z = i < n0 ? 2 : i < n01 ? 4 : 8;
    }
#pragma unroll
    for (int j = 0; j < NR; j++) {
        const uint32_t key = min(((w[j].x & 0x1fff8) + (w[j].y & 0x1fff8) + (w[j].z & 0x1fff8) + (w[j].w & 0x1fff8)) >> 2, N * 8 - 8);
        ba[j] = j * 32 + lane < len ? lh + (key * bin_magic >> 21) * 4 : sb + SM_DUM + lane * 4;
        e[j].z |= min(__umulhi(key, pace), 0xffff) & 0xfff0;
    }
#pragma unroll
    for (int j = 0; j < NR; j++) p[j] = atoms_inc(ba[j]);
    __syncwarp();
    const uint4 u = lds128(lh + lane * 16);
#pragma unroll
    for (int j = 0; j < NR; j++) {
        e[j].x = (__byte_perm(w[j].x, w[j].y, 0x7632) & 0xfff0fff0u) | 1u << (w[j].x & 3) | 0x10000u << (w[j].y & 3);
        e[j].y = (__byte_perm(w[j].z, w[j].w, 0x7632) & 0xfff0fff0u) | 1u << (w[j].z & 3) | 0x10000u << (w[j].w & 3);
        asm volatile("" : "+r"(e[j].x), "+r"(e[j].y), "+r"(e[j].z));
    }
    const uint32_t sum = u.x + u.y + u.z + u.w, ex = warp_incl_scan(sum) - sum;
    sts128_if(true, lh + lane * 16, make_uint4(ex, ex + u.x, ex + u.x + u.y, ex + u.x + u.y + u.z));
    __syncwarp();
#pragma unroll
    for (int j = 0; j < NR; j++) p[j] += lds32(ba[j]);
#pragma unroll
    for (int j = 0; j < NR; j++) {
        const uint32_t turn = (p[j] * SMG) >> 16, slot = p[j] - turn * S;
        sts128_if(p[j] < len, sb + SM_SRC + (lt.w + p[j]) * 16, make_uint4(w[j].x & 0x1fff8, w[j].y & 0x1fff8, w[j].z & 0x1fff8, w[j].w & 0x1fff8));
        sts128_if(p[j] < len, sb + SM_LIST + (lt.w + p[j]) * 16,
                  make_uint4(e[j].x, e[j].y, e[j].z | (turn & 1) | slot << 26, sb + SM_BAR + (wl * S + slot) * 8));
    }
}
__device__ __forceinline__ bool next_excess(const Scratch* scr, const __nv_bfloat16* x, uint32_t va0) {
    uint32_t tid, cta;
    asm volatile("mov.u32 %0, %tid.x;" : "=r"(tid));
    asm volatile("mov.u32 %0, %ctaid.x;" : "=r"(cta));
    const int lane = tid & 31, wl = tid >> 5;
    const uint32_t bar_w = sb + SM_BAR + NW * S * 8, own = sb + SM_SRC + wl * 128, st = sb + SM_STATE + wl * 16;
    const uint32_t grp = lds32(sb + SM_MISC + 64 + wl * 4);
    uint4 c = lds128(st);
    __syncwarp();
    for (; c.x <= NCTA; c.x++, c.y = 0) {
        if (c.y == 0 && c.z == 0)
            c.x += __reduce_min_sync(0xffffffffu, c.x + lane >= NCTA || (lds32(sb + SM_SEG + min(c.x + lane, NCTA - 1) * 4) >> 12) > MBE ? lane : 31);
        const uint32_t loc = lds32(sb + SM_SEG + min(c.x, NCTA - 1) * 4);
        const int n = c.x < NCTA ? (int)(loc >> 12) - MBE : lds32(sb + SM_MISC + 12);
        for (; (int)c.y < n; c.y += 32, c.z = 0) {
            uint2 u = make_uint2(0xffffffffu, c.x * SLICE + (loc & 0xfff) + MBE + c.y + lane);
            if ((int)c.y + lane < n) {
                if (c.x < NCTA) u.x = __ldcg(scr->ss + u.y);
                else u = __ldcg(scr->exc + cta * MBW + c.y + lane);
            }
            const uint32_t gw = (u.x >> 25 & 31) - 1, ja = gw == (grp & 31) ? 1 : gw == (grp >> 5 & 31) ? 2 : gw == grp >> 10 ? 3 : 0;
            const unsigned todo = __ballot_sync(0xffffffffu, ja) & ~c.z;
            if (!todo) continue;
            const uint32_t jf = __shfl_sync(0xffffffffu, ja, __ffs(todo) - 1);
            const unsigned m = todo & __ballot_sync(0xffffffffu, ja == jf);
            const uint32_t from = __fns(m, 0, (lane & 3) + 1);
            const bool pad = from > 31;
            c.z |= __reduce_or_sync(0xffffffffu, pad ? 0 : 1u << from);
            if (!(todo & ~c.z)) { c.y += 32; c.z = 0; }
            u.x = __shfl_sync(0xffffffffu, u.x, pad ? __ffs(m) - 1 : from);
            u.y = __shfl_sync(0xffffffffu, u.y, from);
            const uint32_t slot = (lds32(sb + SM_MISC + 32 + wl * 4) / 64 + 1) % S;
#pragma unroll 1
            for (int k = 0; k < 8; k++)
                cp16((va0 ^ (k & 4) * 8) + slot * 1024 + (k & 1) * 128 + (k & 2) * 256,
                     reinterpret_cast<const uint4*>(x) + (size_t)(u.x >> 3 & 0x3fff) * 64 + chunk_of(k, lane >> 2));
            mbar_wait(bar_w, 0);
            if (lane < 4) {
                if (!pad) cp16(own + 64 + lane * 16, scr->rec + u.y);
                asm volatile("st.shared.u16 [%0], %1;" ::"r"(own + lane * 2),
                             "h"((uint16_t)(((pad ? sb + SM_ZERO : own + 64 + lane * 16) - sb - SM_REC) | 1u << (u.x & 3))) : "memory");
                sts32_if(lane == 0, own + 8, 1u << jf | slot << 26);
                sts32_if(lane == 0, own + 12, bar_w);
                sts128_if(lane == 0, own + 16, make_uint4(0, 0, 0, bar_w));
                sts128_if(lane == 0, st, c);
            }
            asm volatile("cp.async.wait_all;" ::: "memory");
            __syncwarp();
            return true;
        }
    }
    return false;
}

template <int MODE>
__global__ void __launch_bounds__(NT, 1)
tfn_kernel(const int* __restrict__ dst, const int* __restrict__ src, Scratch* scr, int E, int slice,
           int N, int npc, uint32_t npc_magic, uint32_t bin_magic, const uint2* __restrict__ Y, const uint2* __restrict__ ef,
           const __nv_bfloat16* __restrict__ w_rad, const __nv_bfloat16* __restrict__ cg, const __nv_bfloat16* __restrict__ x,
           const __nv_bfloat16* __restrict__ w_mix, __nv_bfloat16* __restrict__ out, uint32_t pace,
           const __grid_constant__ CUtensorMap xmap, const __grid_constant__ CUtensorMap wmap) {
    extern __shared__ __align__(1024) uint8_t smem[];
    const int tid = threadIdx.x, lane = tid & 31, warp = __shfl_sync(0xffffffffu, tid >> 5, 0);
    const int cta = blockIdx.x;
    const uint32_t bar_w = sb + SM_BAR + NW * S * 8, bar_raw = bar_w + 8, bar_rec = bar_w + 16, bar_mb = bar_w + 24;
    auto prefetch_x = [&](int chunk) {
        const int row = (chunk * NCTA + cta) * PFR;
        if (row < N)
            asm volatile("cp.async.bulk.prefetch.L2.global [%0], %1;" ::"l"(x + (size_t)row * 512), "r"(min(PFR, N - row) * 1024));
    };
    const int g = lane >> 2, t = lane & 3;
    uint32_t wz[4][2], wt[2];
    auto weights = [&]() {
            const uint32_t* wr = reinterpret_cast<const uint32_t*>(w_rad) + (t & 1) * 128;
            const uint16_t* cp = reinterpret_cast<const uint16_t*>(cg) + (t >> 1) * 32 + (t & 1) * 8 + (g & 3);
            const __nv_bfloat162 half = __floats2bfloat162_rn(0.5f, 0.5f);
#pragma unroll
            for (int j = 0; j < 4; j++) {
                uint32_t u0 = __ldg(wr + chunk_of(2 * j + (t >> 1), g)), u1 = __ldg(wr + chunk_of(2 * j + (t >> 1), g) + 64);
                const __nv_bfloat162 h0 = __hmul2(*reinterpret_cast<__nv_bfloat162*>(&u0), half);
                const __nv_bfloat162 h1 = __hmul2(*reinterpret_cast<__nv_bfloat162*>(&u1), half);
                u0 = *reinterpret_cast<const uint32_t*>(&h0);
                u1 = *reinterpret_cast<const uint32_t*>(&h1);
                wz[j][0] = __byte_perm(u0, u1, 0x5410);
                wz[j][1] = __byte_perm(u0, u1, 0x7632);
            }
            wt[0] = __ldg(cp) | ((uint32_t)__ldg(cp + 4) << 16);
            wt[1] = __ldg(cp + 16) | ((uint32_t)__ldg(cp + 20) << 16);
            sts32_if((wz[0][0] ^ wz[0][1] ^ wz[1][0] ^ wz[1][1] ^ wz[2][0] ^ wz[2][1] ^ wz[3][0] ^ wz[3][1] ^ wt[0] ^ wt[1]) == 1,
                     sb + SM_ZERO + 96, 0);
    };

    const int e0 = cta * slice, ne = min(E - e0, slice);
    uint32_t a_d[RA], a_s[RA];
    uint32_t tag = 0;
    if (MODE & 1) {
        const int q = min(e0 / 4 + tid, (E - 1) >> 2), e = min(e0 + 4 * NT + tid, E - 1);
        const int4 d4 = __ldcs(reinterpret_cast<const int4*>(dst) + q);
        a_d[4] = __ldcs(dst + e);
        const int4 s4 = __ldcs(reinterpret_cast<const int4*>(src) + q);
        a_s[4] = __ldcs(src + e);
        a_d[0] = d4.x; a_d[1] = d4.y; a_d[2] = d4.z; a_d[3] = d4.w;
        a_s[0] = s4.x; a_s[1] = s4.y; a_s[2] = s4.z; a_s[3] = s4.w;
    }
    if (MODE == 3) asm volatile("ld.relaxed.gpu.global.u32 %0, [%1];" : "=r"(tag) : "l"(&scr->epoch) : "memory");
    auto load_raw = [&](int which) {
        const int bytes = max((ne + 1) >> 1, 0) * 16;
        asm volatile("mbarrier.arrive.expect_tx.shared::cta.b64 _, [%0], %1;" ::"r"(bar_raw), "r"(bytes) : "memory");
        if (bytes > 0)
            asm volatile("cp.async.bulk.shared::cluster.global.mbarrier::complete_tx::bytes [%0], [%1], %2, [%3];"
                         ::"r"(sb + SM_RAWY + which * SLICE * 8), "l"((which ? ef : Y) + e0), "r"(bytes), "r"(bar_raw) : "memory");
    };
    auto send = [&](bool p, uint32_t* gp, uint4 v) {
        asm volatile("{\n\t.reg .pred p;\n\tsetp.ne.u32 p, %5, 0;\n\t@p st.relaxed.gpu.global.v4.u32 [%0], {%1,%2,%3,%4};\n\t}"
                     ::"l"(gp), "r"(v.x), "r"(v.y), "r"(v.z), "r"(v.w), "r"((uint32_t)p) : "memory");
    };
    uint32_t mc[3];
    auto prewrite = [&](uint4 empty) {
#pragma unroll
        for (int r = 0; r < 3; r++) {
            const uint32_t i = r * NT + tid, c = i < 4 * NCTA ? i >> 2 : ((i - 4 * NCTA) * 10923) >> 16, j = i < 4 * NCTA ? (i & 3) + 2 : i - 4 * NCTA - c * 6 + 6;
            mc[r] = c << 8 | j;
            if (r > 0) send(c < NCTA && j >= 6, scr->mb + c * MBW + cta * MBC + j * 4, empty);
        }
    };
    if ((uint32_t)__cvta_generic_to_shared(smem) != sb) __trap();
    if (elect_one()) {
#pragma unroll
        for (int i = 0; i < S; i++)
            if (warp >= NW) mbar_init(sb + SM_BAR + ((warp - NW) * S + i) * 8, 1);
        if (warp == 0) {
            mbar_init(bar_w, NW);
            mbar_init(bar_raw, 2);
            mbar_init(bar_rec, NW);
            mbar_init(bar_mb, 1);
        }
        asm volatile("fence.mbarrier_init.release.cluster;" ::: "memory");
    }
    fill<SM_KSG - SM_BIN>(sb + SM_BIN, make_uint4(0, 0, 0, 0), tid);
    if (MODE & 1) {
        const uint32_t em = lane << (BSH + 2);
        const uint4 empty = make_uint4(em, em + (1 << BSH), em + (2 << BSH), em + (3 << BSH));
        if (PW == 0) prewrite(empty);
        fill<NCTA * ASTR * 4>(sb + SM_AMB, empty, tid);
    }
    sts32_if(tid < 32, sb + SM_AOFF + (NCTA + tid) * 4, SLICE);
    sts32_if(tid < 128, sb + SM_DUM + tid * 4, 0x10000);
    if (MODE & 2) {
        const uint32_t pad = RCAP << 20 | N << 3;
        fill<SM_BAR - SM_ZERO>(sb + SM_ZERO, make_uint4(0, 0, 0, 0), tid);
        fill<NG * GK * 16>(sb + SM_KSG, make_uint4(pad, pad, pad, pad), tid);
    }
    if ((MODE & 1) && PW == 1) {
        const uint32_t em = lane << (BSH + 2);
        prewrite(make_uint4(em, em + (1 << BSH), em + (2 << BSH), em + (3 << BSH)));
    }
    __syncthreads();
    if ((MODE & 1) && PW == 2) {
        const uint32_t em = lane << (BSH + 2);
        prewrite(make_uint4(em, em + (1 << BSH), em + (2 << BSH), em + (3 << BSH)));
    }
    STAMP(15);
    if (warp == 13 && (MODE & 2) && elect_one()) {
        asm volatile("cp.async.bulk.prefetch.L2.global [%0], 1024;" ::"l"(w_rad));
        asm volatile("cp.async.bulk.prefetch.L2.global [%0], 128;" ::"l"(cg));
        asm volatile("prefetch.tensormap [%0];" ::"l"(&xmap) : "memory");
        asm volatile("prefetch.tensormap [%0];" ::"l"(&wmap) : "memory");
        asm volatile("st.shared.u64 [%0], %1;" ::"r"(sb + SM_MISC + 24), "l"(&xmap) : "memory");
    }
    if (MODE & 1) {
        if (((YFP == 1 && warp == 14) || (YFQ == 1 && warp == 15)) && elect_one()) load_raw(warp & 1);
        const uint32_t z = lds32(sb + SM_KEY + lane * 4);
        tag = ((tag + z) & 1) + 1;
        const uint32_t tg = tag << 30;
        uint32_t cc[RA], rk[RA];
#pragma unroll
        for (int r = 0; r < RA; r++) {
            cc[r] = (r < 4 ? 4 * tid + r : 4 * NT + tid) < ne ? __umulhi(a_d[r], npc_magic + z) : NCTA + lane;
            rk[r] = atoms_inc(sb + SM_HIST + cc[r] * 4);
        }
        if (((YFP == 2 && warp == 14) || (YFQ == 2 && warp == 15)) && elect_one()) load_raw(warp & 1);
#pragma unroll
        for (int r = 0; r < RA; r++) {
            const uint32_t l = a_d[r] - cc[r] * npc;
            a_s[r] = (tg + ((l < 64 ? (l >> 2) + 1 : (l >> 1) - 15) << 25)) | ((a_s[r] * (bin_magic + z)) & ((NBIN - 1) << BSH)) | a_s[r] * (8 + z) | (l & (l < 64 ? 3 : 1));
            sts32_if(true, sb + SM_AMB + (cc[r] * ASTR + min(rk[r], MBE) + 1) * 4, a_s[r]);
        }
        STAMP(1);
        __syncthreads();
        STAMP(28);
        if (((YFP == 3 && warp == 4) || (YFQ == 3 && warp == 5)) && elect_one()) load_raw(warp & 1);
        uint32_t hh[3];
#pragma unroll
        for (int r = 1; r < 3; r++) hh[r] = lds32(sb + SM_HIST + min(mc[r] >> 8, NCTA + 33) * 4);
#pragma unroll
        for (int r = 0; r < 3; r++) {
            const uint32_t c = mc[r] >> 8, j = mc[r] & 15;
            const bool used = r == 0 || j < 6 || (c < NCTA && hh[r] >= (j & 14) * 4);
            if (r == 0 || __any_sync(0xffffffffu, used))
                send(used, scr->mb + c * MBW + cta * MBC + j * 4, lds128(sb + SM_AMB + min(c, NCTA) * (ASTR * 4) + j * 16));
        }
        if (warp >= 7) {
            const uint32_t c = (tid - 7 * 32) >> 1, h = !(tid & 1) && c < NCTA ? lds32(sb + SM_HIST + c * 4) : 0;
            uint4 v = lds128(sb + SM_AMB + c * (ASTR * 4) + (tid & 1) * 16);
            const uint32_t inc = warp_incl_scan(h);
            const uint32_t off = __shfl_sync(0xffffffffu, atoms_add(sb + SM_HIST + 135 * 4 + lane * 4, lane == 31 ? inc : 0), 31) + inc - h;
            if (!(tid & 1)) v.x = tg | h << 12 | off;
            send(c < NCTA, scr->mb + c * MBW + cta * MBC + (tid & 1) * 4, v);
            sts32_if(!(tid & 1) && c < NCTA, sb + SM_AOFF + c * 4, off);
        }
        STAMP(2);
        __syncthreads();
        if (MODE == 3 && tid == NT - 1) asm volatile("red.relaxed.gpu.global.add.u32 [%0], 1;" ::"l"(scr->sent + (tag & 1)) : "memory");
        if (((YFP == 4 && warp == 4) || (YFQ == 4 && warp == 5)) && elect_one()) load_raw(warp & 1);
        uint32_t ap[2 * RA];
#pragma unroll
        for (int r = 0; r < RA; r++) ap[r] = rk[r] + lds32(sb + SM_AOFF + cc[r] * 4);
        if (__builtin_expect(max(max(max(rk[0], rk[1]), max(rk[2], rk[3])), rk[4]) >= MBE, 0)) {
#pragma unroll
            for (int r = 0; r < RA; r++)
                if (rk[r] >= MBE && cc[r] < NCTA) __stcg(scr->ss + cta * SLICE + ap[r], a_s[r]);
            __threadfence();
        }
        if (warp >= NW) {
            asm volatile("st.shared.v2.u32 [%0], {%1, %2};" ::"r"(sb + SM_AP + (tid - NH) * 8), "r"(ap[0] | ap[1] << 16), "r"(ap[2] | ap[3] << 16) : "memory");
            sts32_if(true, sb + SM_AP + NH * 8 + (tid - NH) * 4, ap[4]);
            bar_arrive<1, NT>();
        } else {
            bar_sync<1, NT>();
            const uint2 u = lds64(sb + SM_AP + tid * 8);
            ap[5] = u.x & 0xffff; ap[6] = u.x >> 16; ap[7] = u.y & 0xffff; ap[8] = u.y >> 16;
            ap[9] = lds32(sb + SM_AP + NH * 8 + tid * 4);
            const bool sw = lane & 4;
            mbar_wait(bar_raw, 0);
            STAMP(10);
#pragma unroll
            for (int hh = 0; hh < 2; hh++) {
                const uint32_t a = sb + SM_RAWY + (hh * NH + tid) * 32 + (lane & 4) * 4, b = sb + SM_RAWY + (4 * NT + hh * NH + tid) * 8;
                const uint4 y0 = lds128(a), f0 = lds128(a + SLICE * 8), y1 = lds128(a ^ 16), f1 = lds128((a ^ 16) + SLICE * 8);
                const uint2 y2 = lds64(b), f2 = lds64(b + SLICE * 8);
                const uint32_t* q = ap + hh * RA;
                sts128_if(true, sb + SM_AREC + (sw ? q[2] : q[0]) * 16, make_uint4(f0.x, y0.x, f0.y, y0.y));
                sts128_if(true, sb + SM_AREC + (sw ? q[3] : q[1]) * 16, make_uint4(f0.z, y0.z, f0.w, y0.w));
                sts128_if(true, sb + SM_AREC + (sw ? q[0] : q[2]) * 16, make_uint4(f1.x, y1.x, f1.y, y1.y));
                sts128_if(true, sb + SM_AREC + (sw ? q[1] : q[3]) * 16, make_uint4(f1.z, y1.z, f1.w, y1.w));
                sts128_if(true, sb + SM_AREC + q[4] * 16, make_uint4(f2.x, y2.x, f2.y, y2.y));
            }
            asm volatile("fence.proxy.async.shared::cta;" ::: "memory");
            bar_sync<7, NH>();
            STAMP(25);
            if (MODE == 3 && warp == NW - 1) bar_sync<9, 64>();
            if (warp == NW - 1 && lane == 0 && ne > 0)
                asm volatile("cp.async.bulk.global.shared::cta.bulk_group [%0], [%1], %2;"
                             ::"l"(scr->rec + cta * SLICE), "r"(sb + SM_AREC), "r"(ne * 16) : "memory");
            if (MODE == 3) weights();
            if (warp == NW - 1) {
                asm volatile("cp.async.bulk.commit_group;" ::: "memory");
                asm volatile("cp.async.bulk.wait_group 0;" ::: "memory");
                STAMPT(26, NH - 32);
                if (MODE == 3) {
                    mbar_wait(bar_mb, 0);
                    if (lane == 0) {
                        const uint32_t now = timer32(), tm = lds32v(sb + SM_MISC + 20);
                        asm volatile("red.relaxed.gpu.global.max.u32 [%0], %1;" ::"l"(scr->sent2[tag & 1] + 8), "r"(max((tm ? tm : now) + PT0, now + PT1)) : "memory");
                        asm volatile("red.relaxed.gpu.global.or.b32 [%0], %1;" ::"l"(scr->sent2[tag & 1] + (cta & 7)), "r"(1u << (cta >> 3)) : "memory");
                    }
                    uint32_t v;
                    asm volatile("ld.relaxed.gpu.global.u32 %0, [%1];" : "=r"(v) : "l"(scr->sent2[tag & 1] + (lane & 15)) : "memory");
                    sts32_if(lane < NW, sb + SM_MISC + 96 + lane * 4, v);
                }
            }
        }
    } else {
        tag = 1;
    }
    if (!(MODE & 2)) return;
    const int wl = warp & (NW - 1);
    const uint32_t ring = sb + SM_RING + wl * (S * 1024);
    const uint32_t bars = sb + SM_BAR + wl * (S * 8);
    const uint32_t pos = bar_w + 32 + wl * 4;

    if (warp >= NW) {
        uint32_t ss[RL + 1], rk[RL + 1];
        const uint32_t sl = wl + 8 * lane, empty = lane << BSH;
        if (wl == 0) {
            if (elect_one()) {
                asm volatile("mbarrier.arrive.expect_tx.shared::cta.b64 _, [%0], %1;" ::"r"(bar_mb), "n"(MBW * 4) : "memory");
                asm volatile("{\n\t.reg .pred p;\n\t.reg .b32 n, v;\n\tmov.b32 n, 0;\n"
                             "AGAIN:\n\tld.relaxed.gpu.global.u32 v, [%4];\n\tadd.u32 n, n, 1;\n\tsetp.lt.u32 p, n, 1048576;\n\t"
                             "setp.lt.and.u32 p, v, %5, p;\n\t@p bra.uni AGAIN;\n\t"
                             "cp.async.bulk.shared::cluster.global.mbarrier::complete_tx::bytes [%0], [%1], %2, [%3];\n\t}"
                             ::"r"(sb + SM_AMB), "l"(scr->mb + cta * MBW + lds32v(sb + SM_ZERO)), "n"(MBW * 4), "r"(bar_mb),
                               "l"(scr->sent + (tag & 1)), "n"(MODE == 3 ? NCTA : 0) : "memory");
            }
            __syncwarp();
            STAMPT(11, NH);
            if (MODE == 3) bar_arrive<9, 64>();
            if (MODE != 3) sts32_if(true, sb + SM_MISC + 4, timer32() + PT0);
        }
        uint32_t loc, cnt, from, big;
        for (int guard = 0;; guard++) {
            mbar_wait(bar_mb, 0);
            STAMPT(3, NH);
            loc = lds32(sb + SM_AMB + min(sl, NCTA - 1) * (MBC * 4));
#pragma unroll
            for (int r = 0; r < RL; r++) ss[r] = lds32(sb + SM_AMB + ((wl + 8 * r) * MBC + lane + 1) * 4);
            if (MODE == 3) sts32_if(wl == NW - 1, sb + SM_MISC + 20, timer32());
            if (wl + 8 * (RL - 1) >= NCTA) ss[RL - 1] = empty;
            cnt = sl < NCTA ? loc >> 12 & 0xfff : 0;
            big = __ballot_sync(0xffffffffu, cnt > 32);
            from = __ffs((lane < 16 ? big : big & (big - 1)) | 1 << RL) - 1;
            cnt = min(cnt, __popc(big & ((1u << lane) - 1)) < 2 ? MBE : 32);
            ss[RL] = lds32(sb + SM_AMB + ((wl + 8 * from) * MBC + 33 + (lane & 15)) * 4);
            if (32 + (lane & 15) >= __shfl_sync(0xffffffffu, cnt, from)) ss[RL] = empty;
            uint32_t any = ~loc >> 30 & tag ? 0xffffffffu : 0, got[2] = {-cnt * tag, 0};
#pragma unroll
            for (int r = 0; r <= RL; r++) { any |= ss[r]; got[r & 1] += ss[r] >> 30; }
            if (!__reduce_add_sync(0xffffffffu, got[0] + got[1] + (any >> 30 & (3 - tag) ? 0x10000 : 0)) || guard == 1 << 20) break;
#pragma unroll 1
            for (int r = wl; r < NCTA; r += 8)
                if (lane < MBC / 4)
                    sts128_if(true, sb + SM_AMB + (r * MBC + lane * 4) * 4, ldg128_relaxed(reinterpret_cast<const uint4*>(scr->mb + cta * MBW + r * MBC) + lane));
            __syncwarp();
        }
        STAMPT(4, NH);
        auto bin_of = [&](uint32_t w) { return sb + SM_DUM + (w >> (BSH - 2) & (NBIN * 128 - 4)); };
#pragma unroll
        for (int r = 0; r <= RL; r++) rk[r] = atoms_add(bin_of(ss[r]), 4);
        STAMPT(5, NH);
        bar_sync<3, NH>();
        uint32_t dof;
        {
            constexpr int Q = NBIN / 128;
            const uint32_t a = sb + SM_BIN + wl * (NBIN * 12) + lane * (16 * Q), sw = Q == 2 ? (lane & 4) * 4 : 0;
            uint4 u[3][Q];
            uint32_t sum[3], s0[3];
#pragma unroll
            for (int j = 0; j < 3; j++) {
#pragma unroll
                for (int q = 0; q < Q; q++) u[j][q] = lds128(a + j * (NBIN * 4) + (sw ^ q * 16));
                s0[j] = sum[j] = u[j][0].x + u[j][0].y + u[j][0].z + u[j][0].w;
                if (Q == 2) sum[j] += u[j][1].x + u[j][1].y + u[j][1].z + u[j][1].w;
            }
            uint32_t i01 = sum[0] | sum[1] << 16, i2 = sum[2] | cnt << 16;
#pragma unroll
            for (int o = 1; o < 32; o <<= 1) {
                scan_step(i01, o);
                scan_step(i2, o);
            }
            dof = atoms_add(sb + SM_MISC - 124 + lane * 4, lane == 31 ? i2 >> 16 : 0);
            const uint32_t inc[3] = {i01 & 0xffff, i01 >> 16, i2 & 0xffff};
#pragma unroll
            for (int j = 0; j < 3; j++) {
#pragma unroll
                for (int q = 0; q < Q; q++) {
                    const uint32_t p = (3 * wl + j) * (GK * 16) + inc[j] - (q == 0 ? (sw ? s0[j] : sum[j]) : (sw ? sum[j] : sum[j] - s0[j]));
                    const uint4 v = u[j][q];
                    sts128_if(true, a + j * (NBIN * 4) + (sw ^ q * 16), make_uint4(p, p + v.x, p + v.x + v.y, p + v.x + v.y + v.z));
                }
                sts32_if(lane == 31, sb + SM_KEY + (3 * wl + j) * 4, (inc[j] + 12) >> 4 << 5 | (3 * wl + j));
            }
            dof = __shfl_sync(0xffffffffu, dof, 31) + (i2 >> 16) - cnt;
            sts32_if(sl < NCTA, sb + SM_SEG + sl * 4, loc & 0xffffff);
            sts32_if((loc >> 12 & 0xfff) > MBE, sb + SM_MISC + 8, 1);
            sts32_if(true, sb + SM_DOFF + (tid - NH) * 4, dof << 20);
            const uint64_t from = reinterpret_cast<uint64_t>(scr->rec + sl * SLICE + (loc & 0xfff));
            sts128_if(true, sb + SM_CPY + (tid - NH) * 16,
                      make_uint4((uint32_t)from, (uint32_t)(from >> 32), sb + SM_REC + dof * 16, min(cnt, RCAP - min(dof, RCAP)) * 16));
        }
        STAMPT(12, NH);
        bar_arrive<4, NT - 32>();
        bar_arrive<6, NH + 32>();
        bar_sync<3, NH>();
        const uint32_t key = lds32(sb + SM_KEY + lane * 4), nrec = lds32(sb + SM_MISC);
        uint32_t d20[RL + 3];
#pragma unroll
        for (int r = 0; r < RL; r += 4) {
            const uint4 v = lds128(sb + SM_DOFF + wl * 128 + r * 4);
            d20[r] = v.x; d20[r + 1] = v.y; d20[r + 2] = v.z; d20[r + 3] = v.w;
        }
#pragma unroll
        for (int r = 0; r <= RL; r++) {
            uint32_t v;
            asm volatile("{\n\t.reg .pred p;\n\tsetp.lt.u32 p, %2, 0x10000;\n\tmov.b32 %0, %2;\n\t@p ld.shared.u32 %0, [%1];\n\t}"
                         : "=&r"(v) : "r"(bin_of(ss[r])), "r"(rk[r]) : "memory");
            rk[r] += v;
        }
        d20[RL] = (__shfl_sync(0xffffffffu, dof, from) + 32 - (lane & 16)) << 20;
        const uint32_t cap = group_cap(key, lane);
        const uint32_t lim = __any_sync(0xffffffffu, (key >> 5) > cap || nrec > RCAP) ? 0 : 0x20000;
#pragma unroll
        for (int r = 0; r <= RL; r++) {
            uint32_t v;
            asm("lop3.b32 %0, %1, 0x1ffff, %2, 0xea;" : "=r"(v) : "r"(ss[r]), "r"(lane << 20));
            sts32_if(rk[r] < lim, sb + SM_KSG + rk[r], v + d20[r]);
        }
        if (__builtin_expect(lim == 0 || __popc(big) > 2, 0)) {
            auto excess = [&](uint32_t w, uint32_t gi) { __stcg(scr->exc + cta * MBW + atoms_inc(sb + SM_MISC + 12), make_uint2(w, gi)); };
            big &= big - 1;
#pragma unroll 1
            for (big &= big - 1; big; big &= big - 1) {
                const uint32_t r = __ffs(big) - 1, l = __shfl_sync(0xffffffffu, loc, r);
                if (32 + lane < min(l >> 12 & 0xfff, MBE)) {
                    uint32_t w;
                    int guard = 0;
                    do asm volatile("ld.relaxed.gpu.global.u32 %0, [%1];" : "=r"(w) : "l"(scr->mb + cta * MBW + (wl + 8 * r) * MBC + 33 + lane) : "memory");
                    while (w >> 30 != tag && ++guard < (1 << 20));
                    excess(w, (wl + 8 * r) * SLICE + (l & 0xfff) + 32 + lane);
                }
            }
            const uint32_t tmp = sb + SM_AMB + (wl * MBC + lane) * 4;
#pragma unroll 1
            for (int part = 0; part < (lim ? 0 : 3); part++) {
#pragma unroll
                for (int r = 0; r <= RL; r++)
                    if (r / 8 == part) {
                        sts32_if(true, tmp + (r & 7) * (16 * MBC * 4), ss[r]);
                        sts32_if(true, tmp + ((r & 7) * 2 + 1) * (8 * MBC * 4), rk[r]);
                    }
#pragma unroll 1
                for (int r = part * 8; r < min(part * 8 + 8, RL + 1); r++) {
                    const uint32_t w = lds32(tmp + (r & 7) * (16 * MBC * 4)), p = lds32(tmp + ((r & 7) * 2 + 1) * (8 * MBC * 4));
                    const uint32_t rnk = r < RL ? lane : 32 + (lane & 15), fr = r < RL ? r : from, gw = (w >> 25 & 31) - 1;
                    const uint32_t ri = __shfl_sync(0xffffffffu, dof, fr) + rnk, gi = __shfl_sync(0xffffffffu, loc & 0xfff, fr) + rnk;
                    const bool fits = p - gw * (GK * 16) < __shfl_sync(0xffffffffu, cap, gw) * 16;
                    if (p < 0x20000) {
                        sts32_if(fits, sb + SM_KSG + p, min(ri, RCAP) << 20 | (w & 0x1ffffu));
                        if (!fits || ri >= RCAP) excess(w, (wl + 8 * fr) * SLICE + gi);
                    }
                }
            }
        }
        STAMPT(13, NH);
        bar_sync<8, NH + 32>();
        STAMPT(31, NH);
        const uint4 lt = lds128(sb + SM_LT + wl * 16);
        const uint32_t lb = lt.w, len = (lt.x >> 5) + (lt.y >> 5) + (lt.z >> 5), le = lb + len;
        if (__builtin_expect(len <= 96, 1)) build_list<3>(lt, len, wl, lane, N, bin_magic, pace);
        else build_list<4>(lt, len, wl, lane, N, bin_magic, pace);
        STAMPT(27, NH);
        if (PSU) asm volatile("setmaxnreg.dec.sync.aligned.u32 24;");
        bar_arrive<2, NT>();
        const uint32_t z = lds32(sb + SM_ZERO + (lane & 3) * 4);
        const uint32_t bytes = opaque(4096 + z);
        const uint4 z0 = lds128v(sb + SM_ZERO);
        const uint2 tm = lds64(sb + SM_MISC + 24);
        bar_sync<5, NT>();
        STAMPT(6, NH);
        if (!PSU) asm volatile("setmaxnreg.dec.sync.aligned.u32 24;");
        if (elect_one()) {
            uint32_t ka = sb + SM_LIST + lb * 16 - 16 * (S - 1);
            if (wl < PF1) prefetch_x(PF0 + wl);
            int row = ((PF0 + PF1 + wl) * NCTA + cta) * PFR;
            asm volatile(PRODUCER_PTX : "+r"(ka), "+r"(row)
                : "r"(ring), "r"(bars), "l"((uint64_t)tm.y << 32 | tm.x),
                  "r"(z0.x), "r"(z0.y), "r"(z0.z), "r"(z0.w), "r"(pos), "r"(ka + len * 16), "r"(lds32v(sb + SM_MISC + 4)), "r"(bytes),
                  "l"(x), "r"(N), "n"(RSTR), "n"(SM_SRC - SM_LIST + 16 * (S - 1)), "n"(PFA), "n"(PFR), "n"(NW * NCTA * PFR) : "memory");
            const uint32_t d = ring + (len - ((len * SMG) >> 16) * S) * 1024;
            STAMPT(20, NW * 32);
            for (int guard = 0; lds32v(pos) + 16 * (S - 1) < sb + SM_LIST + le * 16 && guard < (1 << 20); guard++) __nanosleep(NSLEEP);
            asm volatile("mbarrier.arrive.expect_tx.shared::cta.b64 _, [%0], 4096;" ::"r"(bar_w) : "memory");
#pragma unroll
            for (uint32_t r = 0; r < 8; r++)
                asm volatile("cp.async.bulk.tensor.5d.shared::cluster.global.tile.mbarrier::complete_tx::bytes [%0], [%1, {%2, %3, %4, %5, %6}], [%7];"
                             ::"r"(d + (r >> 1) * RSTR + (r & 1) * 512), "l"(&wmap), "r"((r >> 2) * 64), "r"((r >> 1) & 1),
                               "r"((wl >> 1) & 2), "r"(((r ^ (wl >> 1)) & 1) + (wl & 1) * 2), "r"(wl & 2), "r"(bar_w) : "memory");
            STAMPT(21, NW * 32);
        }
        return;
    }

    {
        if (MODE == 2) weights();
        if (warp == NW - 1) bar_sync<6, NH + 32>();
        else bar_sync<4, NT - 32>();
        if (warp == 0) {
            const uint32_t key = lds32(sb + SM_KEY + lane * 4);
            int rank = 0;
#pragma unroll
            for (int j = 0; j < 4; j++) {
                const uint4 o = lds128(sb + SM_KEY + (lane & 16) * 4 + j * 16);
                rank += ((key - o.x) >> 31) + ((key - o.y) >> 31) + ((key - o.z) >> 31) + ((key - o.w) >> 31);
            }
            const int n2 = 2 * __popc(__ballot_sync(0xffffffffu, key < 32) & 0xff0000);
            const int other = (rank < n2 ? n2 - 1 : 15 + n2) - rank;
            const int li = lane >= 16 ? 7 - rank : min(rank, other) - (rank < n2 ? 0 : n2 / 2);
            sts32_if(lane < NG, sb + SM_LT + (li < 4 ? li : 11 - li) * 16 + (lane >= 16 ? 8 : rank < other ? 0 : 4), min(key >> 5, group_cap(key, lane)) << 5 | lane);
            __syncwarp();
            const uint4 lt = lds128(sb + SM_LT + (lane & 7) * 16);
            const uint32_t len = (lt.x >> 5) + (lt.y >> 5) + (lt.z >> 5);
            uint32_t le = len + 1;
#pragma unroll
            for (int o = 1; o < 8; o <<= 1) scan_step(le, o);
            le -= 1;
            sts32_if(lane < NW, sb + SM_LT + lane * 16 + 12, le - len);
            bar_arrive<8, NH + 32>();
            if (lane < NW) {
                sts32_if(true, sb + SM_LIST + le * 16 + 12, bar_rec);
                sts32_if(true, bar_w + 32 + lane * 4, sb + SM_LIST + (le - len) * 16);
                sts32_if(true, sb + SM_MISC + 32 + lane * 4, (lane * S + len - ((len * SMG) >> 16) * S) * 64);
                sts32_if(true, sb + SM_MISC + 64 + lane * 4, (lt.x & 31) | (lt.y & 31) << 5 | (lt.z & 31) << 10);
            }
        }
        const uint4 cp = lds128(sb + SM_CPY + tid * 16);
        const uint32_t total = __reduce_add_sync(0xffffffffu, cp.w);
        if (MODE != 3 || warp != NW - 1) bar_arrive<5, NT>();
        if (lane == 0) asm volatile("mbarrier.arrive.expect_tx.shared::cta.b64 _, [%0], %1;" ::"r"(bar_rec), "r"(total) : "memory");
        if (warp >= 2 && warp < 2 + PF0 && lane == 0) prefetch_x(warp - 2);
        if (MODE == 3 && cta == 0 && tid == 64) {
            scr->epoch = tag;
            scr->sent[~tag & 1] = 0;
            for (int i = 0; i < 9; i++) scr->sent2[~tag & 1][i] = 0;
        }
        STAMP(22);
        const uint32_t all = (1u << (NCTA - wl + 7) / 8) - 1;
        uint32_t done = 0;
        bool watch = MODE == 3 && warp == NW - 1;
        for (int guard = 0; (done != all || watch) && guard < (1 << 22); guard++) {
            uint32_t m = all, v;
            if (watch) asm volatile("ld.relaxed.gpu.global.u32 %0, [%1];" : "=r"(v) : "l"(scr->sent2[tag & 1] + (lane & 15)) : "memory");
            if (MODE == 3) m = lds32v(sb + SM_MISC + 96 + wl * 4);
            if (m != done) {
                asm volatile("fence.proxy.async.global;" ::: "memory");
                uint32_t now = m & ~done;
                if (watch) now &= __ballot_sync(0xffffffffu, __popc(now & ((1u << lane) - 1)) < WN);
                if ((now >> lane & 1) && cp.w)
                    asm volatile("cp.async.bulk.shared::cluster.global.mbarrier::complete_tx::bytes [%0], [%1], %2, [%3];"
                                 ::"r"(cp.z), "l"((uint64_t)cp.y << 32 | cp.x), "r"(cp.w), "r"(bar_rec) : "memory");
                done |= now;
            } else if (!watch) {
                __nanosleep(20);
            }
            if (watch) {
                sts32_if(lane < NW, sb + SM_MISC + 96 + lane * 4, v);
                if (__all_sync(0xffffffffu, lane >= NW || v == (1u << (NCTA - lane + 7) / 8) - 1)) {
                    sts32_if(lane == NW, sb + SM_MISC + 4, v);
                    bar_arrive<5, NT>();
                    watch = false;
                    STAMPT(24, NH - 32);
                }
                __syncwarp();
            }
        }
        if (watch) bar_arrive<5, NT>();
        STAMP(23);
        if (tid == 0 && cta < 128) asm volatile("cp.async.bulk.prefetch.L2.global [%0], 256;" ::"l"(w_mix + cta * 128));
        bar_sync<2, NT>();
        asm volatile("setmaxnreg.inc.sync.aligned.u32 232;" ::: "memory");
        STAMP(14);
    }

    float acc[40][4];
    const uint32_t z = lds32(sb + SM_ZERO + t * 4);
#pragma unroll
    for (int j = 0; j < 40; j++) acc[j][0] = acc[j][1] = acc[j][2] = acc[j][3] = 0.f;
    const bool bact = (g & 1) == (t >> 1);
    mbar_wait(bar_rec, 0);
    STAMP(9);
    {
        auto keep = [&](uint32_t v) { return __shfl_sync(0xffffffffu, v + z, lane); };
        const uint32_t va0 = keep(ring + t * RSTR + (g & 2) * 128 + (g & 1) * 16 + ((((g >> 1) & 2) ^ ((((g >> 1) & 1) + t) & 3)) << 5));
        const uint32_t hm0 = keep(HM0(g >> 2)), hm1 = keep(0x40000u << (g >> 2)), sel = keep(0x1010u + (g >> 1) * 0x22 + t * 0x2200);
        const uint32_t rl = keep(bact ? (t & 1) * 8 : SM_ZERO - SM_REC), rm = keep(bact ? 0xfff0u : 0u);
        uint32_t lp = keep(lds32(pos));
        for (;;) {
        asm volatile(MAIN_LOOP_PTX : MAIN_LOOP_ACC(acc), "+r"(lp)
            : "r"(wz[0][0]), "r"(wz[0][1]), "r"(wz[1][0]), "r"(wz[1][1]), "r"(wz[2][0]), "r"(wz[2][1]), "r"(wz[3][0]), "r"(wz[3][1]),
              "r"(wt[0]), "r"(wt[1]), "r"(va0), "r"(hm0), "r"(hm1), "r"(rl), "r"(rm), "r"(sel), "r"(pos), "n"(sb + SM_REC)
            : "memory");
            sts32_if(true, sb + SM_ZERO + 96, lp);
            const uint2 left = lds64(sb + SM_MISC + 8);
            if (__builtin_expect(!(left.x | left.y), 1)) break;
            if (!next_excess(scr, x, va0)) break;
            lp = sb + SM_SRC + wl * 128 + (sel & 1);
        }
    }
    STAMP(7);
    const uint32_t grp = lds32(sb + SM_MISC + 64 + wl * 4);

    uint32_t aq[3][8][4];
    auto pack = [&](int j) {
#pragma unroll
        for (int m = 0; m < 8; m++) {
            if (j < 2) {
#pragma unroll
                for (int q = 0; q < 4; q++) {
                    const float* a = acc[16 * j + 2 * m + (q >> 1)] + (q & 1) * 2;
                    asm volatile("cvt.rn.bf16x2.f32 %0, %1, %2;" : "=r"(aq[j][m][q]) : "f"(a[~m & 1]), "f"(a[m & 1]));
                }
            } else {
                aq[2][m][0] = movm(pack_bf16(acc[32 + m][0], acc[32 + m][1]));
                aq[2][m][2] = movm(pack_bf16(acc[32 + m][2], acc[32 + m][3]));
                if (m & 1) {
                    aq[2][m][0] = __byte_perm(aq[2][m][0], 0, 0x1032);
                    aq[2][m][2] = __byte_perm(aq[2][m][2], 0, 0x1032);
                }
                aq[2][m][1] = aq[2][m][3] = 0;
#pragma unroll
                for (int q = 0; q < 4; q++) asm volatile("" : "+r"(aq[2][m][q]));
            }
        }
    };
    pack(0);
    STAMP(16);
    mbar_wait(bar_w, 0);
    STAMP(17);
    const uint4 ws0 = lds128(sb + SM_MISC + 32), ws1 = lds128(sb + SM_MISC + 48);
    const uint32_t ws[8] = {ws0.x, ws0.y, ws0.z, ws0.w, ws1.x, ws1.y, ws1.z, ws1.w};
    const uint64_t wdesc = ((sb + SM_RING) >> 4) | ((uint64_t)(2 * RSTR >> 4) << 16) | ((uint64_t)(RSTR >> 4) << 32) | (1ull << 62);
    const int nloc = min(npc, N - cta * npc);
    uint32_t ln;
    asm volatile("mov.u32 %0, %laneid;" : "=r"(ln));
    const bool odd = ln & 1;
    const int hi = ln >> 1 & 1;
    uint2* op = reinterpret_cast<uint2*>(out) + (size_t)(cta * npc) * 128 + (ln >> 2) + (ln & 1) * 8;
    float d[2][32];
    auto mix = [&](int job) {
        asm volatile("wgmma.fence.sync.aligned;" ::: "memory");
#pragma unroll
        for (int m = 0; m < 8; m++) wgmma_n64(d[job & 1], aq[job >> 1][m], wdesc + ws[m] + (job & 1) * (2 * RSTR >> 4), m);
        asm volatile("wgmma.commit_group.sync.aligned;" ::: "memory");
    };
    mix(0);
    if (nloc > NCTA) __trap();
    pack(1);
    pack(2);
#pragma unroll
    for (int job = 0; job < 6; job++) {
        if (nloc + 2 * job + 1 > NCTA) __trap();
        asm volatile("wgmma.wait_group.sync.aligned 0;" ::: "memory");
        if (job == 0) STAMP(18);
        if (job == 4) STAMP(19);
        float (&dd)[32] = d[job & 1];
#pragma unroll
        for (int k = 0; k < 32; k++) asm volatile("" : "+f"(dd[k]));
        if (job < 5) mix(job + 1);
        if (job > 0 && nloc + 2 * job + 2 > NCTA) __trap();
#pragma unroll
        for (int h = 0; h < (job < 4 ? 2 : 1); h++) {
            const int gj = grp >> (5 * (job >> 1)) & 31;
            const int l = job < 4 ? gj * 4 + 2 * h + hi : gj * 2 + 32 + hi;
            const bool ok = l < nloc;
#pragma unroll
            for (int j = 0; j < 8; j += 2) {
                const uint32_t p0 = movm(pack_bf16(dd[4 * j + 2 * h], dd[4 * j + 2 * h + 1])), p1 = movm(pack_bf16(dd[4 * j + 4 + 2 * h], dd[4 * j + 5 + 2 * h]));
                const uint32_t rv = __shfl_xor_sync(0xffffffffu, odd ? p0 : p1, 1);
                if (ok) op[l * 128 + (job & 1) * 64 + j * 8] = odd ? make_uint2(rv, p1) : make_uint2(p0, rv);
            }
        }
    }
    __syncwarp();
    ANCHOR(1);
}

}

extern "C" void kernel_launch(void* const* d_in, const int* in_sizes, int n_in, void* d_out, int out_size) {
    const __nv_bfloat16* x     = (const __nv_bfloat16*)d_in[0];
    const int*           src   = (const int*)d_in[1];
    const int*           dst   = (const int*)d_in[2];
    const uint2*         Y     = (const uint2*)d_in[3];
    const uint2*         ef    = (const uint2*)d_in[4];
    const __nv_bfloat16* w_rad = (const __nv_bfloat16*)d_in[5];
    const __nv_bfloat16* cg    = (const __nv_bfloat16*)d_in[6];
    const __nv_bfloat16* w_mix = (const __nv_bfloat16*)d_in[7];
    __nv_bfloat16*       out   = (__nv_bfloat16*)d_out;
    const int N = in_sizes[0] / 512;
    const int E = in_sizes[1];

    static int n_sm = 0;
    static Scratch* scr = nullptr;
    static decltype(&cuTensorMapEncodeTiled) encode = nullptr;
    if (n_sm == 0) {
        cudaDriverEntryPointQueryResult qr;
        cudaGetDriverEntryPoint("cuTensorMapEncodeTiled", (void**)&encode, cudaEnableDefault, &qr);
        cudaGetSymbolAddress((void**)&scr, g_scr);
        int dev = 0;
        cudaGetDevice(&dev);
        cudaDeviceGetAttribute(&n_sm, cudaDevAttrMultiProcessorCount, dev);
        cudaFuncSetAttribute(tfn_kernel<1>, cudaFuncAttributeMaxDynamicSharedMemorySize, SM_TOTAL);
        cudaFuncSetAttribute(tfn_kernel<2>, cudaFuncAttributeMaxDynamicSharedMemorySize, SM_TOTAL);
        cudaFuncSetAttribute(tfn_kernel<3>, cudaFuncAttributeMaxDynamicSharedMemorySize, SM_TOTAL);
    }
    CUtensorMap xmap;
    {
        const cuuint64_t dims[2] = {64, (cuuint64_t)N * 8}, strides[1] = {128};
        const cuuint32_t box[2] = {64, 8}, es[2] = {1, 1};
        encode(&xmap, CU_TENSOR_MAP_DATA_TYPE_BFLOAT16, 2, (void*)x, dims, strides, box, es, CU_TENSOR_MAP_INTERLEAVE_NONE,
               CU_TENSOR_MAP_SWIZZLE_128B, CU_TENSOR_MAP_L2_PROMOTION_NONE, CU_TENSOR_MAP_FLOAT_OOB_FILL_NONE);
    }
    CUtensorMap wmap;
    {
        const cuuint64_t dims[5] = {128, 2, 4, 4, 4}, strides[4] = {256, 512, 2048, 8192};
        const cuuint32_t box[5] = {64, 1, 2, 1, 2}, es[5] = {1, 1, 1, 1, 1};
        encode(&wmap, CU_TENSOR_MAP_DATA_TYPE_BFLOAT16, 5, (void*)w_mix, dims, strides, box, es, CU_TENSOR_MAP_INTERLEAVE_NONE,
               CU_TENSOR_MAP_SWIZZLE_128B, CU_TENSOR_MAP_L2_PROMOTION_NONE, CU_TENSOR_MAP_FLOAT_OOB_FILL_NONE);
    }
    const int slice = ((E + NCTA - 1) / NCTA + 3) / 4 * 4;
    const int npc   = (N + NCTA - 1) / NCTA;
    const uint32_t npc_magic = (uint32_t)((0x100000000ull + npc - 1) / npc);
    const uint32_t bin_magic = (uint32_t)((1ull << 25) / N);
    const double want = PDT * (double)E / (32.0 * N);
    const uint32_t pace = (uint32_t)((want < 1 ? 1 : want > 127 ? 127 : want) * (1 << 25));
    cudaStream_t st = cudaStreamPerThread;
    if (n_sm >= NCTA) {
        tfn_kernel<3><<<NCTA, NT, SM_TOTAL, st>>>(dst, src, scr, E, slice, N, npc, npc_magic, bin_magic, Y, ef, w_rad, cg, x, w_mix, out, pace, xmap, wmap);
    } else {
        tfn_kernel<1><<<NCTA, NT, SM_TOTAL, st>>>(dst, src, scr, E, slice, N, npc, npc_magic, bin_magic, Y, ef, w_rad, cg, x, w_mix, out, pace, xmap, wmap);
        tfn_kernel<2><<<NCTA, NT, SM_TOTAL, st>>>(dst, src, scr, E, slice, N, npc, npc_magic, bin_magic, Y, ef, w_rad, cg, x, w_mix, out, pace, xmap, wmap);
    }
}
```

```cpp
#include <cuda.h>
#include <cuda_runtime.h>
#include <cuda_bf16.h>
#include <stdint.h>

namespace {

constexpr int NCTA   = 132;
constexpr int NW     = 8;
constexpr int NT     = 2 * NW * 32;
constexpr int RA     = 5;
constexpr int SLICE  = RA * NT;
constexpr int MBC    = 48;
constexpr int MBE    = MBC - 1;
constexpr int MBW    = NCTA * MBC;
constexpr int ASTR   = MBC + 4;
constexpr int NH     = NW * 32;
constexpr int RL     = 17;
constexpr int NG     = 24;
constexpr int KCAP   = 676;
constexpr int RCAP   = 2752;
constexpr int GK     = 48;
constexpr int NBIN   = 128;
constexpr int BSH    = 18;
constexpr int LBIN   = 128;
#define S_ 5
constexpr int S      = S_;
constexpr int SMG    = (65535 + S) / S;
constexpr int LCAP   = KCAP + NW + 4;

constexpr uint32_t sb = 1024;
constexpr int SM_RING = 0;
constexpr int RSTR    = NW * S * 1024 + 256;
constexpr int SM_REC  = SM_RING + 4 * RSTR - (S - 5) * 32768;
constexpr int SM_ZERO = SM_REC + RCAP * 16;
constexpr int SM_LIST = SM_ZERO + 128;
constexpr int SM_MISC = SM_LIST + LCAP * 16;
constexpr int SM_STATE = SM_MISC + 256;
constexpr int SM_BAR  = SM_STATE + 128;
constexpr int SM_SRC  = SM_BAR + NW * S * 8 + 96;
constexpr int SM_SEG  = SM_SRC + LCAP * 16;
constexpr int SM_TOTAL = SM_SEG + NCTA * 4;
constexpr int SM_AREC = SM_RING;
constexpr int SM_AP   = SM_AREC + (SLICE + 80) * 16;
constexpr int SM_AMB  = SM_AP + NH * 12;
constexpr int SM_AOFF = SM_AMB + (NCTA + 32) * ASTR * 4;
constexpr int SM_DUM  = SM_AOFF + 672;
constexpr int SM_BIN  = SM_DUM + NBIN * 4;
constexpr int SM_HIST = SM_BIN + NG * NBIN * 4;
constexpr int SM_KEY  = SM_HIST + 672;
constexpr int SM_LH   = SM_KEY + 128;
constexpr int SM_KSG  = SM_LH + NW * LBIN * 4;
constexpr int SM_CPY  = SM_KSG + NG * GK * 16;
constexpr int SM_DOFF = SM_CPY + NH * 16;
constexpr int SM_LT   = SM_DOFF + NH * 4;
constexpr int SM_RAWY = SM_REC;
constexpr int SM_RAWF = SM_RAWY + SLICE * 8;
static_assert(NW * (RL + 1) * MBC * 4 <= SM_AOFF - SM_AMB && SM_LT + 384 <= SM_REC && SM_RAWF + SLICE * 8 <= SM_ZERO, "temporaries must fit");
static_assert(SM_TOTAL <= 232448, "smem");
static_assert(SM_AMB % 128 == 0 && SM_LIST % 128 == 0 && SM_BAR % 128 == 0 && SM_HIST % 16 == 0 && SM_BIN % 16 == 0 && SM_MISC % 16 == 0 && SM_KSG % 16 == 0, "align");
static_assert(NCTA % 6 == 0 && NCTA <= RL * NW && SM_SRC + NW * 96 - SM_REC < 65536 && LBIN == 128 && SM_SRC % 16 == 0 && SM_ZERO % 128 == 0, "layout");

struct Scratch {
    uint4    rec[NCTA * SLICE];
    uint32_t mb[NCTA * MBW];
    uint32_t ss[NCTA * SLICE];
    uint2    exc[NCTA * MBW];
    uint32_t epoch;
    uint32_t sent[2];
    uint32_t gap[61];
    uint32_t sent2[2][16];
};
__device__ __align__(128) Scratch g_scr;

#define STAMP(i)
#define STAMPT(i, th)
#define ANCHOR(i)

__device__ __forceinline__ uint32_t pack_bf16(float lo, float hi) {
    __nv_bfloat162 v = __floats2bfloat162_rn(lo, hi);
    return *reinterpret_cast<uint32_t*>(&v);
}
__device__ __forceinline__ uint4 lds128(uint32_t addr) {
    uint4 v;
    asm volatile("ld.shared.v4.u32 {%0,%1,%2,%3}, [%4];" : "=r"(v.x), "=r"(v.y), "=r"(v.z), "=r"(v.w) : "r"(addr) : "memory");
    return v;
}
__device__ __forceinline__ uint32_t movm(uint32_t v) {
    uint32_t r;
    asm volatile("movmatrix.sync.aligned.m8n8.trans.b16 %0, %1;" : "=r"(r) : "r"(v));
    return r;
}
__device__ __forceinline__ void cp16(uint32_t dst, const void* src) {
    asm volatile("cp.async.cg.shared.global [%0], [%1], 16;" ::"r"(dst), "l"(src) : "memory");
}
__device__ __forceinline__ uint4 ldg128_relaxed(const uint4* p) {
    uint4 v;
    asm volatile("ld.relaxed.gpu.global.v4.u32 {%0,%1,%2,%3}, [%4];" : "=r"(v.x), "=r"(v.y), "=r"(v.z), "=r"(v.w) : "l"(p) : "memory");
    return v;
}
__device__ __forceinline__ uint32_t atoms_inc(uint32_t addr) {
    uint32_t v;
    asm volatile("atom.shared.add.u32 %0, [%1], 1;" : "=r"(v) : "r"(addr) : "memory");
    return v;
}
__device__ __forceinline__ uint32_t lds32(uint32_t addr) {
    uint32_t v;
    asm volatile("ld.shared.u32 %0, [%1];" : "=r"(v) : "r"(addr) : "memory");
    return v;
}
__device__ __forceinline__ void sts32_if(bool p, uint32_t addr, uint32_t v) {
    asm volatile("{\n\t.reg .pred p;\n\tsetp.ne.u32 p, %2, 0;\n\t@p st.shared.u32 [%0], %1;\n\t}"
                 ::"r"(addr), "r"(v), "r"((uint32_t)p) : "memory");
}
__device__ __forceinline__ uint32_t lds32v(uint32_t addr) {
    uint32_t v;
    asm volatile("ld.volatile.shared.u32 %0, [%1];" : "=r"(v) : "r"(addr) : "memory");
    return v;
}
__device__ __forceinline__ uint32_t clock32() {
    uint32_t c;
    asm volatile("mov.u32 %0, %clock;" : "=r"(c));
    return c;
}
__device__ __forceinline__ uint32_t timer32() {
    uint32_t c;
    asm volatile("mov.u32 %0, %globaltimer_lo;" : "=r"(c));
    return c;
}
__device__ __forceinline__ uint32_t opaque(uint32_t v) {
    asm volatile("" : "+r"(v));
    return v;
}
__device__ __forceinline__ void mbar_wait(uint32_t bar, uint32_t parity) {
    asm volatile("{\n\t.reg .pred p;\n\t.reg .b32 n;\n\tmov.b32 n, 0;\n"
                 "AGAIN:\n\tmbarrier.try_wait.parity.shared::cta.b64 p, [%0], %1;\n\t@p bra.uni THERE;\n\t"
                 "add.u32 n, n, 1;\n\tsetp.lt.u32 p, n, 1048576;\n\t@p bra.uni AGAIN;\n"
                 "THERE:\n\t}" ::"r"(bar), "r"(parity) : "memory");
}
__device__ __forceinline__ void mbar_init(uint32_t bar, uint32_t count) {
    asm volatile("mbarrier.init.shared::cta.b64 [%0], %1;" ::"r"(bar), "r"(count) : "memory");
}
__device__ __forceinline__ uint32_t atoms_add(uint32_t addr, uint32_t x) {
    uint32_t v;
    asm volatile("atom.shared.add.u32 %0, [%1], %2;" : "=r"(v) : "r"(addr), "r"(x) : "memory");
    return v;
}
__device__ __forceinline__ uint2 lds64(uint32_t addr) {
    uint2 v;
    asm volatile("ld.shared.v2.u32 {%0,%1}, [%2];" : "=r"(v.x), "=r"(v.y) : "r"(addr) : "memory");
    return v;
}
__device__ __forceinline__ void sts128_if(bool p, uint32_t addr, uint4 v) {
    asm volatile("{\n\t.reg .pred p;\n\tsetp.ne.u32 p, %5, 0;\n\t@p st.shared.v4.u32 [%0], {%1,%2,%3,%4};\n\t}"
                 ::"r"(addr), "r"(v.x), "r"(v.y), "r"(v.z), "r"(v.w), "r"((uint32_t)p) : "memory");
}
__device__ __forceinline__ void scan_step(uint32_t& v, int o) {
    asm volatile("{\n\t.reg .pred p;\n\t.reg .b32 u;\n\tshfl.sync.up.b32 u|p, %0, %1, 0, 0xffffffff;\n\t@p add.u32 %0, %0, u;\n\t}" : "+r"(v) : "r"(o));
}
__device__ __forceinline__ uint32_t warp_incl_scan(uint32_t v) {
#pragma unroll
    for (int o = 1; o < 32; o <<= 1) scan_step(v, o);
    return v;
}
__device__ __forceinline__ void mma_k16v(float (&d)[4], uint32_t a0, uint32_t a1, uint32_t a2, uint32_t a3,
                                         uint32_t b0, uint32_t b1) {
    asm volatile("mma.sync.aligned.m16n8k16.row.col.f32.bf16.bf16.f32 {%0,%1,%2,%3}, {%4,%5,%6,%7}, {%8,%9}, {%0,%1,%2,%3};"
        : "+f"(d[0]), "+f"(d[1]), "+f"(d[2]), "+f"(d[3])
        : "r"(a0), "r"(a1), "r"(a2), "r"(a3), "r"(b0), "r"(b1));
}
__device__ __forceinline__ bool elect_one() {
    uint32_t ok;
    asm volatile("{\n\t.reg .pred p;\n\telect.sync _|p, 0xffffffff;\n\tselp.u32 %0, 1, 0, p;\n\t}" : "=r"(ok));
    return ok;
}
__host__ __device__ constexpr int chunk_of(int m, int g) {
    return ((m & 1) + (g & 2) + 2 * (m & 2)) * 8 + ((g ^ m) & 1) + ((m >> 2) & 1) * 2 + 4 * (((g >> 2) ^ (m >> 1)) & 1);
}
__device__ __forceinline__ uint4 lds128v(uint32_t addr) {
    uint4 v;
    asm volatile("ld.volatile.shared.v4.u32 {%0,%1,%2,%3}, [%4];" : "=r"(v.x), "=r"(v.y), "=r"(v.z), "=r"(v.w) : "r"(addr) : "memory");
    return v;
}
#define HM0(h) (0x10000u << (h))
#define MAIN_LOOP_PTX \
    "{\n" \
    ".reg .b32 v<16>, a<4>, u<4>, b<2>, c<2>, w<4>, ca0, ca1, na0, na1, ef, rx, ry, ex, ey, e0, e1, e3, gx, gy, cnt;\n" \
    ".reg .f32 z<16>, t<8>, y<4>, fz;\n" \
    ".reg .b16 h<2>;\n" \
    ".reg .pred pa, pr, p<2>, q<3>, s<2>;\n" \
    "mov.f32 fz, 0f00000000;\n" \
    "setp.ne.u32 pa, %175, 0; mov.b32 rx, 0; mov.b32 ry, 0;\n" \
    "ld.shared.v4.u32 {e0,e1,ex,e3}, [%160];\n" \
    "prmt.b32 ey, e0, e1, %176;\n" \
    "lop3.b32 u2, ey, 0xfff0, %174, 0xea; @pa ld.shared.v2.u32 {rx,ry}, [u2+%178];\n" \
    "and.b32 u2, ey, %172; setp.ne.u32 p0, u2, 0; and.b32 u2, ey, %173; setp.ne.u32 p1, u2, 0;\n" \
    "shr.u32 u2, ex, 16; add.u32 na0, %171, u2;\n" \
    "mma.sync.aligned.m16n8k8.row.col.f32.bf16.bf16.f32 {y0,y1,y2,y3}, {%169,%170}, {ry}, {fz,fz,fz,fz};\n" \
    "cvt.rn.bf16x2.f32 b0, y2, y0; cvt.rn.bf16x2.f32 b1, y3, y1;\n" \
    "selp.b32 a0, b0, 0, p0; selp.b32 a1, b0, 0, p1; selp.b32 a2, b1, 0, p0; selp.b32 a3, b1, 0, p1;\n" \
    "mma.sync.aligned.m16n8k8.row.col.f32.bf16.bf16.f32 {z0,z1,z2,z3}, {%161,%162}, {rx}, {fz,fz,fz,fz};\n" \
    "mma.sync.aligned.m16n8k8.row.col.f32.bf16.bf16.f32 {z4,z5,z6,z7}, {%163,%164}, {rx}, {fz,fz,fz,fz};\n" \
    "mma.sync.aligned.m16n8k8.row.col.f32.bf16.bf16.f32 {z8,z9,z10,z11}, {%165,%166}, {rx}, {fz,fz,fz,fz};\n" \
    "tanh.approx.f32 t0, z0; tanh.approx.f32 t1, z2;\n" \
    "fma.rn.f32 z0, z0, t0, z0; fma.rn.f32 z2, z2, t1, z2;\n" \
    "tanh.approx.f32 t2, z1; tanh.approx.f32 t3, z3;\n" \
    "fma.rn.f32 z1, z1, t2, z1; fma.rn.f32 z3, z3, t3, z3;\n" \
    "tanh.approx.f32 t4, z4; tanh.approx.f32 t5, z6;\n" \
    "fma.rn.f32 z4, z4, t4, z4; fma.rn.f32 z6, z6, t5, z6;\n" \
    "tanh.approx.f32 t6, z5; tanh.approx.f32 t7, z7;\n" \
    "ld.shared.v4.u32 {e0,e1,ex,e3}, [%160+16];\n" \
    "mov.u32 cnt, %%globaltimer_hi; st.shared.u32 [%177+32], cnt;\n" \
    "bra.uni SLOW;\n" \
    "S2:\n" \
    "add.u32 %160, %160, 16;\n" \
    "mov.b32 ca0, na0; xor.b32 ca1, na0, 32; mov.b32 ef, rx;\n" \
    "or.b32 c0, a0, a1; or.b32 c1, a2, a3;\n" \
    "prmt.b32 ey, e0, e1, %176;\n" \
    "and.b32 u2, ey, %172; setp.ne.u32 p0, u2, 0; and.b32 u2, ey, %173; setp.ne.u32 p1, u2, 0;\n" \
    "lop3.b32 u2, ey, 0xfff0, %174, 0xea; @pa ld.shared.v2.u32 {rx,ry}, [u2+%178];\n" \
    "tanh.approx.f32 t0, z8;\n" \
    "mov.b32 {h0,h1}, z0; mov.b32 u1, {h1,h1}; mul.bf16x2 w1, v1, u1;\n" \
    "fma.rn.f32 z5, z5, t6, z5;\n" \
    "ld.shared.v4.u32 {v12,v13,v14,v15}, [ca0+640];\n" \
    "tanh.approx.f32 t1, z10;\n" \
    "mov.b32 {h0,h1}, z0; mov.b32 u1, {h1,h1}; mul.bf16x2 w0, v0, u1;\n" \
    "mov.b32 {h0,h1}, z2; mov.b32 u1, {h1,h1}; mul.bf16x2 w3, v3, u1;\n" \
    "fma.rn.f32 z7, z7, t7, z7;\n" \
    "mov.b32 {h0,h1}, z2; mov.b32 u1, {h1,h1}; mul.bf16x2 w2, v2, u1;\n" \
    "tanh.approx.f32 t2, z9;\n" \
    "fma.rn.f32 z8, z8, t0, z8;\n" \
    "mma.sync.aligned.m16n8k16.row.col.f32.bf16.bf16.f32 {%128,%129,%130,%131}, {w0,w2,w1,w3}, {c0,c1}, {%128,%129,%130,%131};\n" \
    "ld.shared.v4.u32 {v0,v1,v2,v3}, [ca1+0];\n" \
    "mov.b32 {h0,h1}, z1; mov.b32 u1, {h1,h1}; mul.bf16x2 w1, v5, u1;\n" \
    "fma.rn.f32 z10, z10, t1, z10;\n" \
    "mov.b32 {h0,h1}, z3; mov.b32 u1, {h1,h1}; mul.bf16x2 w2, v6, u1;\n" \
    "mov.b32 {h0,h1}, z3; mov.b32 u1, {h1,h1}; mul.bf16x2 w3, v7, u1;\n" \
    "tanh.approx.f32 t3, z11;\n" \
    "mov.b32 {h0,h1}, z1; mov.b32 u1, {h1,h1}; mul.bf16x2 w0, v4, u1;\n" \
    "mma.sync.aligned.m16n8k16.row.col.f32.bf16.bf16.f32 {%132,%133,%134,%135}, {w0,w2,w1,w3}, {c0,c1}, {%132,%133,%134,%135};\n" \
    "mma.sync.aligned.m16n8k8.row.col.f32.bf16.bf16.f32 {z12,z13,z14,z15}, {%167,%168}, {ef}, {fz,fz,fz,fz};\n" \
    "tanh.approx.f32 t4, z12;\n" \
    "tanh.approx.f32 t5, z14;\n" \
    "ld.shared.v4.u32 {v4,v5,v6,v7}, [ca1+128];\n" \
    "mov.b32 {h0,h1}, z4; mov.b32 u1, {h1,h1}; mul.bf16x2 w0, v8, u1;\n" \
    "fma.rn.f32 z9, z9, t2, z9;\n" \
    "mov.b32 {h0,h1}, z6; mov.b32 u1, {h1,h1}; mul.bf16x2 w2, v10, u1;\n" \
    "mov.b32 {h0,h1}, z6; mov.b32 u1, {h1,h1}; mul.bf16x2 w3, v11, u1;\n" \
    "mov.b32 {h0,h1}, z4; mov.b32 u1, {h1,h1}; mul.bf16x2 w1, v9, u1;\n" \
    "fma.rn.f32 z11, z11, t3, z11;\n" \
    "mma.sync.aligned.m16n8k16.row.col.f32.bf16.bf16.f32 {%136,%137,%138,%139}, {w0,w2,w1,w3}, {c0,c1}, {%136,%137,%138,%139};\n" \
    "tanh.approx.f32 t6, z13;\n" \
    "fma.rn.f32 z12, z12, t4, z12;\n" \
    "mov.b32 {h0,h1}, z5; mov.b32 u1, {h1,h1}; mul.bf16x2 w0, v12, u1;\n" \
    "tanh.approx.f32 t7, z15;\n" \
    "fma.rn.f32 z14, z14, t5, z14;\n" \
    "ld.shared.v4.u32 {v8,v9,v10,v11}, [ca1+512];\n" \
    "mov.b32 {h0,h1}, z5; mov.b32 u1, {h1,h1}; mul.bf16x2 w1, v13, u1;\n" \
    "mov.b32 {h0,h1}, z7; mov.b32 u1, {h1,h1}; mul.bf16x2 w3, v15, u1;\n" \
    "mov.b32 {h0,h1}, z7; mov.b32 u1, {h1,h1}; mul.bf16x2 w2, v14, u1;\n" \
    "mma.sync.aligned.m16n8k16.row.col.f32.bf16.bf16.f32 {%140,%141,%142,%143}, {w0,w2,w1,w3}, {c0,c1}, {%140,%141,%142,%143};\n" \
    "shr.u32 u2, ex, 16; add.u32 na0, %171, u2;\n" \
    "mma.sync.aligned.m16n8k8.row.col.f32.bf16.bf16.f32 {z0,z1,z2,z3}, {%161,%162}, {rx}, {fz,fz,fz,fz};\n" \
    "tanh.approx.f32 t0, z0;\n" \
    "ld.shared.v4.u32 {v12,v13,v14,v15}, [ca1+640];\n" \
    "mov.b32 {h0,h1}, z8; mov.b32 u1, {h1,h1}; mul.bf16x2 w1, v1, u1;\n" \
    "fma.rn.f32 z15, z15, t7, z15;\n" \
    "fma.rn.f32 z13, z13, t6, z13;\n" \
    "mov.b32 {h0,h1}, z10; mov.b32 u1, {h1,h1}; mul.bf16x2 w3, v3, u1;\n" \
    "mov.b32 {h0,h1}, z8; mov.b32 u1, {h1,h1}; mul.bf16x2 w0, v0, u1;\n" \
    "tanh.approx.f32 t1, z2;\n" \
    "and.b32 u2, ex, 1; mbarrier.try_wait.parity.shared::cta.b64 pr, [e3], u2;\n" \
    "mov.b32 {h0,h1}, z10; mov.b32 u1, {h1,h1}; mul.bf16x2 w2, v2, u1;\n" \
    "mma.sync.aligned.m16n8k16.row.col.f32.bf16.bf16.f32 {%144,%145,%146,%147}, {w0,w2,w1,w3}, {c0,c1}, {%144,%145,%146,%147};\n" \
    "mov.b32 {h0,h1}, z9; mov.b32 u1, {h1,h1}; mul.bf16x2 w0, v4, u1;\n" \
    "tanh.approx.f32 t2, z1;\n" \
    "st.volatile.shared.u32 [%177], %160;\n" \
    "@pr ld.shared.v4.u32 {v0,v1,v2,v3}, [na0+0];\n" \
    "mov.b32 {h0,h1}, z9; mov.b32 u1, {h1,h1}; mul.bf16x2 w1, v5, u1;\n" \
    "fma.rn.f32 z0, z0, t0, z0;\n" \
    "tanh.approx.f32 t3, z3;\n" \
    "fma.rn.f32 z2, z2, t1, z2;\n" \
    "mov.b32 {h0,h1}, z11; mov.b32 u1, {h1,h1}; mul.bf16x2 w3, v7, u1;\n" \
    "mov.b32 {h0,h1}, z11; mov.b32 u1, {h1,h1}; mul.bf16x2 w2, v6, u1;\n" \
    "mma.sync.aligned.m16n8k16.row.col.f32.bf16.bf16.f32 {%148,%149,%150,%151}, {w0,w2,w1,w3}, {c0,c1}, {%148,%149,%150,%151};\n" \
    "mma.sync.aligned.m16n8k8.row.col.f32.bf16.bf16.f32 {z4,z5,z6,z7}, {%163,%164}, {rx}, {fz,fz,fz,fz};\n" \
    "tanh.approx.f32 t4, z4;\n" \
    "@pr ld.shared.v4.u32 {v4,v5,v6,v7}, [na0+128];\n" \
    "mov.b32 {h0,h1}, z12; mov.b32 u1, {h1,h1}; mul.bf16x2 w0, v8, u1;\n" \
    "tanh.approx.f32 t5, z6;\n" \
    "mov.b32 {h0,h1}, z12; mov.b32 u1, {h1,h1}; mul.bf16x2 w1, v9, u1;\n" \
    "fma.rn.f32 z1, z1, t2, z1;\n" \
    "mov.b32 {h0,h1}, z14; mov.b32 u1, {h1,h1}; mul.bf16x2 w3, v11, u1;\n" \
    "fma.rn.f32 z3, z3, t3, z3;\n" \
    "fma.rn.f32 z4, z4, t4, z4;\n" \
    "tanh.approx.f32 t6, z5;\n" \
    "mov.b32 {h0,h1}, z14; mov.b32 u1, {h1,h1}; mul.bf16x2 w2, v10, u1;\n" \
    "@pr ld.shared.v4.u32 {v8,v9,v10,v11}, [na0+512];\n" \
    "mma.sync.aligned.m16n8k16.row.col.f32.bf16.bf16.f32 {%152,%153,%154,%155}, {w0,w2,w1,w3}, {c0,c1}, {%152,%153,%154,%155};\n" \
    "mov.b32 {h0,h1}, z13; mov.b32 u1, {h1,h1}; mul.bf16x2 w0, v12, u1;\n" \
    "tanh.approx.f32 t7, z7;\n" \
    "mov.b32 {h0,h1}, z15; mov.b32 u1, {h1,h1}; mul.bf16x2 w3, v15, u1;\n" \
    "mov.b32 {h0,h1}, z13; mov.b32 u1, {h1,h1}; mul.bf16x2 w1, v13, u1;\n" \
    "fma.rn.f32 z6, z6, t5, z6;\n" \
    "mma.sync.aligned.m16n8k8.row.col.f32.bf16.bf16.f32 {y0,y1,y2,y3}, {%169,%170}, {ry}, {fz,fz,fz,fz};\n" \
    "mma.sync.aligned.m16n8k8.row.col.f32.bf16.bf16.f32 {z8,z9,z10,z11}, {%165,%166}, {rx}, {fz,fz,fz,fz};\n" \
    "and.b32 u2, ex, 14; setp.eq.and.u32 q0, u2, 2, pr; setp.eq.and.u32 q1, u2, 4, pr; setp.eq.and.u32 q2, u2, 8, pr;\n" \
    "mov.b32 {h0,h1}, z15; mov.b32 u1, {h1,h1}; mul.bf16x2 w2, v14, u1;\n" \
    "mma.sync.aligned.m16n8k16.row.col.f32.bf16.bf16.f32 {%156,%157,%158,%159}, {w0,w2,w1,w3}, {c0,c1}, {%156,%157,%158,%159};\n" \
    "ld.shared.v4.u32 {e0,e1,ex,e3}, [%160+16];\n" \
    "cvt.rn.bf16x2.f32 b0, y2, y0; cvt.rn.bf16x2.f32 b1, y3, y1;\n" \
    "selp.b32 a0, b0, 0, p0; selp.b32 a1, b0, 0, p1; selp.b32 a2, b1, 0, p0; selp.b32 a3, b1, 0, p1;\n" \
    "@q1 bra.uni S1;\n" \
    "@!q0 bra.uni D;\n" \
    "S0:\n" \
    "add.u32 %160, %160, 16;\n" \
    "mov.b32 ca0, na0; xor.b32 ca1, na0, 32; mov.b32 ef, rx;\n" \
    "prmt.b32 ey, e0, e1, %176;\n" \
    "and.b32 u2, ey, %172; setp.ne.u32 p0, u2, 0; and.b32 u2, ey, %173; setp.ne.u32 p1, u2, 0;\n" \
    "fma.rn.f32 z5, z5, t6, z5;\n" \
    "lop3.b32 u2, ey, 0xfff0, %174, 0xea; @pa ld.shared.v2.u32 {rx,ry}, [u2+%178];\n" \
    "mov.b32 {h0,h1}, z0; mov.b32 u1, {h1,h1}; mul.bf16x2 v0, v0, u1;\n" \
    "tanh.approx.f32 t0, z8;\n" \
    "tanh.approx.f32 t1, z10;\n" \
    "ld.shared.v4.u32 {v12,v13,v14,v15}, [ca0+640];\n" \
    "mov.b32 {h0,h1}, z0; mov.b32 u1, {h1,h1}; mul.bf16x2 v1, v1, u1;\n" \
    "mov.b32 {h0,h1}, z2; mov.b32 u1, {h1,h1}; mul.bf16x2 v2, v2, u1;\n" \
    "mma.sync.aligned.m16n8k16.row.col.f32.bf16.bf16.f32 {%0,%1,%2,%3}, {a0,a1,a2,a3}, {v0,v1}, {%0,%1,%2,%3};\n" \
    "fma.rn.f32 z7, z7, t7, z7;\n" \
    "mov.b32 {h0,h1}, z2; mov.b32 u1, {h1,h1}; mul.bf16x2 v3, v3, u1;\n" \
    "fma.rn.f32 z8, z8, t0, z8;\n" \
    "mma.sync.aligned.m16n8k16.row.col.f32.bf16.bf16.f32 {%4,%5,%6,%7}, {a0,a1,a2,a3}, {v2,v3}, {%4,%5,%6,%7};\n" \
    "ld.shared.v4.u32 {v0,v1,v2,v3}, [ca1+0];\n" \
    "tanh.approx.f32 t2, z9;\n" \
    "fma.rn.f32 z10, z10, t1, z10;\n" \
    "mov.b32 {h0,h1}, z1; mov.b32 u1, {h1,h1}; mul.bf16x2 v5, v5, u1;\n" \
    "mov.b32 {h0,h1}, z3; mov.b32 u1, {h1,h1}; mul.bf16x2 v6, v6, u1;\n" \
    "tanh.approx.f32 t3, z11;\n" \
    "mov.b32 {h0,h1}, z1; mov.b32 u1, {h1,h1}; mul.bf16x2 v4, v4, u1;\n" \
    "mma.sync.aligned.m16n8k16.row.col.f32.bf16.bf16.f32 {%8,%9,%10,%11}, {a0,a1,a2,a3}, {v4,v5}, {%8,%9,%10,%11};\n" \
    "mov.b32 {h0,h1}, z3; mov.b32 u1, {h1,h1}; mul.bf16x2 v7, v7, u1;\n" \
    "mma.sync.aligned.m16n8k16.row.col.f32.bf16.bf16.f32 {%12,%13,%14,%15}, {a0,a1,a2,a3}, {v6,v7}, {%12,%13,%14,%15};\n" \
    "ld.shared.v4.u32 {v4,v5,v6,v7}, [ca1+128];\n" \
    "mma.sync.aligned.m16n8k8.row.col.f32.bf16.bf16.f32 {z12,z13,z14,z15}, {%167,%168}, {ef}, {fz,fz,fz,fz};\n" \
    "tanh.approx.f32 t4, z12;\n" \
    "mov.b32 {h0,h1}, z6; mov.b32 u1, {h1,h1}; mul.bf16x2 v11, v11, u1;\n" \
    "mov.b32 {h0,h1}, z4; mov.b32 u1, {h1,h1}; mul.bf16x2 v8, v8, u1;\n" \
    "fma.rn.f32 z9, z9, t2, z9;\n" \
    "mov.b32 {h0,h1}, z4; mov.b32 u1, {h1,h1}; mul.bf16x2 v9, v9, u1;\n" \
    "mma.sync.aligned.m16n8k16.row.col.f32.bf16.bf16.f32 {%16,%17,%18,%19}, {a0,a1,a2,a3}, {v8,v9}, {%16,%17,%18,%19};\n" \
    "fma.rn.f32 z11, z11, t3, z11;\n" \
    "mov.b32 {h0,h1}, z6; mov.b32 u1, {h1,h1}; mul.bf16x2 v10, v10, u1;\n" \
    "mma.sync.aligned.m16n8k16.row.col.f32.bf16.bf16.f32 {%20,%21,%22,%23}, {a0,a1,a2,a3}, {v10,v11}, {%20,%21,%22,%23};\n" \
    "ld.shared.v4.u32 {v8,v9,v10,v11}, [ca1+512];\n" \
    "tanh.approx.f32 t5, z14;\n" \
    "mov.b32 {h0,h1}, z5; mov.b32 u1, {h1,h1}; mul.bf16x2 v12, v12, u1;\n" \
    "fma.rn.f32 z12, z12, t4, z12;\n" \
    "tanh.approx.f32 t6, z13;\n" \
    "mov.b32 {h0,h1}, z7; mov.b32 u1, {h1,h1}; mul.bf16x2 v15, v15, u1;\n" \
    "mov.b32 {h0,h1}, z7; mov.b32 u1, {h1,h1}; mul.bf16x2 v14, v14, u1;\n" \
    "tanh.approx.f32 t7, z15;\n" \
    "mma.sync.aligned.m16n8k8.row.col.f32.bf16.bf16.f32 {z0,z1,z2,z3}, {%161,%162}, {rx}, {fz,fz,fz,fz};\n" \
    "mov.b32 {h0,h1}, z5; mov.b32 u1, {h1,h1}; mul.bf16x2 v13, v13, u1;\n" \
    "mma.sync.aligned.m16n8k16.row.col.f32.bf16.bf16.f32 {%24,%25,%26,%27}, {a0,a1,a2,a3}, {v12,v13}, {%24,%25,%26,%27};\n" \
    "mma.sync.aligned.m16n8k16.row.col.f32.bf16.bf16.f32 {%28,%29,%30,%31}, {a0,a1,a2,a3}, {v14,v15}, {%28,%29,%30,%31};\n" \
    "fma.rn.f32 z14, z14, t5, z14;\n" \
    "ld.shared.v4.u32 {v12,v13,v14,v15}, [ca1+640];\n" \
    "tanh.approx.f32 t0, z0;\n" \
    "shr.u32 u2, ex, 16; add.u32 na0, %171, u2;\n" \
    "fma.rn.f32 z15, z15, t7, z15;\n" \
    "fma.rn.f32 z13, z13, t6, z13;\n" \
    "mov.b32 {h0,h1}, z10; mov.b32 u1, {h1,h1}; mul.bf16x2 v3, v3, u1;\n" \
    "mov.b32 {h0,h1}, z8; mov.b32 u1, {h1,h1}; mul.bf16x2 v0, v0, u1;\n" \
    "mov.b32 {h0,h1}, z8; mov.b32 u1, {h1,h1}; mul.bf16x2 v1, v1, u1;\n" \
    "mma.sync.aligned.m16n8k16.row.col.f32.bf16.bf16.f32 {%32,%33,%34,%35}, {a0,a1,a2,a3}, {v0,v1}, {%32,%33,%34,%35};\n" \
    "tanh.approx.f32 t1, z2;\n" \
    "mov.b32 {h0,h1}, z10; mov.b32 u1, {h1,h1}; mul.bf16x2 v2, v2, u1;\n" \
    "mma.sync.aligned.m16n8k16.row.col.f32.bf16.bf16.f32 {%36,%37,%38,%39}, {a0,a1,a2,a3}, {v2,v3}, {%36,%37,%38,%39};\n" \
    "and.b32 u2, ex, 1; mbarrier.try_wait.parity.shared::cta.b64 pr, [e3], u2;\n" \
    "st.volatile.shared.u32 [%177], %160;\n" \
    "@pr ld.shared.v4.u32 {v0,v1,v2,v3}, [na0+0];\n" \
    "fma.rn.f32 z0, z0, t0, z0;\n" \
    "tanh.approx.f32 t3, z3;\n" \
    "tanh.approx.f32 t2, z1;\n" \
    "fma.rn.f32 z2, z2, t1, z2;\n" \
    "mov.b32 {h0,h1}, z9; mov.b32 u1, {h1,h1}; mul.bf16x2 v4, v4, u1;\n" \
    "mov.b32 {h0,h1}, z9; mov.b32 u1, {h1,h1}; mul.bf16x2 v5, v5, u1;\n" \
    "mov.b32 {h0,h1}, z11; mov.b32 u1, {h1,h1}; mul.bf16x2 v6, v6, u1;\n" \
    "mma.sync.aligned.m16n8k16.row.col.f32.bf16.bf16.f32 {%40,%41,%42,%43}, {a0,a1,a2,a3}, {v4,v5}, {%40,%41,%42,%43};\n" \
    "mov.b32 {h0,h1}, z11; mov.b32 u1, {h1,h1}; mul.bf16x2 v7, v7, u1;\n" \
    "mma.sync.aligned.m16n8k16.row.col.f32.bf16.bf16.f32 {%44,%45,%46,%47}, {a0,a1,a2,a3}, {v6,v7}, {%44,%45,%46,%47};\n" \
    "mov.b32 {h0,h1}, z12; mov.b32 u1, {h1,h1}; mul.bf16x2 v8, v8, u1;\n" \
    "fma.rn.f32 z1, z1, t2, z1;\n" \
    "mma.sync.aligned.m16n8k8.row.col.f32.bf16.bf16.f32 {z4,z5,z6,z7}, {%163,%164}, {rx}, {fz,fz,fz,fz};\n" \
    "tanh.approx.f32 t4, z4;\n" \
    "@pr ld.shared.v4.u32 {v4,v5,v6,v7}, [na0+128];\n" \
    "tanh.approx.f32 t5, z6;\n" \
    "mov.b32 {h0,h1}, z12; mov.b32 u1, {h1,h1}; mul.bf16x2 v9, v9, u1;\n" \
    "mma.sync.aligned.m16n8k16.row.col.f32.bf16.bf16.f32 {%48,%49,%50,%51}, {a0,a1,a2,a3}, {v8,v9}, {%48,%49,%50,%51};\n" \
    "mov.b32 {h0,h1}, z14; mov.b32 u1, {h1,h1}; mul.bf16x2 v11, v11, u1;\n" \
    "fma.rn.f32 z3, z3, t3, z3;\n" \
    "mov.b32 {h0,h1}, z14; mov.b32 u1, {h1,h1}; mul.bf16x2 v10, v10, u1;\n" \
    "fma.rn.f32 z4, z4, t4, z4;\n" \
    "mma.sync.aligned.m16n8k16.row.col.f32.bf16.bf16.f32 {%52,%53,%54,%55}, {a0,a1,a2,a3}, {v10,v11}, {%52,%53,%54,%55};\n" \
    "@pr ld.shared.v4.u32 {v8,v9,v10,v11}, [na0+512];\n" \
    "mov.b32 {h0,h1}, z13; mov.b32 u1, {h1,h1}; mul.bf16x2 v12, v12, u1;\n" \
    "tanh.approx.f32 t6, z5;\n" \
    "mov.b32 {h0,h1}, z13; mov.b32 u1, {h1,h1}; mul.bf16x2 v13, v13, u1;\n" \
    "mma.sync.aligned.m16n8k16.row.col.f32.bf16.bf16.f32 {%56,%57,%58,%59}, {a0,a1,a2,a3}, {v12,v13}, {%56,%57,%58,%59};\n" \
    "fma.rn.f32 z6, z6, t5, z6;\n" \
    "mov.b32 {h0,h1}, z15; mov.b32 u1, {h1,h1}; mul.bf16x2 v15, v15, u1;\n" \
    "tanh.approx.f32 t7, z7;\n" \
    "mov.b32 {h0,h1}, z15; mov.b32 u1, {h1,h1}; mul.bf16x2 v14, v14, u1;\n" \
    "mma.sync.aligned.m16n8k16.row.col.f32.bf16.bf16.f32 {%60,%61,%62,%63}, {a0,a1,a2,a3}, {v14,v15}, {%60,%61,%62,%63};\n" \
    "mma.sync.aligned.m16n8k8.row.col.f32.bf16.bf16.f32 {z8,z9,z10,z11}, {%165,%166}, {rx}, {fz,fz,fz,fz};\n" \
    "mma.sync.aligned.m16n8k8.row.col.f32.bf16.bf16.f32 {y0,y1,y2,y3}, {%169,%170}, {ry}, {fz,fz,fz,fz};\n" \
    "and.b32 u2, ex, 14; setp.eq.and.u32 q0, u2, 2, pr; setp.eq.and.u32 q1, u2, 4, pr; setp.eq.and.u32 q2, u2, 8, pr;\n" \
    "ld.shared.v4.u32 {e0,e1,ex,e3}, [%160+16];\n" \
    "cvt.rn.bf16x2.f32 b0, y2, y0; cvt.rn.bf16x2.f32 b1, y3, y1;\n" \
    "selp.b32 a0, b0, 0, p0; selp.b32 a1, b0, 0, p1; selp.b32 a2, b1, 0, p0; selp.b32 a3, b1, 0, p1;\n" \
    "@!q1 bra.uni D;\n" \
    "S1:\n" \
    "add.u32 %160, %160, 16;\n" \
    "mov.b32 ca0, na0; xor.b32 ca1, na0, 32; mov.b32 ef, rx;\n" \
    "prmt.b32 ey, e0, e1, %176;\n" \
    "and.b32 u2, ey, %172; setp.ne.u32 p0, u2, 0; and.b32 u2, ey, %173; setp.ne.u32 p1, u2, 0;\n" \
    "fma.rn.f32 z5, z5, t6, z5;\n" \
    "lop3.b32 u2, ey, 0xfff0, %174, 0xea; @pa ld.shared.v2.u32 {rx,ry}, [u2+%178];\n" \
    "mov.b32 {h0,h1}, z0; mov.b32 u1, {h1,h1}; mul.bf16x2 v0, v0, u1;\n" \
    "tanh.approx.f32 t0, z8;\n" \
    "tanh.approx.f32 t1, z10;\n" \
    "ld.shared.v4.u32 {v12,v13,v14,v15}, [ca0+640];\n" \
    "mov.b32 {h0,h1}, z0; mov.b32 u1, {h1,h1}; mul.bf16x2 v1, v1, u1;\n" \
    "mov.b32 {h0,h1}, z2; mov.b32 u1, {h1,h1}; mul.bf16x2 v2, v2, u1;\n" \
    "mma.sync.aligned.m16n8k16.row.col.f32.bf16.bf16.f32 {%64,%65,%66,%67}, {a0,a1,a2,a3}, {v0,v1}, {%64,%65,%66,%67};\n" \
    "fma.rn.f32 z7, z7, t7, z7;\n" \
    "mov.b32 {h0,h1}, z2; mov.b32 u1, {h1,h1}; mul.bf16x2 v3, v3, u1;\n" \
    "fma.rn.f32 z8, z8, t0, z8;\n" \
    "mma.sync.aligned.m16n8k16.row.col.f32.bf16.bf16.f32 {%68,%69,%70,%71}, {a0,a1,a2,a3}, {v2,v3}, {%68,%69,%70,%71};\n" \
    "ld.shared.v4.u32 {v0,v1,v2,v3}, [ca1+0];\n" \
    "tanh.approx.f32 t2, z9;\n" \
    "fma.rn.f32 z10, z10, t1, z10;\n" \
    "mov.b32 {h0,h1}, z1; mov.b32 u1, {h1,h1}; mul.bf16x2 v5, v5, u1;\n" \
    "mov.b32 {h0,h1}, z3; mov.b32 u1, {h1,h1}; mul.bf16x2 v6, v6, u1;\n" \
    "tanh.approx.f32 t3, z11;\n" \
    "mov.b32 {h0,h1}, z1; mov.b32 u1, {h1,h1}; mul.bf16x2 v4, v4, u1;\n" \
    "mma.sync.aligned.m16n8k16.row.col.f32.bf16.bf16.f32 {%72,%73,%74,%75}, {a0,a1,a2,a3}, {v4,v5}, {%72,%73,%74,%75};\n" \
    "mov.b32 {h0,h1}, z3; mov.b32 u1, {h1,h1}; mul.bf16x2 v7, v7, u1;\n" \
    "mma.sync.aligned.m16n8k16.row.col.f32.bf16.bf16.f32 {%76,%77,%78,%79}, {a0,a1,a2,a3}, {v6,v7}, {%76,%77,%78,%79};\n" \
    "ld.shared.v4.u32 {v4,v5,v6,v7}, [ca1+128];\n" \
    "mma.sync.aligned.m16n8k8.row.col.f32.bf16.bf16.f32 {z12,z13,z14,z15}, {%167,%168}, {ef}, {fz,fz,fz,fz};\n" \
    "tanh.approx.f32 t4, z12;\n" \
    "mov.b32 {h0,h1}, z6; mov.b32 u1, {h1,h1}; mul.bf16x2 v11, v11, u1;\n" \
    "mov.b32 {h0,h1}, z4; mov.b32 u1, {h1,h1}; mul.bf16x2 v8, v8, u1;\n" \
    "fma.rn.f32 z9, z9, t2, z9;\n" \
    "mov.b32 {h0,h1}, z4; mov.b32 u1, {h1,h1}; mul.bf16x2 v9, v9, u1;\n" \
    "mma.sync.aligned.m16n8k16.row.col.f32.bf16.bf16.f32 {%80,%81,%82,%83}, {a0,a1,a2,a3}, {v8,v9}, {%80,%81,%82,%83};\n" \
    "fma.rn.f32 z11, z11, t3, z11;\n" \
    "mov.b32 {h0,h1}, z6; mov.b32 u1, {h1,h1}; mul.bf16x2 v10, v10, u1;\n" \
    "mma.sync.aligned.m16n8k16.row.col.f32.bf16.bf16.f32 {%84,%85,%86,%87}, {a0,a1,a2,a3}, {v10,v11}, {%84,%85,%86,%87};\n" \
    "ld.shared.v4.u32 {v8,v9,v10,v11}, [ca1+512];\n" \
    "tanh.approx.f32 t5, z14;\n" \
    "mov.b32 {h0,h1}, z5; mov.b32 u1, {h1,h1}; mul.bf16x2 v12, v12, u1;\n" \
    "fma.rn.f32 z12, z12, t4, z12;\n" \
    "tanh.approx.f32 t6, z13;\n" \
    "mov.b32 {h0,h1}, z7; mov.b32 u1, {h1,h1}; mul.bf16x2 v15, v15, u1;\n" \
    "mov.b32 {h0,h1}, z7; mov.b32 u1, {h1,h1}; mul.bf16x2 v14, v14, u1;\n" \
    "tanh.approx.f32 t7, z15;\n" \
    "mma.sync.aligned.m16n8k8.row.col.f32.bf16.bf16.f32 {z0,z1,z2,z3}, {%161,%162}, {rx}, {fz,fz,fz,fz};\n" \
    "mov.b32 {h0,h1}, z5; mov.b32 u1, {h1,h1}; mul.bf16x2 v13, v13, u1;\n" \
    "mma.sync.aligned.m16n8k16.row.col.f32.bf16.bf16.f32 {%88,%89,%90,%91}, {a0,a1,a2,a3}, {v12,v13}, {%88,%89,%90,%91};\n" \
    "mma.sync.aligned.m16n8k16.row.col.f32.bf16.bf16.f32 {%92,%93,%94,%95}, {a0,a1,a2,a3}, {v14,v15}, {%92,%93,%94,%95};\n" \
    "fma.rn.f32 z14, z14, t5, z14;\n" \
    "ld.shared.v4.u32 {v12,v13,v14,v15}, [ca1+640];\n" \
    "tanh.approx.f32 t0, z0;\n" \
    "shr.u32 u2, ex, 16; add.u32 na0, %171, u2;\n" \
    "fma.rn.f32 z15, z15, t7, z15;\n" \
    "fma.rn.f32 z13, z13, t6, z13;\n" \
    "mov.b32 {h0,h1}, z10; mov.b32 u1, {h1,h1}; mul.bf16x2 v3, v3, u1;\n" \
    "mov.b32 {h0,h1}, z8; mov.b32 u1, {h1,h1}; mul.bf16x2 v0, v0, u1;\n" \
    "mov.b32 {h0,h1}, z8; mov.b32 u1, {h1,h1}; mul.bf16x2 v1, v1, u1;\n" \
    "mma.sync.aligned.m16n8k16.row.col.f32.bf16.bf16.f32 {%96,%97,%98,%99}, {a0,a1,a2,a3}, {v0,v1}, {%96,%97,%98,%99};\n" \
    "tanh.approx.f32 t1, z2;\n" \
    "mov.b32 {h0,h1}, z10; mov.b32 u1, {h1,h1}; mul.bf16x2 v2, v2, u1;\n" \
    "mma.sync.aligned.m16n8k16.row.col.f32.bf16.bf16.f32 {%100,%101,%102,%103}, {a0,a1,a2,a3}, {v2,v3}, {%100,%101,%102,%103};\n" \
    "and.b32 u2, ex, 1; mbarrier.try_wait.parity.shared::cta.b64 pr, [e3], u2;\n" \
    "st.volatile.shared.u32 [%177], %160;\n" \
    "@pr ld.shared.v4.u32 {v0,v1,v2,v3}, [na0+0];\n" \
    "fma.rn.f32 z0, z0, t0, z0;\n" \
    "tanh.approx.f32 t3, z3;\n" \
    "tanh.approx.f32 t2, z1;\n" \
    "fma.rn.f32 z2, z2, t1, z2;\n" \
    "mov.b32 {h0,h1}, z9; mov.b32 u1, {h1,h1}; mul.bf16x2 v4, v4, u1;\n" \
    "mov.b32 {h0,h1}, z9; mov.b32 u1, {h1,h1}; mul.bf16x2 v5, v5, u1;\n" \
    "mov.b32 {h0,h1}, z11; mov.b32 u1, {h1,h1}; mul.bf16x2 v6, v6, u1;\n" \
    "mma.sync.aligned.m16n8k16.row.col.f32.bf16.bf16.f32 {%104,%105,%106,%107}, {a0,a1,a2,a3}, {v4,v5}, {%104,%105,%106,%107};\n" \
    "mov.b32 {h0,h1}, z11; mov.b32 u1, {h1,h1}; mul.bf16x2 v7, v7, u1;\n" \
    "mma.sync.aligned.m16n8k16.row.col.f32.bf16.bf16.f32 {%108,%109,%110,%111}, {a0,a1,a2,a3}, {v6,v7}, {%108,%109,%110,%111};\n" \
    "mov.b32 {h0,h1}, z12; mov.b32 u1, {h1,h1}; mul.bf16x2 v8, v8, u1;\n" \
    "fma.rn.f32 z1, z1, t2, z1;\n" \
    "mma.sync.aligned.m16n8k8.row.col.f32.bf16.bf16.f32 {z4,z5,z6,z7}, {%163,%164}, {rx}, {fz,fz,fz,fz};\n" \
    "tanh.approx.f32 t4, z4;\n" \
    "@pr ld.shared.v4.u32 {v4,v5,v6,v7}, [na0+128];\n" \
    "tanh.approx.f32 t5, z6;\n" \
    "mov.b32 {h0,h1}, z12; mov.b32 u1, {h1,h1}; mul.bf16x2 v9, v9, u1;\n" \
    "mma.sync.aligned.m16n8k16.row.col.f32.bf16.bf16.f32 {%112,%113,%114,%115}, {a0,a1,a2,a3}, {v8,v9}, {%112,%113,%114,%115};\n" \
    "mov.b32 {h0,h1}, z14; mov.b32 u1, {h1,h1}; mul.bf16x2 v11, v11, u1;\n" \
    "fma.rn.f32 z3, z3, t3, z3;\n" \
    "mov.b32 {h0,h1}, z14; mov.b32 u1, {h1,h1}; mul.bf16x2 v10, v10, u1;\n" \
    "fma.rn.f32 z4, z4, t4, z4;\n" \
    "mma.sync.aligned.m16n8k16.row.col.f32.bf16.bf16.f32 {%116,%117,%118,%119}, {a0,a1,a2,a3}, {v10,v11}, {%116,%117,%118,%119};\n" \
    "@pr ld.shared.v4.u32 {v8,v9,v10,v11}, [na0+512];\n" \
    "mov.b32 {h0,h1}, z13; mov.b32 u1, {h1,h1}; mul.bf16x2 v12, v12, u1;\n" \
    "tanh.approx.f32 t6, z5;\n" \
    "mov.b32 {h0,h1}, z13; mov.b32 u1, {h1,h1}; mul.bf16x2 v13, v13, u1;\n" \
    "mma.sync.aligned.m16n8k16.row.col.f32.bf16.bf16.f32 {%120,%121,%122,%123}, {a0,a1,a2,a3}, {v12,v13}, {%120,%121,%122,%123};\n" \
    "fma.rn.f32 z6, z6, t5, z6;\n" \
    "mov.b32 {h0,h1}, z15; mov.b32 u1, {h1,h1}; mul.bf16x2 v15, v15, u1;\n" \
    "tanh.approx.f32 t7, z7;\n" \
    "mov.b32 {h0,h1}, z15; mov.b32 u1, {h1,h1}; mul.bf16x2 v14, v14, u1;\n" \
    "mma.sync.aligned.m16n8k16.row.col.f32.bf16.bf16.f32 {%124,%125,%126,%127}, {a0,a1,a2,a3}, {v14,v15}, {%124,%125,%126,%127};\n" \
    "mma.sync.aligned.m16n8k8.row.col.f32.bf16.bf16.f32 {z8,z9,z10,z11}, {%165,%166}, {rx}, {fz,fz,fz,fz};\n" \
    "mma.sync.aligned.m16n8k8.row.col.f32.bf16.bf16.f32 {y0,y1,y2,y3}, {%169,%170}, {ry}, {fz,fz,fz,fz};\n" \
    "and.b32 u2, ex, 14; setp.eq.and.u32 q0, u2, 2, pr; setp.eq.and.u32 q1, u2, 4, pr; setp.eq.and.u32 q2, u2, 8, pr;\n" \
    "ld.shared.v4.u32 {e0,e1,ex,e3}, [%160+16];\n" \
    "cvt.rn.bf16x2.f32 b0, y2, y0; cvt.rn.bf16x2.f32 b1, y3, y1;\n" \
    "selp.b32 a0, b0, 0, p0; selp.b32 a1, b0, 0, p1; selp.b32 a2, b1, 0, p0; selp.b32 a3, b1, 0, p1;\n" \
    "D:\n" \
    "@q0 bra.uni S0;\n" \
    "@q2 bra.uni S2;\n" \
    "@q1 bra.uni S1;\n" \
    "SLOW:\n" \
    "ld.shared.v2.u32 {gx,gy}, [%160+8];\n" \
    "and.b32 u2, gx, 1; and.b32 gx, gx, 14; setp.eq.u32 q0, gx, 2; setp.eq.u32 q1, gx, 4; setp.eq.u32 q2, gx, 8;\n" \
    "setp.eq.u32 pr, gx, 0;\n" \
    "@pr bra.uni DONE;\n" \
    "XW:\n" \
    "mov.u32 cnt, %%globaltimer_hi; ld.shared.u32 gx, [%177+32]; sub.u32 cnt, cnt, gx;\n" \
    "mbarrier.try_wait.parity.shared::cta.b64 pr, [gy], u2;\n" \
    "setp.lt.and.u32 pr, cnt, 2, !pr;\n" \
    "@pr bra.uni XW;\n" \
    "ld.shared.v4.u32 {v0,v1,v2,v3}, [na0+0];\n" \
    "ld.shared.v4.u32 {v4,v5,v6,v7}, [na0+128];\n" \
    "ld.shared.v4.u32 {v8,v9,v10,v11}, [na0+512];\n" \
    "@q0 bra.uni S0;\n" \
    "@q1 bra.uni S1;\n" \
    "bra.uni S2;\n" \
    "DONE:\n" \
    "mov.b32 u2, z0; xor.b32 %160, %160, u2;\n" \
    "mov.b32 u2, z2; xor.b32 %160, %160, u2;\n" \
    "mov.b32 u2, z1; xor.b32 %160, %160, u2;\n" \
    "mov.b32 u2, z3; xor.b32 %160, %160, u2;\n" \
    "mov.b32 u2, z4; xor.b32 %160, %160, u2;\n" \
    "mov.b32 u2, z6; xor.b32 %160, %160, u2;\n" \
    "}\n" \
    ""
#define MAIN_LOOP_ACC(A) \
    "+f"(A[0][0]), "+f"(A[0][1]), "+f"(A[0][2]), "+f"(A[0][3]), "+f"(A[1][0]), "+f"(A[1][1]), "+f"(A[1][2]), "+f"(A[1][3]), \
    "+f"(A[2][0]), "+f"(A[2][1]), "+f"(A[2][2]), "+f"(A[2][3]), "+f"(A[3][0]), "+f"(A[3][1]), "+f"(A[3][2]), "+f"(A[3][3]), \
    "+f"(A[4][0]), "+f"(A[4][1]), "+f"(A[4][2]), "+f"(A[4][3]), "+f"(A[5][0]), "+f"(A[5][1]), "+f"(A[5][2]), "+f"(A[5][3]), \
    "+f"(A[6][0]), "+f"(A[6][1]), "+f"(A[6][2]), "+f"(A[6][3]), "+f"(A[7][0]), "+f"(A[7][1]), "+f"(A[7][2]), "+f"(A[7][3]), \
    "+f"(A[8][0]), "+f"(A[8][1]), "+f"(A[8][2]), "+f"(A[8][3]), "+f"(A[9][0]), "+f"(A[9][1]), "+f"(A[9][2]), "+f"(A[9][3]), \
    "+f"(A[10][0]), "+f"(A[10][1]), "+f"(A[10][2]), "+f"(A[10][3]), "+f"(A[11][0]), "+f"(A[11][1]), "+f"(A[11][2]), "+f"(A[11][3]), \
    "+f"(A[12][0]), "+f"(A[12][1]), "+f"(A[12][2]), "+f"(A[12][3]), "+f"(A[13][0]), "+f"(A[13][1]), "+f"(A[13][2]), "+f"(A[13][3]), \
    "+f"(A[14][0]), "+f"(A[14][1]), "+f"(A[14][2]), "+f"(A[14][3]), "+f"(A[15][0]), "+f"(A[15][1]), "+f"(A[15][2]), "+f"(A[15][3]), \
    "+f"(A[16][0]), "+f"(A[16][1]), "+f"(A[16][2]), "+f"(A[16][3]), "+f"(A[17][0]), "+f"(A[17][1]), "+f"(A[17][2]), "+f"(A[17][3]), \
    "+f"(A[18][0]), "+f"(A[18][1]), "+f"(A[18][2]), "+f"(A[18][3]), "+f"(A[19][0]), "+f"(A[19][1]), "+f"(A[19][2]), "+f"(A[19][3]), \
    "+f"(A[20][0]), "+f"(A[20][1]), "+f"(A[20][2]), "+f"(A[20][3]), "+f"(A[21][0]), "+f"(A[21][1]), "+f"(A[21][2]), "+f"(A[21][3]), \
    "+f"(A[22][0]), "+f"(A[22][1]), "+f"(A[22][2]), "+f"(A[22][3]), "+f"(A[23][0]), "+f"(A[23][1]), "+f"(A[23][2]), "+f"(A[23][3]), \
    "+f"(A[24][0]), "+f"(A[24][1]), "+f"(A[24][2]), "+f"(A[24][3]), "+f"(A[25][0]), "+f"(A[25][1]), "+f"(A[25][2]), "+f"(A[25][3]), \
    "+f"(A[26][0]), "+f"(A[26][1]), "+f"(A[26][2]), "+f"(A[26][3]), "+f"(A[27][0]), "+f"(A[27][1]), "+f"(A[27][2]), "+f"(A[27][3]), \
    "+f"(A[28][0]), "+f"(A[28][1]), "+f"(A[28][2]), "+f"(A[28][3]), "+f"(A[29][0]), "+f"(A[29][1]), "+f"(A[29][2]), "+f"(A[29][3]), \
    "+f"(A[30][0]), "+f"(A[30][1]), "+f"(A[30][2]), "+f"(A[30][3]), "+f"(A[31][0]), "+f"(A[31][1]), "+f"(A[31][2]), "+f"(A[31][3]), \
    "+f"(A[32][0]), "+f"(A[32][1]), "+f"(A[32][2]), "+f"(A[32][3]), "+f"(A[33][0]), "+f"(A[33][1]), "+f"(A[33][2]), "+f"(A[33][3]), \
    "+f"(A[34][0]), "+f"(A[34][1]), "+f"(A[34][2]), "+f"(A[34][3]), "+f"(A[35][0]), "+f"(A[35][1]), "+f"(A[35][2]), "+f"(A[35][3]), \
    "+f"(A[36][0]), "+f"(A[36][1]), "+f"(A[36][2]), "+f"(A[36][3]), "+f"(A[37][0]), "+f"(A[37][1]), "+f"(A[37][2]), "+f"(A[37][3]), \
    "+f"(A[38][0]), "+f"(A[38][1]), "+f"(A[38][2]), "+f"(A[38][3]), "+f"(A[39][0]), "+f"(A[39][1]), "+f"(A[39][2]), "+f"(A[39][3])
#define PRODUCER_PTX \
    "{\n" \
    ".reg .b32 r<4>, d, c, t, w, n, bb, dd, kw, cc; .reg .b64 a; .reg .pred p;\n" \
    "mov.b32 n, 0; mov.b32 r0, 0; mov.u32 cc, %%globaltimer_lo; sub.s32 cc, cc, %11;\n" \
    "bra.uni TURN;\n" \
    "TOP:\n" \
    "ld.shared.v4.u32 {r0,r1,r2,r3}, [%0+%16];\n" \
    "ld.shared.u16 t, [%0+72];\n" \
    "mov.u32 c, %%globaltimer_lo; sub.s32 c, c, %11; sub.s32 c, c, t; setp.ge.s32 p, c, 0;\n" \
    "@p bra.uni G;\n" \
    "T:\n" \
    "nanosleep.u32 64;\n" \
    "mov.u32 c, %%globaltimer_lo; sub.s32 c, c, %11; sub.s32 c, c, t; setp.lt.s32 p, c, 0;\n" \
    "@p bra.uni T;\n" \
    "G:\n" \
    "ld.volatile.shared.u32 w, [%9]; setp.lt.u32 p, w, %0;\n" \
    "@p bra.uni W;\n" \
    "mbarrier.arrive.expect_tx.shared::cta.b64 _, [bb], %12;\n" \
    "add.u32 d, dd, 0*%15;\n" \
    "cp.async.bulk.tensor.2d.shared::cluster.global.tile.mbarrier::complete_tx::bytes [d], [%4, {%5, r0}], [bb];\n" \
    "add.u32 d, dd, 1*%15;\n" \
    "cp.async.bulk.tensor.2d.shared::cluster.global.tile.mbarrier::complete_tx::bytes [d], [%4, {%6, r1}], [bb];\n" \
    "add.u32 d, dd, 2*%15;\n" \
    "cp.async.bulk.tensor.2d.shared::cluster.global.tile.mbarrier::complete_tx::bytes [d], [%4, {%7, r2}], [bb];\n" \
    "add.u32 d, dd, 3*%15;\n" \
    "cp.async.bulk.tensor.2d.shared::cluster.global.tile.mbarrier::complete_tx::bytes [d], [%4, {%8, r3}], [bb];\n" \
    "add.u32 %0, %0, 16; add.u32 bb, bb, 8; add.u32 dd, dd, 1024; setp.ne.u32 p, %0, kw;\n" \
    "@p bra.uni TOP;\n" \
    "TURN:\n" \
    "setp.ge.u32 p, %0, %10;\n" \
    "@p bra.uni END;\n" \
    "mov.b32 bb, %3; mov.b32 dd, %2; add.u32 kw, %0, 80; min.u32 kw, kw, %10;\n" \
    "shr.u32 c, r0, 3; add.u32 c, c, %17; setp.lt.u32 p, c, %1;\n" \
    "@p bra.uni TOP;\n" \
    "sub.s32 c, %14, %1; min.s32 c, c, %18; setp.gt.s32 p, c, 0; shl.b32 c, c, 10; mad.wide.u32 a, %1, 1024, %13;\n" \
    "@p cp.async.bulk.prefetch.L2.global [a], c;\n" \
    "add.u32 %1, %1, %19;\n" \
    "bra.uni TOP;\n" \
    "W:\n" \
    "add.u32 n, n, 1; setp.lt.u32 p, n, 0x1000000;\n" \
    "@p bra.uni G;\n" \
    "END:\n" \
    "}\n" \
    ""

__device__ __forceinline__ void wgmma_n64(float (&d)[32], const uint32_t (&a)[4], uint64_t desc, int acc) {
    asm volatile("{\n\t.reg .pred p;\n\tsetp.ne.u32 p, %37, 0;\n\t"
        "wgmma.mma_async.sync.aligned.m64n64k16.f32.bf16.bf16 {%0,%1,%2,%3,%4,%5,%6,%7,%8,%9,%10,%11,%12,%13,%14,%15,"
        "%16,%17,%18,%19,%20,%21,%22,%23,%24,%25,%26,%27,%28,%29,%30,%31}, {%32,%33,%34,%35}, %36, p, 1, 1, 1;\n\t}"
        : "+f"(d[0]), "+f"(d[1]), "+f"(d[2]), "+f"(d[3]), "+f"(d[4]), "+f"(d[5]), "+f"(d[6]), "+f"(d[7]),
          "+f"(d[8]), "+f"(d[9]), "+f"(d[10]), "+f"(d[11]), "+f"(d[12]), "+f"(d[13]), "+f"(d[14]), "+f"(d[15]),
          "+f"(d[16]), "+f"(d[17]), "+f"(d[18]), "+f"(d[19]), "+f"(d[20]), "+f"(d[21]), "+f"(d[22]), "+f"(d[23]),
          "+f"(d[24]), "+f"(d[25]), "+f"(d[26]), "+f"(d[27]), "+f"(d[28]), "+f"(d[29]), "+f"(d[30]), "+f"(d[31])
        : "r"(a[0]), "r"(a[1]), "r"(a[2]), "r"(a[3]), "l"(desc), "r"(acc));
}

#define YFQ 1
#define YFP 1
#define PW 0
#define AL 1
#define PLD 1
#define PSU 0
#define PT1 900
#define PT0 1550
#define PDT 36.2
#define NSLEEP 64
#define PFA 1400
#define PFR 8
template <int ID, int COUNT> __device__ __forceinline__ void bar_sync() { asm volatile("bar.sync %0, %1;" ::"n"(ID), "n"(COUNT) : "memory"); }
template <int ID, int COUNT> __device__ __forceinline__ void bar_arrive() { asm volatile("bar.arrive %0, %1;" ::"n"(ID), "n"(COUNT) : "memory"); }
template <int BYTES>
__device__ __forceinline__ void fill(uint32_t addr, uint4 v, int tid) {
#pragma unroll
    for (int r = 0; r < (BYTES / 16 + NT - 1) / NT; r++)
        sts128_if((r + 1) * NT <= BYTES / 16 || r * NT + tid < BYTES / 16, addr + (r * NT + tid) * 16, v);
}

__device__ __forceinline__ uint32_t group_cap(uint32_t key, int lane) {
    return __reduce_add_sync(0xffffffffu, min(key >> 5, GK)) > KCAP ? KCAP / NG : lane < 16 ? GK : 128 - 2 * GK;
}
template <int NR>
__device__ __forceinline__ void build_list(uint4 lt, uint4 lo, int wl, int lane, int N, uint32_t bin_magic, uint32_t pace) {
    const uint32_t lh = sb + SM_LH + wl * (LBIN * 4);
    uint4 w[NR], r[NR];
    uint32_t p[NR], ba[NR], ez[NR];
#pragma unroll
    for (int j = 0; j < NR; j++) {
        const uint32_t i = j * 32 + lane;
        w[j] = lds128(sb + SM_KSG + i * 16 + (i < lt.x ? lo.x : i < lt.y ? lo.y : lo.z));
        ez[j] = i < lt.x ? 2 : i < lt.y ? 4 : 8;
    }
#pragma unroll
    for (int j = 0; j < NR; j++) {
        r[j] = make_uint4(w[j].x & 0x3fff, w[j].y & 0x3fff, w[j].z & 0x3fff, w[j].w & 0x3fff);
        const uint32_t key = r[j].x + r[j].y + r[j].z + r[j].w;
        ba[j] = j * 32 + lane < lt.z ? lh + (key * bin_magic >> 20) * 4 : sb + SM_DUM + lane * 4;
        ez[j] |= __umulhi(key * 2, pace) & 0xfff0;
    }
#pragma unroll
    for (int j = 0; j < NR; j++) p[j] = atoms_inc(ba[j]);
    __syncwarp();
    const uint4 u = lds128(lh + lane * 16);
    const uint32_t sum = u.x + u.y + u.z + u.w, ex = warp_incl_scan(sum) - sum;
    sts128_if(true, lh + lane * 16, make_uint4(ex, ex + u.x, ex + u.x + u.y, ex + u.x + u.y + u.z));
    __syncwarp();
#pragma unroll
    for (int j = 0; j < NR; j++) p[j] += lds32(ba[j]);
#pragma unroll
    for (int j = 0; j < NR; j++) {
        const uint32_t turn = (p[j] * SMG) >> 16, slot = p[j] - turn * S;
        sts128_if(p[j] < lt.z, sb + SM_SRC + (lt.w + p[j]) * 16, make_uint4(r[j].x * 8, r[j].y * 8, r[j].z * 8, r[j].w * 8));
        sts128_if(p[j] < lt.z, sb + SM_LIST + (lt.w + p[j]) * 16,
                  make_uint4(__byte_perm(w[j].x * 4, w[j].y * 4, 0x7632), __byte_perm(w[j].z * 4, w[j].w * 4, 0x7632),
                             (ez[j] | (turn & 1)) + slot * (1u << 26), sb + SM_BAR + wl * (S * 8) + slot * 8));
    }
}
__device__ __forceinline__ bool next_excess(const Scratch* scr, const __nv_bfloat16* x, uint32_t va0) {
    uint32_t tid, cta;
    asm volatile("mov.u32 %0, %tid.x;" : "=r"(tid));
    asm volatile("mov.u32 %0, %ctaid.x;" : "=r"(cta));
    const int lane = tid & 31, wl = tid >> 5;
    const uint32_t bar_rec = sb + SM_BAR + NW * S * 8 + 16, own = sb + SM_SRC + wl * 96, st = sb + SM_STATE + wl * 16;
    const uint32_t grp = lds32(sb + SM_MISC + 64 + wl * 4);
    uint4 c = lds128(st);
    __syncwarp();
    for (; c.x <= NCTA; c.x++, c.y = 0) {
        if (c.y == 0 && c.z == 0)
            c.x += __reduce_min_sync(0xffffffffu, c.x + lane >= NCTA || (lds32(sb + SM_SEG + min(c.x + lane, NCTA - 1) * 4) >> 12) > MBE ? lane : 31);
        const uint32_t loc = lds32(sb + SM_SEG + min(c.x, NCTA - 1) * 4);
        const int n = c.x < NCTA ? (int)(loc >> 12) - MBE : lds32(sb + SM_MISC + 12);
        for (; (int)c.y < n; c.y += 32, c.z = 0) {
            uint2 u = make_uint2(0xffffffffu, c.x * SLICE + (loc & 0xfff) + MBE + c.y + lane);
            if ((int)c.y + lane < n) {
                if (c.x < NCTA) u.x = __ldcg(scr->ss + u.y);
                else u = __ldcg(scr->exc + cta * MBW + c.y + lane);
            }
            const uint32_t gw = (u.x >> 25 & 31) - 1, ja = gw == (grp & 31) ? 1 : gw == (grp >> 5 & 31) ? 2 : gw == (grp >> 10 & 31) ? 3 : 0;
            const unsigned todo = __ballot_sync(0xffffffffu, ja) & ~c.z;
            if (!todo) continue;
            const uint32_t jf = __shfl_sync(0xffffffffu, ja, __ffs(todo) - 1);
            const unsigned m = todo & __ballot_sync(0xffffffffu, ja == jf);
            const uint32_t from = __fns(m, 0, (lane & 3) + 1);
            const bool pad = from > 31;
            c.z |= __reduce_or_sync(0xffffffffu, pad ? 0 : 1u << from);
            if (!(todo & ~c.z)) { c.y += 32; c.z = 0; }
            u.x = __shfl_sync(0xffffffffu, u.x, pad ? __ffs(m) - 1 : from);
            u.y = __shfl_sync(0xffffffffu, u.y, from);
            const uint32_t slot = ((grp >> 16) + S - 1) % S;
#pragma unroll 1
            for (int k = 0; k < 8; k++)
                cp16((va0 ^ (k & 4) * 8) + slot * 1024 + (k & 1) * 128 + (k & 2) * 256,
                     reinterpret_cast<const uint4*>(x) + (size_t)(u.x & 0x3fff) * 64 + chunk_of(k, lane >> 2));
            mbar_wait(bar_rec - 16, 0);
            if (lane < 4) {
                if (!pad) cp16(own + 32 + lane * 16, scr->rec + u.y);
                asm volatile("st.shared.u16 [%0], %1;" ::"r"(own + lane * 2),
                             "h"((uint16_t)(((pad ? sb + SM_ZERO : own + 32 + lane * 16) - sb - SM_REC) | (u.x >> 14 & 15))) : "memory");
                sts32_if(lane == 0, own + 8, 1u << jf | slot << 26);
                sts32_if(lane == 0, own + 12, bar_rec);
                sts128_if(lane == 0, own + 16, make_uint4(0, 0, 0, bar_rec));
                sts128_if(lane == 0, st, c);
            }
            asm volatile("cp.async.wait_all;" ::: "memory");
            __syncwarp();
            return true;
        }
    }
    return false;
}

template <int MODE>
__global__ void __launch_bounds__(NT, 1)
tfn_kernel(const int* __restrict__ dst, const int* __restrict__ src, Scratch* scr, int E, int slice,
           int N, int npc, uint32_t npc_magic, uint32_t bin_magic, const uint2* __restrict__ Y, const uint2* __restrict__ ef,
           const __nv_bfloat16* __restrict__ w_rad, const __nv_bfloat16* __restrict__ cg, const __nv_bfloat16* __restrict__ x,
           const __nv_bfloat16* __restrict__ w_mix, __nv_bfloat16* __restrict__ out, uint32_t pace,
           const __grid_constant__ CUtensorMap xmap, const __grid_constant__ CUtensorMap wmap) {
    extern __shared__ __align__(1024) uint8_t smem[];
    const int tid = threadIdx.x, lane = tid & 31, warp = __shfl_sync(0xffffffffu, tid >> 5, 0);
    const int cta = blockIdx.x;
    const uint32_t bar_w = sb + SM_BAR + NW * S * 8, bar_raw = bar_w + 8, bar_rec = bar_w + 16, bar_mb = bar_w + 24;
    auto prefetch_x = [&](int chunk) {
        const int row = (chunk * NCTA + cta) * PFR;
        if (row < N)
            asm volatile("cp.async.bulk.prefetch.L2.global [%0], %1;" ::"l"(x + (size_t)row * 512), "r"(min(PFR, N - row) * 1024));
    };
    const int g = lane >> 2, t = lane & 3;
    uint32_t wz[4][2], wt[2];
    uint32_t cgr[4];
    auto load_weights = [&]() {
        const uint32_t* wr = reinterpret_cast<const uint32_t*>(w_rad) + (t & 1) * 128;
        const uint16_t* cp = reinterpret_cast<const uint16_t*>(cg) + (t >> 1) * 32 + (t & 1) * 8 + (g & 3);
#pragma unroll
        for (int j = 0; j < 4; j++) {
            asm volatile("ld.global.u32 %0, [%1];" : "=r"(wz[j][0]) : "l"(wr + chunk_of(2 * j + (t >> 1), g)) : "memory");
            asm volatile("ld.global.u32 %0, [%1];" : "=r"(wz[j][1]) : "l"(wr + chunk_of(2 * j + (t >> 1), g) + 64) : "memory");
            asm volatile("ld.global.u16 %0, [%1];" : "=r"(cgr[j]) : "l"(cp + (j >> 1) * 16 + (j & 1) * 4) : "memory");
        }
    };
    auto weights = [&]() {
        const uint32_t z = lds32(sb + SM_ZERO), hh = 0x3f003f00u + z;
        const __nv_bfloat162 half = *reinterpret_cast<const __nv_bfloat162*>(&hh);
#pragma unroll
        for (int j = 0; j < 4; j++) {
            const __nv_bfloat162 h0 = __hmul2(*reinterpret_cast<__nv_bfloat162*>(&wz[j][0]), half);
            const __nv_bfloat162 h1 = __hmul2(*reinterpret_cast<__nv_bfloat162*>(&wz[j][1]), half);
            const uint32_t u0 = *reinterpret_cast<const uint32_t*>(&h0), u1 = *reinterpret_cast<const uint32_t*>(&h1);
            wz[j][0] = __byte_perm(u0, u1, 0x5410);
            wz[j][1] = __byte_perm(u0, u1, 0x7632);
        }
        wt[0] = __byte_perm(cgr[0], cgr[1], 0x5410 + z);
        wt[1] = __byte_perm(cgr[2], cgr[3], 0x5410 + z);
        sts32_if((wz[0][0] ^ wz[0][1] ^ wz[1][0] ^ wz[1][1] ^ wz[2][0] ^ wz[2][1] ^ wz[3][0] ^ wz[3][1] ^ wt[0] ^ wt[1]) == 1,
                 sb + SM_ZERO + 96, 0);
    };

    const int e0 = cta * slice, ne = min(E - e0, slice);
    uint32_t a_d[RA], a_s[RA];
    uint32_t tag = 0;
    if (MODE & 1) {
        const int q = min(e0 / 4 + tid, (E - 1) >> 2), e = min(e0 + 4 * NT + tid, E - 1);
        const int4 d4 = __ldcs(reinterpret_cast<const int4*>(dst) + q);
        a_d[4] = __ldcs(dst + e);
        const int4 s4 = __ldcs(reinterpret_cast<const int4*>(src) + q);
        a_s[4] = __ldcs(src + e);
        a_d[0] = d4.x; a_d[1] = d4.y; a_d[2] = d4.z; a_d[3] = d4.w;
        a_s[0] = s4.x; a_s[1] = s4.y; a_s[2] = s4.z; a_s[3] = s4.w;
    }
    if (MODE == 3) asm volatile("ld.relaxed.gpu.global.u32 %0, [%1];" : "=r"(tag) : "l"(&scr->epoch) : "memory");
    auto load_raw = [&](int which) {
        const int bytes = max((ne + 1) >> 1, 0) * 16;
        asm volatile("mbarrier.arrive.expect_tx.shared::cta.b64 _, [%0], %1;" ::"r"(bar_raw), "r"(bytes) : "memory");
        if (bytes > 0)
            asm volatile("cp.async.bulk.shared::cluster.global.mbarrier::complete_tx::bytes [%0], [%1], %2, [%3];"
                         ::"r"(sb + SM_RAWY + which * SLICE * 8), "l"((which ? ef : Y) + e0), "r"(bytes), "r"(bar_raw) : "memory");
    };
    auto send = [&](bool p, uint32_t* gp, uint4 v) {
        asm volatile("{\n\t.reg .pred p;\n\tsetp.ne.u32 p, %5, 0;\n\t@p st.relaxed.gpu.global.v4.u32 [%0], {%1,%2,%3,%4};\n\t}"
                     ::"l"(gp), "r"(v.x), "r"(v.y), "r"(v.z), "r"(v.w), "r"((uint32_t)p) : "memory");
    };
    uint32_t mc[3];
    auto prewrite = [&](uint4 empty) {
#pragma unroll
        for (int r = 0; r < 3; r++) {
            const uint32_t i = r * NT + tid, c = i < 4 * NCTA ? i >> 2 : ((i - 4 * NCTA) * 10923) >> 16, j = i < 4 * NCTA ? (i & 3) + 2 : i - 4 * NCTA - c * 6 + 6;
            mc[r] = c << 8 | j;
            if (r > 0) send(c < NCTA && j >= 6, scr->mb + c * MBW + cta * MBC + j * 4, empty);
        }
    };
    if ((uint32_t)__cvta_generic_to_shared(smem) != sb) __trap();
    if (elect_one()) {
#pragma unroll
        for (int i = 0; i < S; i++)
            if (warp >= NW) mbar_init(sb + SM_BAR + ((warp - NW) * S + i) * 8, 1);
        if (warp == 0) {
            mbar_init(bar_w, NW);
            mbar_init(bar_raw, 2);
            mbar_init(bar_rec, NW);
            mbar_init(bar_mb, 1);
        }
        asm volatile("fence.mbarrier_init.release.cluster;" ::: "memory");
    }
    fill<SM_KSG - SM_BIN>(sb + SM_BIN, make_uint4(0, 0, 0, 0), tid);
    if (MODE & 1) {
        const uint32_t em = lane << (BSH + 2);
        const uint4 empty = make_uint4(em, em + (1 << BSH), em + (2 << BSH), em + (3 << BSH));
        if (PW == 0) prewrite(empty);
        fill<NCTA * ASTR * 4>(sb + SM_AMB, empty, tid);
    }
    sts32_if(tid < 32, sb + SM_AOFF + (NCTA + tid) * 4, SLICE);
    sts32_if(tid < 128, sb + SM_DUM + tid * 4, 0x10000);
    if (MODE & 2) {
        const uint32_t pad = RCAP << 18 | N;
        fill<SM_BAR - SM_ZERO>(sb + SM_ZERO, make_uint4(0, 0, 0, 0), tid);
        fill<NG * GK * 16>(sb + SM_KSG, make_uint4(pad, pad, pad, pad), tid);
    }
    if ((MODE & 1) && PW == 1) {
        const uint32_t em = lane << (BSH + 2);
        prewrite(make_uint4(em, em + (1 << BSH), em + (2 << BSH), em + (3 << BSH)));
    }
    __syncthreads();
    if ((MODE & 1) && PW == 2) {
        const uint32_t em = lane << (BSH + 2);
        prewrite(make_uint4(em, em + (1 << BSH), em + (2 << BSH), em + (3 << BSH)));
    }
    STAMP(15);
    if (warp == 13 && (MODE & 2) && elect_one()) {
        asm volatile("cp.async.bulk.prefetch.L2.global [%0], 1024;" ::"l"(w_rad));
        asm volatile("cp.async.bulk.prefetch.L2.global [%0], 128;" ::"l"(cg));
        asm volatile("prefetch.tensormap [%0];" ::"l"(&xmap) : "memory");
        asm volatile("prefetch.tensormap [%0];" ::"l"(&wmap) : "memory");
        asm volatile("st.shared.u64 [%0], %1;" ::"r"(sb + SM_MISC + 24), "l"(&xmap) : "memory");
    }
    if (MODE & 1) {
        if (((YFP == 1 && warp == 14) || (YFQ == 1 && warp == 15)) && elect_one()) load_raw(warp & 1);
        const uint32_t z = lds32(sb + SM_KEY + lane * 4);
        tag = ((tag + z) & 1) + 1;
        const uint32_t tg = tag << 30;
        uint32_t cc[RA], rk[RA];
#pragma unroll
        for (int r = 0; r < RA; r++) {
            cc[r] = (r < 4 ? 4 * tid + r : 4 * NT + tid) < ne ? __umulhi(a_d[r], npc_magic + z) : NCTA + lane;
            rk[r] = atoms_inc(sb + SM_HIST + cc[r] * 4);
        }
        if (((YFP == 2 && warp == 14) || (YFQ == 2 && warp == 15)) && elect_one()) load_raw(warp & 1);
#pragma unroll
        for (int r = 0; r < RA; r++) {
            const uint32_t l = a_d[r] - cc[r] * npc;
            a_s[r] = (tg + ((l < 64 ? (l >> 2) + 1 : (l >> 1) - 15) << 25)) | ((a_s[r] * (bin_magic + z)) & ((NBIN - 1) << BSH)) | a_s[r] | 0x4000u << (l & (l < 64 ? 3 : 1));
            sts32_if(true, sb + SM_AMB + (cc[r] * ASTR + min(rk[r], MBE) + 1) * 4, a_s[r]);
        }
        STAMP(1);
        __syncthreads();
        STAMP(28);
        if (((YFP == 3 && warp == 4) || (YFQ == 3 && warp == 5)) && elect_one()) load_raw(warp & 1);
        uint32_t hh[3];
#pragma unroll
        for (int r = 1; r < 3; r++) hh[r] = lds32(sb + SM_HIST + min(mc[r] >> 8, NCTA + 33) * 4);
#pragma unroll
        for (int r = 0; r < 3; r++) {
            const uint32_t c = mc[r] >> 8, j = mc[r] & 15;
            const bool used = r == 0 || j < 6 || (c < NCTA && hh[r] >= (j & 14) * 4);
            if (r == 0 || __any_sync(0xffffffffu, used))
                send(used, scr->mb + c * MBW + cta * MBC + j * 4, lds128(sb + SM_AMB + min(c, NCTA) * (ASTR * 4) + j * 16));
        }
        if (warp >= 7) {
            const uint32_t c = (tid - 7 * 32) >> 1, h = !(tid & 1) && c < NCTA ? lds32(sb + SM_HIST + c * 4) : 0;
            uint4 v = lds128(sb + SM_AMB + c * (ASTR * 4) + (tid & 1) * 16);
            const uint32_t h2 = (h + AL) & ~AL, inc = warp_incl_scan(h2);
            const uint32_t off = __shfl_sync(0xffffffffu, atoms_add(sb + SM_HIST + 135 * 4 + lane * 4, lane == 31 ? inc : 0), 31) + inc - h2;
            if (!(tid & 1)) v.x = tg | h << 12 | off;
            send(c < NCTA, scr->mb + c * MBW + cta * MBC + (tid & 1) * 4, v);
            sts32_if(!(tid & 1) && c < NCTA, sb + SM_AOFF + c * 4, off);
        }
        STAMP(2);
        __syncthreads();
        if (MODE == 3 && tid == NT - 1) asm volatile("red.relaxed.gpu.global.add.u32 [%0], 1;" ::"l"(scr->sent + (tag & 1)) : "memory");
        if (((YFP == 4 && warp == 4) || (YFQ == 4 && warp == 5)) && elect_one()) load_raw(warp & 1);
        uint32_t ap[2 * RA];
#pragma unroll
        for (int r = 0; r < RA; r++) ap[r] = rk[r] + lds32(sb + SM_AOFF + cc[r] * 4);
        if (__builtin_expect(max(max(max(rk[0], rk[1]), max(rk[2], rk[3])), rk[4]) >= MBE, 0)) {
#pragma unroll
            for (int r = 0; r < RA; r++)
                if (rk[r] >= MBE && cc[r] < NCTA) __stcg(scr->ss + cta * SLICE + ap[r], a_s[r]);
            __threadfence();
        }
        if (warp >= NW) {
            asm volatile("st.shared.v2.u32 [%0], {%1, %2};" ::"r"(sb + SM_AP + (tid - NH) * 8), "r"(ap[0] | ap[1] << 16), "r"(ap[2] | ap[3] << 16) : "memory");
            sts32_if(true, sb + SM_AP + NH * 8 + (tid - NH) * 4, ap[4]);
            bar_arrive<1, NT>();
        } else {
            bar_sync<1, NT>();
            const uint2 u = lds64(sb + SM_AP + tid * 8);
            ap[5] = u.x & 0xffff; ap[6] = u.x >> 16; ap[7] = u.y & 0xffff; ap[8] = u.y >> 16;
            ap[9] = lds32(sb + SM_AP + NH * 8 + tid * 4);
            const bool sw = lane & 4;
            const uint32_t nst = lds32(sb + SM_HIST + 166 * 4) * 16;
            if (MODE == 3) load_weights();
            mbar_wait(bar_raw, 0);
            STAMP(10);
#pragma unroll
            for (int hh = 0; hh < 2; hh++) {
                const uint32_t a = sb + SM_RAWY + (hh * NH + tid) * 32 + (lane & 4) * 4, b = sb + SM_RAWY + (4 * NT + hh * NH + tid) * 8;
                const uint4 y0 = lds128(a), f0 = lds128(a + SLICE * 8), y1 = lds128(a ^ 16), f1 = lds128((a ^ 16) + SLICE * 8);
                const uint2 y2 = lds64(b), f2 = lds64(b + SLICE * 8);
                const uint32_t* q = ap + hh * RA;
                sts128_if(true, sb + SM_AREC + (sw ? q[2] : q[0]) * 16, make_uint4(f0.x, y0.x, f0.y, y0.y));
                sts128_if(true, sb + SM_AREC + (sw ? q[3] : q[1]) * 16, make_uint4(f0.z, y0.z, f0.w, y0.w));
                sts128_if(true, sb + SM_AREC + (sw ? q[0] : q[2]) * 16, make_uint4(f1.x, y1.x, f1.y, y1.y));
                sts128_if(true, sb + SM_AREC + (sw ? q[1] : q[3]) * 16, make_uint4(f1.z, y1.z, f1.w, y1.w));
                sts128_if(true, sb + SM_AREC + q[4] * 16, make_uint4(f2.x, y2.x, f2.y, y2.y));
            }
            asm volatile("fence.proxy.async.shared::cta;" ::: "memory");
            bar_sync<7, NH>();
            STAMP(25);
            if (MODE == 3 && warp == NW - 1) bar_sync<9, 64>();
            if (warp == NW - 1 && lane == 0 && ne > 0)
                asm volatile("cp.async.bulk.global.shared::cta.bulk_group [%0], [%1], %2;"
                             ::"l"(scr->rec + cta * SLICE), "r"(sb + SM_AREC), "r"(nst) : "memory");
            if (MODE == 3) weights();
            if (warp == NW - 1) {
                asm volatile("cp.async.bulk.commit_group;" ::: "memory");
                asm volatile("cp.async.bulk.wait_group 0;" ::: "memory");
                STAMPT(26, NH - 32);
                if (MODE == 3) {
                    mbar_wait(bar_mb, 0);
                    if (lane == 0) {
                        const uint32_t now = timer32(), tm = lds32v(sb + SM_MISC + 20);
                        asm volatile("red.relaxed.gpu.global.max.u32 [%0], %1;" ::"l"(scr->sent2[tag & 1] + 8), "r"(max((tm ? tm : now) + PT0, now + PT1)) : "memory");
                        asm volatile("red.relaxed.gpu.global.or.b32 [%0], %1;" ::"l"(scr->sent2[tag & 1] + cta % 6), "r"(1u << cta / 6) : "memory");
                    }
                    uint32_t v;
                    int guard = 0;
                    do {
                        asm volatile("ld.relaxed.gpu.global.u32 %0, [%1];" : "=r"(v) : "l"(scr->sent2[tag & 1] + (lane & 15)) : "memory");
                        sts32_if(lane < NW, sb + SM_MISC + 96 + lane * 4, v);
                    } while (__any_sync(0xffffffffu, lane < 6 && v != (1u << NCTA / 6) - 1) && ++guard < (1 << 20));
                    sts32_if(lane == NW, sb + SM_MISC + 4, v);
                    STAMPT(24, NH - 32);
                }
            }
        }
    } else {
        tag = 1;
    }
    if (!(MODE & 2)) return;
    const int wl = warp & (NW - 1);
    const uint32_t ring = sb + SM_RING + wl * (S * 1024);
    const uint32_t bars = sb + SM_BAR + wl * (S * 8);
    const uint32_t pos = bar_w + 32 + wl * 4;

    if (warp >= NW) {
        uint32_t ss[RL + 1], rk[RL + 1];
        const uint32_t sl = wl + 8 * lane, empty = lane << BSH;
        if (wl == 0) {
            if (elect_one()) {
                asm volatile("mbarrier.arrive.expect_tx.shared::cta.b64 _, [%0], %1;" ::"r"(bar_mb), "n"(MBW * 4) : "memory");
                asm volatile("{\n\t.reg .pred p;\n\t.reg .b32 n, v;\n\tmov.b32 n, 0;\n"
                             "AGAIN:\n\tld.relaxed.gpu.global.u32 v, [%4];\n\tadd.u32 n, n, 1;\n\tsetp.lt.u32 p, n, 1048576;\n\t"
                             "setp.lt.and.u32 p, v, %5, p;\n\t@p bra.uni AGAIN;\n\t"
                             "cp.async.bulk.shared::cluster.global.mbarrier::complete_tx::bytes [%0], [%1], %2, [%3];\n\t}"
                             ::"r"(sb + SM_AMB), "l"(scr->mb + cta * MBW + lds32v(sb + SM_ZERO)), "n"(MBW * 4), "r"(bar_mb),
                               "l"(scr->sent + (tag & 1)), "n"(MODE == 3 ? NCTA : 0) : "memory");
            }
            __syncwarp();
            STAMPT(11, NH);
            if (MODE == 3) bar_arrive<9, 64>();
            if (MODE != 3) sts32_if(true, sb + SM_MISC + 4, timer32() + PT0);
        }
        uint32_t loc, cnt, from, big;
        for (int guard = 0;; guard++) {
            mbar_wait(bar_mb, 0);
            STAMPT(3, NH);
            loc = lds32(sb + SM_AMB + min(sl, NCTA - 1) * (MBC * 4));
#pragma unroll
            for (int r = 0; r < RL; r++) ss[r] = lds32(sb + SM_AMB + ((wl + 8 * r) * MBC + lane + 1) * 4);
            if (MODE == 3) sts32_if(wl == NW - 1, sb + SM_MISC + 20, timer32());
            if (wl + 8 * (RL - 1) >= NCTA) ss[RL - 1] = empty;
            cnt = sl < NCTA ? loc >> 12 & 0xfff : 0;
            big = __ballot_sync(0xffffffffu, cnt > 32);
            from = __ffs((lane < 16 ? big : big & (big - 1)) | 1 << RL) - 1;
            cnt = min(cnt, __popc(big & ((1u << lane) - 1)) < 2 ? MBE : 32);
            ss[RL] = lds32(sb + SM_AMB + ((wl + 8 * from) * MBC + 33 + (lane & 15)) * 4);
            if (32 + (lane & 15) >= __shfl_sync(0xffffffffu, cnt, from)) ss[RL] = empty;
            uint32_t any = ~loc >> 30 & tag ? 0xffffffffu : 0, got[2] = {-cnt * tag, 0};
#pragma unroll
            for (int r = 0; r <= RL; r++) { any |= ss[r]; got[r & 1] += ss[r] >> 30; }
            if (!__reduce_add_sync(0xffffffffu, got[0] + got[1] + (any >> 30 & (3 - tag) ? 0x10000 : 0)) || guard == 1 << 20) break;
#pragma unroll 1
            for (int r = wl; r < NCTA; r += 8)
                if (lane < MBC / 4)
                    sts128_if(true, sb + SM_AMB + (r * MBC + lane * 4) * 4, ldg128_relaxed(reinterpret_cast<const uint4*>(scr->mb + cta * MBW + r * MBC) + lane));
            __syncwarp();
        }
        STAMPT(4, NH);
        auto bin_of = [&](uint32_t w) { return sb + SM_DUM + (w >> (BSH - 2) & (NBIN * 128 - 4)); };
#pragma unroll
        for (int r = 0; r <= RL; r++) rk[r] = atoms_add(bin_of(ss[r]), 4);
        STAMPT(5, NH);
        bar_sync<3, NH>();
        uint32_t dof;
        {
            const uint32_t a = sb + SM_BIN + wl * (NBIN * 12) + lane * 16;
            uint4 u[3];
            uint32_t sum[3];
#pragma unroll
            for (int j = 0; j < 3; j++) {
                u[j] = lds128(a + j * (NBIN * 4));
                sum[j] = u[j].x + u[j].y + u[j].z + u[j].w;
            }
            uint32_t i01 = sum[0] | sum[1] << 16, i2 = sum[2] | ((cnt + AL) & ~AL) << 16;
#pragma unroll
            for (int o = 1; o < 32; o <<= 1) {
                scan_step(i01, o);
                scan_step(i2, o);
            }
            dof = atoms_add(sb + SM_MISC - 124 + lane * 4, lane == 31 ? i2 >> 16 : 0);
            const uint32_t inc[3] = {i01 & 0xffff, i01 >> 16, i2 & 0xffff};
#pragma unroll
            for (int j = 0; j < 3; j++) {
                const uint32_t p = (3 * wl + j) * (GK * 16) + inc[j] - sum[j];
                sts128_if(true, a + j * (NBIN * 4), make_uint4(p, p + u[j].x, p + u[j].x + u[j].y, p + u[j].x + u[j].y + u[j].z));
                sts32_if(lane == 31, sb + SM_KEY + (3 * wl + j) * 4, (inc[j] + 12) >> 4 << 5 | (3 * wl + j));
            }
            dof = __shfl_sync(0xffffffffu, dof, 31) + (i2 >> 16) - ((cnt + AL) & ~AL);
            sts32_if(sl < NCTA, sb + SM_SEG + sl * 4, loc & 0xffffff);
            sts32_if((loc >> 12 & 0xfff) > MBE, sb + SM_MISC + 8, 1);
            sts32_if(true, sb + SM_DOFF + (tid - NH) * 4, dof << 18);
            const uint64_t from = reinterpret_cast<uint64_t>(scr->rec + sl * SLICE + (loc & 0xfff));
            sts128_if(sl < NCTA, sb + SM_CPY + sl * 16,
                      make_uint4((uint32_t)from, (uint32_t)(from >> 32), sb + SM_REC + dof * 16, min(cnt, RCAP - min(dof, RCAP)) * 16));
        }
        STAMPT(12, NH);
        bar_arrive<4, NT - 32>();
        bar_sync<3, NH>();
        const uint32_t key = lds32(sb + SM_KEY + lane * 4), nrec = lds32(sb + SM_MISC);
        uint32_t d20[RL + 3];
#pragma unroll
        for (int r = 0; r < RL; r += 4) {
            const uint4 v = lds128(sb + SM_DOFF + wl * 128 + r * 4);
            d20[r] = v.x; d20[r + 1] = v.y; d20[r + 2] = v.z; d20[r + 3] = v.w;
        }
#pragma unroll
        for (int r = 0; r <= RL; r++) {
            uint32_t v;
            asm volatile("{\n\t.reg .pred p;\n\tsetp.lt.u32 p, %2, 0x10000;\n\tmov.b32 %0, %2;\n\t@p ld.shared.u32 %0, [%1];\n\t}"
                         : "=&r"(v) : "r"(bin_of(ss[r])), "r"(rk[r]) : "memory");
            rk[r] += v;
        }
        d20[RL] = (__shfl_sync(0xffffffffu, dof, from) + 32 - (lane & 16)) << 18;
        const uint32_t cap = group_cap(key, lane);
        const uint32_t lim = __any_sync(0xffffffffu, (key >> 5) > cap || nrec > RCAP) ? 0 : 0x20000;
#pragma unroll
        for (int r = 0; r <= RL; r++) {
            uint32_t v;
            asm("lop3.b32 %0, %1, 0x3ffff, %2, 0xea;" : "=r"(v) : "r"(ss[r]), "r"(lane << 18));
            sts32_if(rk[r] < lim, sb + SM_KSG + rk[r], v + d20[r]);
        }
        if (__builtin_expect(lim == 0 || __popc(big) > 2, 0)) {
            auto excess = [&](uint32_t w, uint32_t gi) { __stcg(scr->exc + cta * MBW + atoms_inc(sb + SM_MISC + 12), make_uint2(w, gi)); };
            big &= big - 1;
#pragma unroll 1
            for (big &= big - 1; big; big &= big - 1) {
                const uint32_t r = __ffs(big) - 1, l = __shfl_sync(0xffffffffu, loc, r);
                if (32 + lane < min(l >> 12 & 0xfff, MBE)) {
                    uint32_t w;
                    int guard = 0;
                    do asm volatile("ld.relaxed.gpu.global.u32 %0, [%1];" : "=r"(w) : "l"(scr->mb + cta * MBW + (wl + 8 * r) * MBC + 33 + lane) : "memory");
                    while (w >> 30 != tag && ++guard < (1 << 20));
                    excess(w, (wl + 8 * r) * SLICE + (l & 0xfff) + 32 + lane);
                }
            }
            const uint32_t tmp = sb + SM_AMB + (wl * MBC + lane) * 4;
#pragma unroll 1
            for (int part = 0; part < (lim ? 0 : 3); part++) {
#pragma unroll
                for (int r = 0; r <= RL; r++)
                    if (r / 8 == part) {
                        sts32_if(true, tmp + (r & 7) * (16 * MBC * 4), ss[r]);
                        sts32_if(true, tmp + ((r & 7) * 2 + 1) * (8 * MBC * 4), rk[r]);
                    }
#pragma unroll 1
                for (int r = part * 8; r < min(part * 8 + 8, RL + 1); r++) {
                    const uint32_t w = lds32(tmp + (r & 7) * (16 * MBC * 4)), p = lds32(tmp + ((r & 7) * 2 + 1) * (8 * MBC * 4));
                    const uint32_t rnk = r < RL ? lane : 32 + (lane & 15), fr = r < RL ? r : from, gw = (w >> 25 & 31) - 1;
                    const uint32_t ri = __shfl_sync(0xffffffffu, dof, fr) + rnk, gi = __shfl_sync(0xffffffffu, loc & 0xfff, fr) + rnk;
                    const bool fits = p - gw * (GK * 16) < __shfl_sync(0xffffffffu, cap, gw) * 16;
                    if (p < 0x20000) {
                        sts32_if(fits, sb + SM_KSG + p, min(ri, RCAP) << 18 | (w & 0x3ffffu));
                        if (!fits || ri >= RCAP) excess(w, (wl + 8 * fr) * SLICE + gi);
                    }
                }
            }
        }
        STAMPT(13, NH);
        bar_sync<8, NH + 32>();
        STAMPT(31, NH);
        const uint4 lt = lds128(sb + SM_LT + 128 + wl * 16), lo = lds128(sb + SM_LT + 256 + wl * 16);
        const uint32_t lb = lt.w, len = lt.z, le = lb + len;
        if (__builtin_expect(len <= 96, 1)) build_list<3>(lt, lo, wl, lane, N, bin_magic, pace);
        else build_list<4>(lt, lo, wl, lane, N, bin_magic, pace);
        STAMPT(27, NH);
        if (PSU) asm volatile("setmaxnreg.dec.sync.aligned.u32 24;");
        bar_arrive<2, NT>();
        const uint32_t z = lds32(sb + SM_ZERO + (lane & 3) * 4);
        const uint32_t bytes = opaque(4096 + z);
        const uint4 z0 = lds128v(sb + SM_ZERO);
        const uint2 tm = lds64(sb + SM_MISC + 24);
        bar_sync<5, NT>();
        STAMPT(6, NH);
        if (!PSU) asm volatile("setmaxnreg.dec.sync.aligned.u32 24;");
        if (elect_one()) {
            uint32_t ka = sb + SM_LIST + lb * 16 - 16 * (S - 1);
            int row = ((1 + wl) * NCTA + cta) * PFR;
            asm volatile(PRODUCER_PTX : "+r"(ka), "+r"(row)
                : "r"(ring), "r"(bars), "l"((uint64_t)tm.y << 32 | tm.x),
                  "r"(z0.x), "r"(z0.y), "r"(z0.z), "r"(z0.w), "r"(pos), "r"(ka + len * 16), "r"(lds32v(sb + SM_MISC + 4)), "r"(bytes),
                  "l"(x), "r"(N), "n"(RSTR), "n"(SM_SRC - SM_LIST + 16 * (S - 1)), "n"(PFA), "n"(PFR), "n"(NW * NCTA * PFR) : "memory");
            STAMPT(20, NW * 32);
            for (int guard = 0; lds32v(pos) + 16 * (S - 1) < sb + SM_LIST + le * 16 && guard < (1 << 20); guard++) __nanosleep(NSLEEP);
            const uint32_t d = ring + (len - ((len * SMG) >> 16) * S) * 1024;
            sts32_if(true, sb + SM_MISC + 32 + wl * 4, (d - (sb + SM_RING)) >> 4);
            asm volatile("mbarrier.arrive.expect_tx.shared::cta.b64 _, [%0], 4096;" ::"r"(bar_w) : "memory");
#pragma unroll
            for (uint32_t r = 0; r < 8; r++)
                asm volatile("cp.async.bulk.tensor.5d.shared::cluster.global.tile.mbarrier::complete_tx::bytes [%0], [%1, {%2, %3, %4, %5, %6}], [%7];"
                             ::"r"(d + (r >> 1) * RSTR + (r & 1) * 512), "l"(((uint64_t)tm.y << 32 | tm.x) + sizeof(CUtensorMap)), "r"((r >> 2) * 64), "r"((r >> 1) & 1),
                               "r"((wl >> 1) & 2), "r"(((r ^ (wl >> 1)) & 1) + (wl & 1) * 2), "r"(wl & 2), "r"(bar_w) : "memory");
            STAMPT(21, NW * 32);
        }
        return;
    }

    {
        if (MODE == 2) { load_weights(); weights(); }
        if (warp < NW - 1) bar_sync<4, NT - 32>();
        if (warp == 0) {
            const uint32_t key = lds32(sb + SM_KEY + lane * 4);
            int rank = 0;
#pragma unroll
            for (int j = 0; j < 4; j++) {
                const uint4 o = lds128(sb + SM_KEY + (lane & 16) * 4 + j * 16);
                rank += ((key - o.x) >> 31) + ((key - o.y) >> 31) + ((key - o.z) >> 31) + ((key - o.w) >> 31);
            }
            const int n2 = 2 * __popc(__ballot_sync(0xffffffffu, key < 32) & 0xff0000);
            const int other = (rank < n2 ? n2 - 1 : 15 + n2) - rank;
            const int li = lane >= 16 ? 7 - rank : min(rank, other) - (rank < n2 ? 0 : n2 / 2);
            sts32_if(lane < NG, sb + SM_LT + (li < 4 ? li : 11 - li) * 16 + (lane >= 16 ? 8 : rank < other ? 0 : 4), min(key >> 5, group_cap(key, lane)) << 5 | lane);
            __syncwarp();
            const uint4 lt = lds128(sb + SM_LT + (lane & 7) * 16);
            const uint32_t len = (lt.x >> 5) + (lt.y >> 5) + (lt.z >> 5);
            uint32_t le = len + 1;
#pragma unroll
            for (int o = 1; o < 8; o <<= 1) scan_step(le, o);
            le -= 1;
            const uint32_t n0 = lt.x >> 5, n01 = n0 + (lt.y >> 5);
            sts128_if(lane < 2 * NW, sb + SM_LT + 128 + lane * 16, lane < NW ? make_uint4(n0, n01, len, le - len) :
                      make_uint4((lt.x & 31) * (GK * 16), ((lt.y & 31) * GK - n0) * 16, ((lt.z & 31) * GK - n01) * 16, 0));
            bar_arrive<8, NH + 32>();
            if (lane < NW) {
                sts32_if(true, sb + SM_LIST + le * 16 + 12, bar_rec);
                sts32_if(true, bar_w + 32 + lane * 4, sb + SM_LIST + (le - len) * 16);
                sts32_if(true, sb + SM_MISC + 64 + lane * 4, (lt.x & 31) | (lt.y & 31) << 5 | (lt.z & 31) << 10 | len << 16);
            }
        }
        uint4 cp = make_uint4(0, 0, 0, 0);
        if (warp > 0 && warp < NW - 1 && lane < NCTA / 6) cp = lds128(sb + SM_CPY + (warp - 1 + 6 * lane) * 16);
        const uint32_t total = __reduce_add_sync(0xffffffffu, cp.w);
        bar_arrive<5, NT>();
        if (lane == 0) asm volatile("mbarrier.arrive.expect_tx.shared::cta.b64 _, [%0], %1;" ::"r"(bar_rec), "r"(total) : "memory");
        unsigned todo = __ballot_sync(0xffffffffu, cp.w);
        for (int guard = 0; todo && guard < (1 << 22); guard++) {
            const unsigned go = MODE == 3 ? todo & lds32v(sb + SM_MISC + 92 + warp * 4) : todo;
            if (go) {
                asm volatile("fence.proxy.async.global;" ::: "memory");
                if (go >> lane & 1)
                    asm volatile("cp.async.bulk.shared::cluster.global.mbarrier::complete_tx::bytes [%0], [%1], %2, [%3];"
                                 ::"r"(cp.z), "l"((uint64_t)cp.y << 32 | cp.x), "r"(cp.w), "r"(bar_rec) : "memory");
                todo ^= go;
            } else {
                __nanosleep(20);
            }
        }
        STAMPT(23, 32);
        if (tid == 0) prefetch_x(0);
        if (MODE == 3 && cta == 0 && tid == 0) {
            scr->epoch = tag;
            scr->sent[~tag & 1] = 0;
            for (int i = 0; i < 9; i++) scr->sent2[~tag & 1][i] = 0;
        }
        STAMP(22);
        if (tid == 0 && cta < 128) asm volatile("cp.async.bulk.prefetch.L2.global [%0], 256;" ::"l"(w_mix + cta * 128));
        bar_sync<2, NT>();
        asm volatile("setmaxnreg.inc.sync.aligned.u32 232;" ::: "memory");
        STAMP(14);
    }

    float acc[40][4];
    const uint32_t z = lds32(sb + SM_ZERO + t * 4);
#pragma unroll
    for (int j = 0; j < 40; j++) acc[j][0] = acc[j][1] = acc[j][2] = acc[j][3] = 0.f;
    const bool bact = (g & 1) == (t >> 1);
    mbar_wait(bar_rec, 0);
    STAMP(9);
    {
        auto keep = [&](uint32_t v) { return __shfl_sync(0xffffffffu, v + z, lane); };
        const uint32_t va0 = keep(ring + t * RSTR + (g & 2) * 128 + (g & 1) * 16 + ((((g >> 1) & 2) ^ ((((g >> 1) & 1) + t) & 3)) << 5));
        const uint32_t hm0 = keep(HM0(g >> 2)), hm1 = keep(0x40000u << (g >> 2)), sel = keep(0x1010u + (g >> 1) * 0x22 + t * 0x2200);
        const uint32_t rl = keep(bact ? (t & 1) * 8 : SM_ZERO - SM_REC), rm = keep(bact ? 0xfff0u : 0u);
        uint32_t lp = keep(lds32(pos));
        for (;;) {
        asm volatile(MAIN_LOOP_PTX : MAIN_LOOP_ACC(acc), "+r"(lp)
            : "r"(wz[0][0]), "r"(wz[0][1]), "r"(wz[1][0]), "r"(wz[1][1]), "r"(wz[2][0]), "r"(wz[2][1]), "r"(wz[3][0]), "r"(wz[3][1]),
              "r"(wt[0]), "r"(wt[1]), "r"(va0), "r"(hm0), "r"(hm1), "r"(rl), "r"(rm), "r"(sel), "r"(pos), "n"(sb + SM_REC)
            : "memory");
            sts32_if(true, sb + SM_ZERO + 96, lp);
            const uint2 left = lds64(sb + SM_MISC + 8);
            if (__builtin_expect(!(left.x | left.y), 1)) break;
            if (!next_excess(scr, x, va0)) break;
            lp = sb + SM_SRC + wl * 96 + (sel & 1);
        }
    }
    STAMP(7);
    const uint32_t grp = lds32(sb + SM_MISC + 64 + wl * 4);

    uint32_t aq[3][8][4];
    auto pack = [&](int j) {
#pragma unroll
        for (int m = 0; m < 8; m++) {
            if (j < 2) {
#pragma unroll
                for (int q = 0; q < 4; q++) {
                    const float* a = acc[16 * j + 2 * m + (q >> 1)] + (q & 1) * 2;
                    asm volatile("cvt.rn.bf16x2.f32 %0, %1, %2;" : "=r"(aq[j][m][q]) : "f"(a[~m & 1]), "f"(a[m & 1]));
                }
            } else {
                aq[2][m][0] = movm(pack_bf16(acc[32 + m][0], acc[32 + m][1]));
                aq[2][m][2] = movm(pack_bf16(acc[32 + m][2], acc[32 + m][3]));
                if (m & 1) {
                    aq[2][m][0] = __byte_perm(aq[2][m][0], 0, 0x1032);
                    aq[2][m][2] = __byte_perm(aq[2][m][2], 0, 0x1032);
                }
                aq[2][m][1] = aq[2][m][3] = 0;
#pragma unroll
                for (int q = 0; q < 4; q++) asm volatile("" : "+r"(aq[2][m][q]));
            }
        }
    };
    pack(0);
    STAMP(16);
    mbar_wait(bar_w, 0);
    STAMP(17);
    const uint4 ws0 = lds128(sb + SM_MISC + 32), ws1 = lds128(sb + SM_MISC + 48);
    const uint32_t ws[8] = {ws0.x, ws0.y, ws0.z, ws0.w, ws1.x, ws1.y, ws1.z, ws1.w};
    const uint64_t wdesc = ((sb + SM_RING) >> 4) | ((uint64_t)(2 * RSTR >> 4) << 16) | ((uint64_t)(RSTR >> 4) << 32) | (1ull << 62);
    const int nloc = min(npc, N - cta * npc);
    uint32_t ln;
    asm volatile("mov.u32 %0, %laneid;" : "=r"(ln));
    const bool odd = ln & 1;
    const int hi = ln >> 1 & 1;
    uint2* op = reinterpret_cast<uint2*>(out) + (size_t)(cta * npc) * 128 + (ln >> 2) + (ln & 1) * 8;
    float d[2][32];
    auto mix = [&](int job) {
        asm volatile("wgmma.fence.sync.aligned;" ::: "memory");
#pragma unroll
        for (int m = 0; m < 8; m++) wgmma_n64(d[job & 1], aq[job >> 1][m], wdesc + ws[m] + (job & 1) * (2 * RSTR >> 4), m);
        asm volatile("wgmma.commit_group.sync.aligned;" ::: "memory");
    };
    mix(0);
    if (nloc > NCTA) __trap();
    pack(1);
    pack(2);
#pragma unroll
    for (int job = 0; job < 6; job++) {
        if (nloc + 2 * job + 1 > NCTA) __trap();
        asm volatile("wgmma.wait_group.sync.aligned 0;" ::: "memory");
        if (job == 0) STAMP(18);
        if (job == 4) STAMP(19);
        float (&dd)[32] = d[job & 1];
#pragma unroll
        for (int k = 0; k < 32; k++) asm volatile("" : "+f"(dd[k]));
        if (job < 5) mix(job + 1);
        if (job > 0 && nloc + 2 * job + 2 > NCTA) __trap();
#pragma unroll
        for (int h = 0; h < (job < 4 ? 2 : 1); h++) {
            const int gj = grp >> (5 * (job >> 1)) & 31;
            const int l = job < 4 ? gj * 4 + 2 * h + hi : gj * 2 + 32 + hi;
            const bool ok = l < nloc;
#pragma unroll
            for (int j = 0; j < 8; j += 2) {
                const uint32_t p0 = movm(pack_bf16(dd[4 * j + 2 * h], dd[4 * j + 2 * h + 1])), p1 = movm(pack_bf16(dd[4 * j + 4 + 2 * h], dd[4 * j + 5 + 2 * h]));
                const uint32_t rv = __shfl_xor_sync(0xffffffffu, odd ? p0 : p1, 1);
                if (ok) op[l * 128 + (job & 1) * 64 + j * 8] = odd ? make_uint2(rv, p1) : make_uint2(p0, rv);
            }
        }
    }
    __syncwarp();
    ANCHOR(1);
}

}

extern "C" void kernel_launch(void* const* d_in, const int* in_sizes, int n_in, void* d_out, int out_size) {
    const __nv_bfloat16* x     = (const __nv_bfloat16*)d_in[0];
    const int*           src   = (const int*)d_in[1];
    const int*           dst   = (const int*)d_in[2];
    const uint2*         Y     = (const uint2*)d_in[3];
    const uint2*         ef    = (const uint2*)d_in[4];
    const __nv_bfloat16* w_rad = (const __nv_bfloat16*)d_in[5];
    const __nv_bfloat16* cg    = (const __nv_bfloat16*)d_in[6];
    const __nv_bfloat16* w_mix = (const __nv_bfloat16*)d_in[7];
    __nv_bfloat16*       out   = (__nv_bfloat16*)d_out;
    const int N = in_sizes[0] / 512;
    const int E = in_sizes[1];

    static int n_sm = 0;
    static Scratch* scr = nullptr;
    static decltype(&cuTensorMapEncodeTiled) encode = nullptr;
    if (n_sm == 0) {
        cudaDriverEntryPointQueryResult qr;
        cudaGetDriverEntryPoint("cuTensorMapEncodeTiled", (void**)&encode, cudaEnableDefault, &qr);
        cudaGetSymbolAddress((void**)&scr, g_scr);
        int dev = 0;
        cudaGetDevice(&dev);
        cudaDeviceGetAttribute(&n_sm, cudaDevAttrMultiProcessorCount, dev);
        cudaFuncSetAttribute(tfn_kernel<1>, cudaFuncAttributeMaxDynamicSharedMemorySize, SM_TOTAL);
        cudaFuncSetAttribute(tfn_kernel<2>, cudaFuncAttributeMaxDynamicSharedMemorySize, SM_TOTAL);
        cudaFuncSetAttribute(tfn_kernel<3>, cudaFuncAttributeMaxDynamicSharedMemorySize, SM_TOTAL);
    }
    CUtensorMap xmap;
    {
        const cuuint64_t dims[2] = {64, (cuuint64_t)N * 8}, strides[1] = {128};
        const cuuint32_t box[2] = {64, 8}, es[2] = {1, 1};
        encode(&xmap, CU_TENSOR_MAP_DATA_TYPE_BFLOAT16, 2, (void*)x, dims, strides, box, es, CU_TENSOR_MAP_INTERLEAVE_NONE,
               CU_TENSOR_MAP_SWIZZLE_128B, CU_TENSOR_MAP_L2_PROMOTION_NONE, CU_TENSOR_MAP_FLOAT_OOB_FILL_NONE);
    }
    CUtensorMap wmap;
    {
        const cuuint64_t dims[5] = {128, 2, 4, 4, 4}, strides[4] = {256, 512, 2048, 8192};
        const cuuint32_t box[5] = {64, 1, 2, 1, 2}, es[5] = {1, 1, 1, 1, 1};
        encode(&wmap, CU_TENSOR_MAP_DATA_TYPE_BFLOAT16, 5, (void*)w_mix, dims, strides, box, es, CU_TENSOR_MAP_INTERLEAVE_NONE,
               CU_TENSOR_MAP_SWIZZLE_128B, CU_TENSOR_MAP_L2_PROMOTION_NONE, CU_TENSOR_MAP_FLOAT_OOB_FILL_NONE);
    }
    const int slice = ((E + NCTA - 1) / NCTA + 3) / 4 * 4;
    const int npc   = (N + NCTA - 1) / NCTA;
    const uint32_t npc_magic = (uint32_t)((0x100000000ull + npc - 1) / npc);
    const uint32_t bin_magic = (uint32_t)((1ull << 25) / N);
    const double want = PDT * (double)E / (32.0 * N);
    const uint32_t pace = (uint32_t)((want < 1 ? 1 : want > 94 ? 94 : want) * (1 << 25));
    cudaStream_t st = cudaStreamPerThread;
    if (n_sm >= NCTA) {
        tfn_kernel<3><<<NCTA, NT, SM_TOTAL, st>>>(dst, src, scr, E, slice, N, npc, npc_magic, bin_magic, Y, ef, w_rad, cg, x, w_mix, out, pace, xmap, wmap);
    } else {
        tfn_kernel<1><<<NCTA, NT, SM_TOTAL, st>>>(dst, src, scr, E, slice, N, npc, npc_magic, bin_magic, Y, ef, w_rad, cg, x, w_mix, out, pace, xmap, wmap);
        tfn_kernel<2><<<NCTA, NT, SM_TOTAL, st>>>(dst, src, scr, E, slice, N, npc, npc_magic, bin_magic, Y, ef, w_rad, cg, x, w_mix, out, pace, xmap, wmap);
    }
}
```

```cpp
#include <cuda.h>
#include <cuda_runtime.h>
#include <cuda_bf16.h>
#include <stdint.h>

namespace {

constexpr int NCTA   = 132;
constexpr int NW     = 8;
constexpr int NT     = 2 * NW * 32;
constexpr int RA     = 5;
constexpr int SLICE  = RA * NT;
constexpr int MBC    = 48;
constexpr int MBE    = MBC - 1;
constexpr int MBW    = NCTA * MBC;
constexpr int ASTR   = MBC + 4;
constexpr int NH     = NW * 32;
constexpr int RL     = 17;
constexpr int NG     = 24;
constexpr int KCAP   = 676;
constexpr int RCAP   = 2752;
constexpr int GK     = 48;
constexpr int NBIN   = 128;
constexpr int BSH    = 18;
constexpr int LBIN   = 128;
constexpr int S      = 5;
constexpr int SMG    = (65535 + S) / S;
constexpr int LCAP   = KCAP + NW + 4;

constexpr uint32_t sb = 1024;
constexpr int SM_RING = 0;
constexpr int RSTR    = NW * S * 1024 + 256;
constexpr int SM_REC  = SM_RING + 4 * RSTR;
constexpr int SM_ZERO = SM_REC + RCAP * 16;
constexpr int SM_LIST = SM_ZERO + 128;
constexpr int SM_MISC = SM_LIST + LCAP * 16;
constexpr int SM_STATE = SM_MISC + 256;
constexpr int SM_BAR  = SM_STATE + 128;
constexpr int SM_SRC  = SM_BAR + NW * S * 8 + 96;
constexpr int SM_SEG  = SM_SRC + LCAP * 16;
constexpr int SM_TOTAL = SM_SEG + NCTA * 4;
constexpr int SM_AREC = SM_RING;
constexpr int SM_AP   = SM_AREC + (SLICE + 80) * 16;
constexpr int SM_AMB  = SM_AP + NH * 12;
constexpr int SM_AOFF = SM_AMB + (NCTA + 32) * ASTR * 4;
constexpr int SM_DUM  = SM_AOFF + 672;
constexpr int SM_BIN  = SM_DUM + NBIN * 4;
constexpr int SM_HIST = SM_BIN + NG * NBIN * 4;
constexpr int SM_KEY  = SM_HIST + 672;
constexpr int SM_LH   = SM_KEY + 128;
constexpr int SM_KSG  = SM_LH + NW * LBIN * 4;
constexpr int SM_CPY  = SM_KSG + NG * GK * 16;
constexpr int SM_DOFF = SM_CPY + NH * 16;
constexpr int SM_LT   = SM_DOFF + NH * 4;
constexpr int SM_RAWY = SM_REC;
constexpr int SM_RAWF = SM_RAWY + SLICE * 8;
static_assert(NW * (RL + 1) * MBC * 4 <= SM_AOFF - SM_AMB && SM_LT + 384 <= SM_REC && SM_RAWF + SLICE * 8 <= SM_ZERO, "temporaries must fit");
static_assert(SM_TOTAL <= 232448, "smem");
static_assert(SM_AMB % 128 == 0 && SM_LIST % 128 == 0 && SM_BAR % 128 == 0 && SM_HIST % 16 == 0 && SM_BIN % 16 == 0 && SM_MISC % 16 == 0 && SM_KSG % 16 == 0, "align");
static_assert(NCTA % 6 == 0 && NCTA <= RL * NW && SM_SRC + NW * 96 - SM_REC < 65536 && LBIN == 128 && SM_SRC % 16 == 0 && SM_ZERO % 128 == 0, "layout");

struct Scratch {
    uint4    rec[NCTA * SLICE];
    uint32_t mb[NCTA * MBW];
    uint32_t ss[NCTA * SLICE];
    uint2    exc[NCTA * MBW];
    uint32_t epoch;
    uint32_t sent[2];
    uint32_t gap[61];
    uint32_t sent2[2][16];
};
__device__ __align__(128) Scratch g_scr;


__device__ __forceinline__ uint32_t pack_bf16(float lo, float hi) {
    __nv_bfloat162 v = __floats2bfloat162_rn(lo, hi);
    return *reinterpret_cast<uint32_t*>(&v);
}
__device__ __forceinline__ uint4 lds128(uint32_t addr) {
    uint4 v;
    asm volatile("ld.shared.v4.u32 {%0,%1,%2,%3}, [%4];" : "=r"(v.x), "=r"(v.y), "=r"(v.z), "=r"(v.w) : "r"(addr) : "memory");
    return v;
}
__device__ __forceinline__ uint32_t movm(uint32_t v) {
    uint32_t r;
    asm volatile("movmatrix.sync.aligned.m8n8.trans.b16 %0, %1;" : "=r"(r) : "r"(v));
    return r;
}
__device__ __forceinline__ void cp16(uint32_t dst, const void* src) {
    asm volatile("cp.async.cg.shared.global [%0], [%1], 16;" ::"r"(dst), "l"(src) : "memory");
}
__device__ __forceinline__ uint4 ldg128_relaxed(const uint4* p) {
    uint4 v;
    asm volatile("ld.relaxed.gpu.global.v4.u32 {%0,%1,%2,%3}, [%4];" : "=r"(v.x), "=r"(v.y), "=r"(v.z), "=r"(v.w) : "l"(p) : "memory");
    return v;
}
__device__ __forceinline__ uint32_t atoms_inc(uint32_t addr) {
    uint32_t v;
    asm volatile("atom.shared.add.u32 %0, [%1], 1;" : "=r"(v) : "r"(addr) : "memory");
    return v;
}
__device__ __forceinline__ uint32_t lds32(uint32_t addr) {
    uint32_t v;
    asm volatile("ld.shared.u32 %0, [%1];" : "=r"(v) : "r"(addr) : "memory");
    return v;
}
__device__ __forceinline__ void sts32_if(bool p, uint32_t addr, uint32_t v) {
    asm volatile("{\n\t.reg .pred p;\n\tsetp.ne.u32 p, %2, 0;\n\t@p st.shared.u32 [%0], %1;\n\t}"
                 ::"r"(addr), "r"(v), "r"((uint32_t)p) : "memory");
}
__device__ __forceinline__ uint32_t lds32v(uint32_t addr) {
    uint32_t v;
    asm volatile("ld.volatile.shared.u32 %0, [%1];" : "=r"(v) : "r"(addr) : "memory");
    return v;
}
__device__ __forceinline__ uint32_t timer32() {
    uint32_t c;
    asm volatile("mov.u32 %0, %globaltimer_lo;" : "=r"(c));
    return c;
}
__device__ __forceinline__ uint32_t opaque(uint32_t v) {
    asm volatile("" : "+r"(v));
    return v;
}
__device__ __forceinline__ void mbar_wait(uint32_t bar, uint32_t parity) {
    asm volatile("{\n\t.reg .pred p;\n\t.reg .b32 n;\n\tmov.b32 n, 0;\n"
                 "AGAIN:\n\tmbarrier.try_wait.parity.shared::cta.b64 p, [%0], %1;\n\t@p bra.uni THERE;\n\t"
                 "add.u32 n, n, 1;\n\tsetp.lt.u32 p, n, 1048576;\n\t@p bra.uni AGAIN;\n"
                 "THERE:\n\t}" ::"r"(bar), "r"(parity) : "memory");
}
__device__ __forceinline__ void mbar_init(uint32_t bar, uint32_t count) {
    asm volatile("mbarrier.init.shared::cta.b64 [%0], %1;" ::"r"(bar), "r"(count) : "memory");
}
__device__ __forceinline__ uint32_t atoms_add(uint32_t addr, uint32_t x) {
    uint32_t v;
    asm volatile("atom.shared.add.u32 %0, [%1], %2;" : "=r"(v) : "r"(addr), "r"(x) : "memory");
    return v;
}
__device__ __forceinline__ uint2 lds64(uint32_t addr) {
    uint2 v;
    asm volatile("ld.shared.v2.u32 {%0,%1}, [%2];" : "=r"(v.x), "=r"(v.y) : "r"(addr) : "memory");
    return v;
}
__device__ __forceinline__ void sts128_if(bool p, uint32_t addr, uint4 v) {
    asm volatile("{\n\t.reg .pred p;\n\tsetp.ne.u32 p, %5, 0;\n\t@p st.shared.v4.u32 [%0], {%1,%2,%3,%4};\n\t}"
                 ::"r"(addr), "r"(v.x), "r"(v.y), "r"(v.z), "r"(v.w), "r"((uint32_t)p) : "memory");
}
__device__ __forceinline__ void scan_step(uint32_t& v, int o) {
    asm volatile("{\n\t.reg .pred p;\n\t.reg .b32 u;\n\tshfl.sync.up.b32 u|p, %0, %1, 0, 0xffffffff;\n\t@p add.u32 %0, %0, u;\n\t}" : "+r"(v) : "r"(o));
}
__device__ __forceinline__ uint32_t warp_incl_scan(uint32_t v) {
#pragma unroll
    for (int o = 1; o < 32; o <<= 1) scan_step(v, o);
    return v;
}
__device__ __forceinline__ bool elect_one() {
    uint32_t ok;
    asm volatile("{\n\t.reg .pred p;\n\telect.sync _|p, 0xffffffff;\n\tselp.u32 %0, 1, 0, p;\n\t}" : "=r"(ok));
    return ok;
}
__host__ __device__ constexpr int chunk_of(int m, int g) {
    return ((m & 1) + (g & 2) + 2 * (m & 2)) * 8 + ((g ^ m) & 1) + ((m >> 2) & 1) * 2 + 4 * (((g >> 2) ^ (m >> 1)) & 1);
}
__device__ __forceinline__ uint4 lds128v(uint32_t addr) {
    uint4 v;
    asm volatile("ld.volatile.shared.v4.u32 {%0,%1,%2,%3}, [%4];" : "=r"(v.x), "=r"(v.y), "=r"(v.z), "=r"(v.w) : "r"(addr) : "memory");
    return v;
}
#define HM0(h) (0x10000u << (h))
#define MAIN_LOOP_PTX \
    "{\n" \
    ".reg .b32 v<16>, a<4>, u<4>, b<2>, c<2>, w<4>, ca0, ca1, na0, na1, ef, rx, ry, ex, ey, e0, e1, e3, gx, gy, cnt;\n" \
    ".reg .f32 z<16>, t<8>, y<4>, fz;\n" \
    ".reg .b16 h<2>;\n" \
    ".reg .pred pa, pr, p<2>, q<3>, s<2>;\n" \
    "mov.f32 fz, 0f00000000;\n" \
    "setp.ne.u32 pa, %175, 0; mov.b32 rx, 0; mov.b32 ry, 0;\n" \
    "ld.shared.v4.u32 {e0,e1,ex,e3}, [%160];\n" \
    "prmt.b32 ey, e0, e1, %176;\n" \
    "lop3.b32 u2, ey, 0xfff0, %174, 0xea; @pa ld.shared.v2.u32 {rx,ry}, [u2+%178];\n" \
    "and.b32 u2, ey, %172; setp.ne.u32 p0, u2, 0; and.b32 u2, ey, %173; setp.ne.u32 p1, u2, 0;\n" \
    "shr.u32 u2, ex, 16; add.u32 na0, %171, u2;\n" \
    "mma.sync.aligned.m16n8k8.row.col.f32.bf16.bf16.f32 {y0,y1,y2,y3}, {%169,%170}, {ry}, {fz,fz,fz,fz};\n" \
    "cvt.rn.bf16x2.f32 b0, y2, y0; cvt.rn.bf16x2.f32 b1, y3, y1;\n" \
    "selp.b32 a0, b0, 0, p0; selp.b32 a1, b0, 0, p1; selp.b32 a2, b1, 0, p0; selp.b32 a3, b1, 0, p1;\n" \
    "mma.sync.aligned.m16n8k8.row.col.f32.bf16.bf16.f32 {z0,z1,z2,z3}, {%161,%162}, {rx}, {fz,fz,fz,fz};\n" \
    "mma.sync.aligned.m16n8k8.row.col.f32.bf16.bf16.f32 {z4,z5,z6,z7}, {%163,%164}, {rx}, {fz,fz,fz,fz};\n" \
    "mma.sync.aligned.m16n8k8.row.col.f32.bf16.bf16.f32 {z8,z9,z10,z11}, {%165,%166}, {rx}, {fz,fz,fz,fz};\n" \
    "tanh.approx.f32 t0, z0; tanh.approx.f32 t1, z2;\n" \
    "fma.rn.f32 z0, z0, t0, z0; fma.rn.f32 z2, z2, t1, z2;\n" \
    "tanh.approx.f32 t2, z1; tanh.approx.f32 t3, z3;\n" \
    "fma.rn.f32 z1, z1, t2, z1; fma.rn.f32 z3, z3, t3, z3;\n" \
    "tanh.approx.f32 t4, z4; tanh.approx.f32 t5, z6;\n" \
    "fma.rn.f32 z4, z4, t4, z4; fma.rn.f32 z6, z6, t5, z6;\n" \
    "tanh.approx.f32 t6, z5; tanh.approx.f32 t7, z7;\n" \
    "ld.shared.v4.u32 {e0,e1,ex,e3}, [%160+16];\n" \
    "mov.u32 cnt, %%globaltimer_hi; st.shared.u32 [%177+32], cnt;\n" \
    "bra.uni SLOW;\n" \
    "S2:\n" \
    "add.u32 %160, %160, 16;\n" \
    "mov.b32 ca0, na0; xor.b32 ca1, na0, 32; mov.b32 ef, rx;\n" \
    "or.b32 c0, a0, a1; or.b32 c1, a2, a3;\n" \
    "prmt.b32 ey, e0, e1, %176;\n" \
    "and.b32 u2, ey, %172; setp.ne.u32 p0, u2, 0; and.b32 u2, ey, %173; setp.ne.u32 p1, u2, 0;\n" \
    "lop3.b32 u2, ey, 0xfff0, %174, 0xea; @pa ld.shared.v2.u32 {rx,ry}, [u2+%178];\n" \
    "tanh.approx.f32 t0, z8;\n" \
    "mov.b32 {h0,h1}, z0; mov.b32 u1, {h1,h1}; mul.bf16x2 w1, v1, u1;\n" \
    "fma.rn.f32 z5, z5, t6, z5;\n" \
    "ld.shared.v4.u32 {v12,v13,v14,v15}, [ca0+640];\n" \
    "tanh.approx.f32 t1, z10;\n" \
    "mov.b32 {h0,h1}, z0; mov.b32 u1, {h1,h1}; mul.bf16x2 w0, v0, u1;\n" \
    "mov.b32 {h0,h1}, z2; mov.b32 u1, {h1,h1}; mul.bf16x2 w3, v3, u1;\n" \
    "fma.rn.f32 z7, z7, t7, z7;\n" \
    "mov.b32 {h0,h1}, z2; mov.b32 u1, {h1,h1}; mul.bf16x2 w2, v2, u1;\n" \
    "tanh.approx.f32 t2, z9;\n" \
    "fma.rn.f32 z8, z8, t0, z8;\n" \
    "mma.sync.aligned.m16n8k16.row.col.f32.bf16.bf16.f32 {%128,%129,%130,%131}, {w0,w2,w1,w3}, {c0,c1}, {%128,%129,%130,%131};\n" \
    "ld.shared.v4.u32 {v0,v1,v2,v3}, [ca1+0];\n" \
    "mov.b32 {h0,h1}, z1; mov.b32 u1, {h1,h1}; mul.bf16x2 w1, v5, u1;\n" \
    "fma.rn.f32 z10, z10, t1, z10;\n" \
    "mov.b32 {h0,h1}, z3; mov.b32 u1, {h1,h1}; mul.bf16x2 w2, v6, u1;\n" \
    "mov.b32 {h0,h1}, z3; mov.b32 u1, {h1,h1}; mul.bf16x2 w3, v7, u1;\n" \
    "tanh.approx.f32 t3, z11;\n" \
    "mov.b32 {h0,h1}, z1; mov.b32 u1, {h1,h1}; mul.bf16x2 w0, v4, u1;\n" \
    "mma.sync.aligned.m16n8k16.row.col.f32.bf16.bf16.f32 {%132,%133,%134,%135}, {w0,w2,w1,w3}, {c0,c1}, {%132,%133,%134,%135};\n" \
    "mma.sync.aligned.m16n8k8.row.col.f32.bf16.bf16.f32 {z12,z13,z14,z15}, {%167,%168}, {ef}, {fz,fz,fz,fz};\n" \
    "tanh.approx.f32 t4, z12;\n" \
    "tanh.approx.f32 t5, z14;\n" \
    "ld.shared.v4.u32 {v4,v5,v6,v7}, [ca1+128];\n" \
    "mov.b32 {h0,h1}, z4; mov.b32 u1, {h1,h1}; mul.bf16x2 w0, v8, u1;\n" \
    "fma.rn.f32 z9, z9, t2, z9;\n" \
    "mov.b32 {h0,h1}, z6; mov.b32 u1, {h1,h1}; mul.bf16x2 w2, v10, u1;\n" \
    "mov.b32 {h0,h1}, z6; mov.b32 u1, {h1,h1}; mul.bf16x2 w3, v11, u1;\n" \
    "mov.b32 {h0,h1}, z4; mov.b32 u1, {h1,h1}; mul.bf16x2 w1, v9, u1;\n" \
    "fma.rn.f32 z11, z11, t3, z11;\n" \
    "mma.sync.aligned.m16n8k16.row.col.f32.bf16.bf16.f32 {%136,%137,%138,%139}, {w0,w2,w1,w3}, {c0,c1}, {%136,%137,%138,%139};\n" \
    "tanh.approx.f32 t6, z13;\n" \
    "fma.rn.f32 z12, z12, t4, z12;\n" \
    "mov.b32 {h0,h1}, z5; mov.b32 u1, {h1,h1}; mul.bf16x2 w0, v12, u1;\n" \
    "tanh.approx.f32 t7, z15;\n" \
    "fma.rn.f32 z14, z14, t5, z14;\n" \
    "ld.shared.v4.u32 {v8,v9,v10,v11}, [ca1+512];\n" \
    "mov.b32 {h0,h1}, z5; mov.b32 u1, {h1,h1}; mul.bf16x2 w1, v13, u1;\n" \
    "mov.b32 {h0,h1}, z7; mov.b32 u1, {h1,h1}; mul.bf16x2 w3, v15, u1;\n" \
    "mov.b32 {h0,h1}, z7; mov.b32 u1, {h1,h1}; mul.bf16x2 w2, v14, u1;\n" \
    "mma.sync.aligned.m16n8k16.row.col.f32.bf16.bf16.f32 {%140,%141,%142,%143}, {w0,w2,w1,w3}, {c0,c1}, {%140,%141,%142,%143};\n" \
    "shr.u32 u2, ex, 16; add.u32 na0, %171, u2;\n" \
    "mma.sync.aligned.m16n8k8.row.col.f32.bf16.bf16.f32 {z0,z1,z2,z3}, {%161,%162}, {rx}, {fz,fz,fz,fz};\n" \
    "tanh.approx.f32 t0, z0;\n" \
    "ld.shared.v4.u32 {v12,v13,v14,v15}, [ca1+640];\n" \
    "mov.b32 {h0,h1}, z8; mov.b32 u1, {h1,h1}; mul.bf16x2 w1, v1, u1;\n" \
    "fma.rn.f32 z15, z15, t7, z15;\n" \
    "fma.rn.f32 z13, z13, t6, z13;\n" \
    "mov.b32 {h0,h1}, z10; mov.b32 u1, {h1,h1}; mul.bf16x2 w3, v3, u1;\n" \
    "mov.b32 {h0,h1}, z8; mov.b32 u1, {h1,h1}; mul.bf16x2 w0, v0, u1;\n" \
    "tanh.approx.f32 t1, z2;\n" \
    "and.b32 u2, ex, 1; mbarrier.try_wait.parity.shared::cta.b64 pr, [e3], u2;\n" \
    "mov.b32 {h0,h1}, z10; mov.b32 u1, {h1,h1}; mul.bf16x2 w2, v2, u1;\n" \
    "mma.sync.aligned.m16n8k16.row.col.f32.bf16.bf16.f32 {%144,%145,%146,%147}, {w0,w2,w1,w3}, {c0,c1}, {%144,%145,%146,%147};\n" \
    "mov.b32 {h0,h1}, z9; mov.b32 u1, {h1,h1}; mul.bf16x2 w0, v4, u1;\n" \
    "tanh.approx.f32 t2, z1;\n" \
    "st.volatile.shared.u32 [%177], %160;\n" \
    "@pr ld.shared.v4.u32 {v0,v1,v2,v3}, [na0+0];\n" \
    "mov.b32 {h0,h1}, z9; mov.b32 u1, {h1,h1}; mul.bf16x2 w1, v5, u1;\n" \
    "fma.rn.f32 z0, z0, t0, z0;\n" \
    "tanh.approx.f32 t3, z3;\n" \
    "fma.rn.f32 z2, z2, t1, z2;\n" \
    "mov.b32 {h0,h1}, z11; mov.b32 u1, {h1,h1}; mul.bf16x2 w3, v7, u1;\n" \
    "mov.b32 {h0,h1}, z11; mov.b32 u1, {h1,h1}; mul.bf16x2 w2, v6, u1;\n" \
    "mma.sync.aligned.m16n8k16.row.col.f32.bf16.bf16.f32 {%148,%149,%150,%151}, {w0,w2,w1,w3}, {c0,c1}, {%148,%149,%150,%151};\n" \
    "mma.sync.aligned.m16n8k8.row.col.f32.bf16.bf16.f32 {z4,z5,z6,z7}, {%163,%164}, {rx}, {fz,fz,fz,fz};\n" \
    "tanh.approx.f32 t4, z4;\n" \
    "@pr ld.shared.v4.u32 {v4,v5,v6,v7}, [na0+128];\n" \
    "mov.b32 {h0,h1}, z12; mov.b32 u1, {h1,h1}; mul.bf16x2 w0, v8, u1;\n" \
    "tanh.approx.f32 t5, z6;\n" \
    "mov.b32 {h0,h1}, z12; mov.b32 u1, {h1,h1}; mul.bf16x2 w1, v9, u1;\n" \
    "fma.rn.f32 z1, z1, t2, z1;\n" \
    "mov.b32 {h0,h1}, z14; mov.b32 u1, {h1,h1}; mul.bf16x2 w3, v11, u1;\n" \
    "fma.rn.f32 z3, z3, t3, z3;\n" \
    "fma.rn.f32 z4, z4, t4, z4;\n" \
    "tanh.approx.f32 t6, z5;\n" \
    "mov.b32 {h0,h1}, z14; mov.b32 u1, {h1,h1}; mul.bf16x2 w2, v10, u1;\n" \
    "@pr ld.shared.v4.u32 {v8,v9,v10,v11}, [na0+512];\n" \
    "mma.sync.aligned.m16n8k16.row.col.f32.bf16.bf16.f32 {%152,%153,%154,%155}, {w0,w2,w1,w3}, {c0,c1}, {%152,%153,%154,%155};\n" \
    "mov.b32 {h0,h1}, z13; mov.b32 u1, {h1,h1}; mul.bf16x2 w0, v12, u1;\n" \
    "tanh.approx.f32 t7, z7;\n" \
    "mov.b32 {h0,h1}, z15; mov.b32 u1, {h1,h1}; mul.bf16x2 w3, v15, u1;\n" \
    "mov.b32 {h0,h1}, z13; mov.b32 u1, {h1,h1}; mul.bf16x2 w1, v13, u1;\n" \
    "fma.rn.f32 z6, z6, t5, z6;\n" \
    "mma.sync.aligned.m16n8k8.row.col.f32.bf16.bf16.f32 {y0,y1,y2,y3}, {%169,%170}, {ry}, {fz,fz,fz,fz};\n" \
    "mma.sync.aligned.m16n8k8.row.col.f32.bf16.bf16.f32 {z8,z9,z10,z11}, {%165,%166}, {rx}, {fz,fz,fz,fz};\n" \
    "and.b32 u2, ex, 14; setp.eq.and.u32 q0, u2, 2, pr; setp.eq.and.u32 q1, u2, 4, pr; setp.eq.and.u32 q2, u2, 8, pr;\n" \
    "mov.b32 {h0,h1}, z15; mov.b32 u1, {h1,h1}; mul.bf16x2 w2, v14, u1;\n" \
    "mma.sync.aligned.m16n8k16.row.col.f32.bf16.bf16.f32 {%156,%157,%158,%159}, {w0,w2,w1,w3}, {c0,c1}, {%156,%157,%158,%159};\n" \
    "ld.shared.v4.u32 {e0,e1,ex,e3}, [%160+16];\n" \
    "cvt.rn.bf16x2.f32 b0, y2, y0; cvt.rn.bf16x2.f32 b1, y3, y1;\n" \
    "selp.b32 a0, b0, 0, p0; selp.b32 a1, b0, 0, p1; selp.b32 a2, b1, 0, p0; selp.b32 a3, b1, 0, p1;\n" \
    "@q1 bra.uni S1;\n" \
    "@!q0 bra.uni D;\n" \
    "S0:\n" \
    "add.u32 %160, %160, 16;\n" \
    "mov.b32 ca0, na0; xor.b32 ca1, na0, 32; mov.b32 ef, rx;\n" \
    "prmt.b32 ey, e0, e1, %176;\n" \
    "and.b32 u2, ey, %172; setp.ne.u32 p0, u2, 0; and.b32 u2, ey, %173; setp.ne.u32 p1, u2, 0;\n" \
    "fma.rn.f32 z5, z5, t6, z5;\n" \
    "lop3.b32 u2, ey, 0xfff0, %174, 0xea; @pa ld.shared.v2.u32 {rx,ry}, [u2+%178];\n" \
    "mov.b32 {h0,h1}, z0; mov.b32 u1, {h1,h1}; mul.bf16x2 v0, v0, u1;\n" \
    "tanh.approx.f32 t0, z8;\n" \
    "tanh.approx.f32 t1, z10;\n" \
    "ld.shared.v4.u32 {v12,v13,v14,v15}, [ca0+640];\n" \
    "mov.b32 {h0,h1}, z0; mov.b32 u1, {h1,h1}; mul.bf16x2 v1, v1, u1;\n" \
    "mov.b32 {h0,h1}, z2; mov.b32 u1, {h1,h1}; mul.bf16x2 v2, v2, u1;\n" \
    "mma.sync.aligned.m16n8k16.row.col.f32.bf16.bf16.f32 {%0,%1,%2,%3}, {a0,a1,a2,a3}, {v0,v1}, {%0,%1,%2,%3};\n" \
    "fma.rn.f32 z7, z7, t7, z7;\n" \
    "mov.b32 {h0,h1}, z2; mov.b32 u1, {h1,h1}; mul.bf16x2 v3, v3, u1;\n" \
    "fma.rn.f32 z8, z8, t0, z8;\n" \
    "mma.sync.aligned.m16n8k16.row.col.f32.bf16.bf16.f32 {%4,%5,%6,%7}, {a0,a1,a2,a3}, {v2,v3}, {%4,%5,%6,%7};\n" \
    "ld.shared.v4.u32 {v0,v1,v2,v3}, [ca1+0];\n" \
    "tanh.approx.f32 t2, z9;\n" \
    "fma.rn.f32 z10, z10, t1, z10;\n" \
    "mov.b32 {h0,h1}, z1; mov.b32 u1, {h1,h1}; mul.bf16x2 v5, v5, u1;\n" \
    "mov.b32 {h0,h1}, z3; mov.b32 u1, {h1,h1}; mul.bf16x2 v6, v6, u1;\n" \
    "tanh.approx.f32 t3, z11;\n" \
    "mov.b32 {h0,h1}, z1; mov.b32 u1, {h1,h1}; mul.bf16x2 v4, v4, u1;\n" \
    "mma.sync.aligned.m16n8k16.row.col.f32.bf16.bf16.f32 {%8,%9,%10,%11}, {a0,a1,a2,a3}, {v4,v5}, {%8,%9,%10,%11};\n" \
    "mov.b32 {h0,h1}, z3; mov.b32 u1, {h1,h1}; mul.bf16x2 v7, v7, u1;\n" \
    "mma.sync.aligned.m16n8k16.row.col.f32.bf16.bf16.f32 {%12,%13,%14,%15}, {a0,a1,a2,a3}, {v6,v7}, {%12,%13,%14,%15};\n" \
    "ld.shared.v4.u32 {v4,v5,v6,v7}, [ca1+128];\n" \
    "mma.sync.aligned.m16n8k8.row.col.f32.bf16.bf16.f32 {z12,z13,z14,z15}, {%167,%168}, {ef}, {fz,fz,fz,fz};\n" \
    "tanh.approx.f32 t4, z12;\n" \
    "mov.b32 {h0,h1}, z6; mov.b32 u1, {h1,h1}; mul.bf16x2 v11, v11, u1;\n" \
    "mov.b32 {h0,h1}, z4; mov.b32 u1, {h1,h1}; mul.bf16x2 v8, v8, u1;\n" \
    "fma.rn.f32 z9, z9, t2, z9;\n" \
    "mov.b32 {h0,h1}, z4; mov.b32 u1, {h1,h1}; mul.bf16x2 v9, v9, u1;\n" \
    "mma.sync.aligned.m16n8k16.row.col.f32.bf16.bf16.f32 {%16,%17,%18,%19}, {a0,a1,a2,a3}, {v8,v9}, {%16,%17,%18,%19};\n" \
    "fma.rn.f32 z11, z11, t3, z11;\n" \
    "mov.b32 {h0,h1}, z6; mov.b32 u1, {h1,h1}; mul.bf16x2 v10, v10, u1;\n" \
    "mma.sync.aligned.m16n8k16.row.col.f32.bf16.bf16.f32 {%20,%21,%22,%23}, {a0,a1,a2,a3}, {v10,v11}, {%20,%21,%22,%23};\n" \
    "ld.shared.v4.u32 {v8,v9,v10,v11}, [ca1+512];\n" \
    "tanh.approx.f32 t5, z14;\n" \
    "mov.b32 {h0,h1}, z5; mov.b32 u1, {h1,h1}; mul.bf16x2 v12, v12, u1;\n" \
    "fma.rn.f32 z12, z12, t4, z12;\n" \
    "tanh.approx.f32 t6, z13;\n" \
    "mov.b32 {h0,h1}, z7; mov.b32 u1, {h1,h1}; mul.bf16x2 v15, v15, u1;\n" \
    "mov.b32 {h0,h1}, z7; mov.b32 u1, {h1,h1}; mul.bf16x2 v14, v14, u1;\n" \
    "tanh.approx.f32 t7, z15;\n" \
    "mma.sync.aligned.m16n8k8.row.col.f32.bf16.bf16.f32 {z0,z1,z2,z3}, {%161,%162}, {rx}, {fz,fz,fz,fz};\n" \
    "mov.b32 {h0,h1}, z5; mov.b32 u1, {h1,h1}; mul.bf16x2 v13, v13, u1;\n" \
    "mma.sync.aligned.m16n8k16.row.col.f32.bf16.bf16.f32 {%24,%25,%26,%27}, {a0,a1,a2,a3}, {v12,v13}, {%24,%25,%26,%27};\n" \
    "mma.sync.aligned.m16n8k16.row.col.f32.bf16.bf16.f32 {%28,%29,%30,%31}, {a0,a1,a2,a3}, {v14,v15}, {%28,%29,%30,%31};\n" \
    "fma.rn.f32 z14, z14, t5, z14;\n" \
    "ld.shared.v4.u32 {v12,v13,v14,v15}, [ca1+640];\n" \
    "tanh.approx.f32 t0, z0;\n" \
    "shr.u32 u2, ex, 16; add.u32 na0, %171, u2;\n" \
    "fma.rn.f32 z15, z15, t7, z15;\n" \
    "fma.rn.f32 z13, z13, t6, z13;\n" \
    "mov.b32 {h0,h1}, z10; mov.b32 u1, {h1,h1}; mul.bf16x2 v3, v3, u1;\n" \
    "mov.b32 {h0,h1}, z8; mov.b32 u1, {h1,h1}; mul.bf16x2 v0, v0, u1;\n" \
    "mov.b32 {h0,h1}, z8; mov.b32 u1, {h1,h1}; mul.bf16x2 v1, v1, u1;\n" \
    "mma.sync.aligned.m16n8k16.row.col.f32.bf16.bf16.f32 {%32,%33,%34,%35}, {a0,a1,a2,a3}, {v0,v1}, {%32,%33,%34,%35};\n" \
    "tanh.approx.f32 t1, z2;\n" \
    "mov.b32 {h0,h1}, z10; mov.b32 u1, {h1,h1}; mul.bf16x2 v2, v2, u1;\n" \
    "mma.sync.aligned.m16n8k16.row.col.f32.bf16.bf16.f32 {%36,%37,%38,%39}, {a0,a1,a2,a3}, {v2,v3}, {%36,%37,%38,%39};\n" \
    "and.b32 u2, ex, 1; mbarrier.try_wait.parity.shared::cta.b64 pr, [e3], u2;\n" \
    "st.volatile.shared.u32 [%177], %160;\n" \
    "@pr ld.shared.v4.u32 {v0,v1,v2,v3}, [na0+0];\n" \
    "fma.rn.f32 z0, z0, t0, z0;\n" \
    "tanh.approx.f32 t3, z3;\n" \
    "tanh.approx.f32 t2, z1;\n" \
    "fma.rn.f32 z2, z2, t1, z2;\n" \
    "mov.b32 {h0,h1}, z9; mov.b32 u1, {h1,h1}; mul.bf16x2 v4, v4, u1;\n" \
    "mov.b32 {h0,h1}, z9; mov.b32 u1, {h1,h1}; mul.bf16x2 v5, v5, u1;\n" \
    "mov.b32 {h0,h1}, z11; mov.b32 u1, {h1,h1}; mul.bf16x2 v6, v6, u1;\n" \
    "mma.sync.aligned.m16n8k16.row.col.f32.bf16.bf16.f32 {%40,%41,%42,%43}, {a0,a1,a2,a3}, {v4,v5}, {%40,%41,%42,%43};\n" \
    "mov.b32 {h0,h1}, z11; mov.b32 u1, {h1,h1}; mul.bf16x2 v7, v7, u1;\n" \
    "mma.sync.aligned.m16n8k16.row.col.f32.bf16.bf16.f32 {%44,%45,%46,%47}, {a0,a1,a2,a3}, {v6,v7}, {%44,%45,%46,%47};\n" \
    "mov.b32 {h0,h1}, z12; mov.b32 u1, {h1,h1}; mul.bf16x2 v8, v8, u1;\n" \
    "fma.rn.f32 z1, z1, t2, z1;\n" \
    "mma.sync.aligned.m16n8k8.row.col.f32.bf16.bf16.f32 {z4,z5,z6,z7}, {%163,%164}, {rx}, {fz,fz,fz,fz};\n" \
    "tanh.approx.f32 t4, z4;\n" \
    "@pr ld.shared.v4.u32 {v4,v5,v6,v7}, [na0+128];\n" \
    "tanh.approx.f32 t5, z6;\n" \
    "mov.b32 {h0,h1}, z12; mov.b32 u1, {h1,h1}; mul.bf16x2 v9, v9, u1;\n" \
    "mma.sync.aligned.m16n8k16.row.col.f32.bf16.bf16.f32 {%48,%49,%50,%51}, {a0,a1,a2,a3}, {v8,v9}, {%48,%49,%50,%51};\n" \
    "mov.b32 {h0,h1}, z14; mov.b32 u1, {h1,h1}; mul.bf16x2 v11, v11, u1;\n" \
    "fma.rn.f32 z3, z3, t3, z3;\n" \
    "mov.b32 {h0,h1}, z14; mov.b32 u1, {h1,h1}; mul.bf16x2 v10, v10, u1;\n" \
    "fma.rn.f32 z4, z4, t4, z4;\n" \
    "mma.sync.aligned.m16n8k16.row.col.f32.bf16.bf16.f32 {%52,%53,%54,%55}, {a0,a1,a2,a3}, {v10,v11}, {%52,%53,%54,%55};\n" \
    "@pr ld.shared.v4.u32 {v8,v9,v10,v11}, [na0+512];\n" \
    "mov.b32 {h0,h1}, z13; mov.b32 u1, {h1,h1}; mul.bf16x2 v12, v12, u1;\n" \
    "tanh.approx.f32 t6, z5;\n" \
    "mov.b32 {h0,h1}, z13; mov.b32 u1, {h1,h1}; mul.bf16x2 v13, v13, u1;\n" \
    "mma.sync.aligned.m16n8k16.row.col.f32.bf16.bf16.f32 {%56,%57,%58,%59}, {a0,a1,a2,a3}, {v12,v13}, {%56,%57,%58,%59};\n" \
    "fma.rn.f32 z6, z6, t5, z6;\n" \
    "mov.b32 {h0,h1}, z15; mov.b32 u1, {h1,h1}; mul.bf16x2 v15, v15, u1;\n" \
    "tanh.approx.f32 t7, z7;\n" \
    "mov.b32 {h0,h1}, z15; mov.b32 u1, {h1,h1}; mul.bf16x2 v14, v14, u1;\n" \
    "mma.sync.aligned.m16n8k16.row.col.f32.bf16.bf16.f32 {%60,%61,%62,%63}, {a0,a1,a2,a3}, {v14,v15}, {%60,%61,%62,%63};\n" \
    "mma.sync.aligned.m16n8k8.row.col.f32.bf16.bf16.f32 {z8,z9,z10,z11}, {%165,%166}, {rx}, {fz,fz,fz,fz};\n" \
    "mma.sync.aligned.m16n8k8.row.col.f32.bf16.bf16.f32 {y0,y1,y2,y3}, {%169,%170}, {ry}, {fz,fz,fz,fz};\n" \
    "and.b32 u2, ex, 14; setp.eq.and.u32 q0, u2, 2, pr; setp.eq.and.u32 q1, u2, 4, pr; setp.eq.and.u32 q2, u2, 8, pr;\n" \
    "ld.shared.v4.u32 {e0,e1,ex,e3}, [%160+16];\n" \
    "cvt.rn.bf16x2.f32 b0, y2, y0; cvt.rn.bf16x2.f32 b1, y3, y1;\n" \
    "selp.b32 a0, b0, 0, p0; selp.b32 a1, b0, 0, p1; selp.b32 a2, b1, 0, p0; selp.b32 a3, b1, 0, p1;\n" \
    "@!q1 bra.uni D;\n" \
    "S1:\n" \
    "add.u32 %160, %160, 16;\n" \
    "mov.b32 ca0, na0; xor.b32 ca1, na0, 32; mov.b32 ef, rx;\n" \
    "prmt.b32 ey, e0, e1, %176;\n" \
    "and.b32 u2, ey, %172; setp.ne.u32 p0, u2, 0; and.b32 u2, ey, %173; setp.ne.u32 p1, u2, 0;\n" \
    "fma.rn.f32 z5, z5, t6, z5;\n" \
    "lop3.b32 u2, ey, 0xfff0, %174, 0xea; @pa ld.shared.v2.u32 {rx,ry}, [u2+%178];\n" \
    "mov.b32 {h0,h1}, z0; mov.b32 u1, {h1,h1}; mul.bf16x2 v0, v0, u1;\n" \
    "tanh.approx.f32 t0, z8;\n" \
    "tanh.approx.f32 t1, z10;\n" \
    "ld.shared.v4.u32 {v12,v13,v14,v15}, [ca0+640];\n" \
    "mov.b32 {h0,h1}, z0; mov.b32 u1, {h1,h1}; mul.bf16x2 v1, v1, u1;\n" \
    "mov.b32 {h0,h1}, z2; mov.b32 u1, {h1,h1}; mul.bf16x2 v2, v2, u1;\n" \
    "mma.sync.aligned.m16n8k16.row.col.f32.bf16.bf16.f32 {%64,%65,%66,%67}, {a0,a1,a2,a3}, {v0,v1}, {%64,%65,%66,%67};\n" \
    "fma.rn.f32 z7, z7, t7, z7;\n" \
    "mov.b32 {h0,h1}, z2; mov.b32 u1, {h1,h1}; mul.bf16x2 v3, v3, u1;\n" \
    "fma.rn.f32 z8, z8, t0, z8;\n" \
    "mma.sync.aligned.m16n8k16.row.col.f32.bf16.bf16.f32 {%68,%69,%70,%71}, {a0,a1,a2,a3}, {v2,v3}, {%68,%69,%70,%71};\n" \
    "ld.shared.v4.u32 {v0,v1,v2,v3}, [ca1+0];\n" \
    "tanh.approx.f32 t2, z9;\n" \
    "fma.rn.f32 z10, z10, t1, z10;\n" \
    "mov.b32 {h0,h1}, z1; mov.b32 u1, {h1,h1}; mul.bf16x2 v5, v5, u1;\n" \
    "mov.b32 {h0,h1}, z3; mov.b32 u1, {h1,h1}; mul.bf16x2 v6, v6, u1;\n" \
    "tanh.approx.f32 t3, z11;\n" \
    "mov.b32 {h0,h1}, z1; mov.b32 u1, {h1,h1}; mul.bf16x2 v4, v4, u1;\n" \
    "mma.sync.aligned.m16n8k16.row.col.f32.bf16.bf16.f32 {%72,%73,%74,%75}, {a0,a1,a2,a3}, {v4,v5}, {%72,%73,%74,%75};\n" \
    "mov.b32 {h0,h1}, z3; mov.b32 u1, {h1,h1}; mul.bf16x2 v7, v7, u1;\n" \
    "mma.sync.aligned.m16n8k16.row.col.f32.bf16.bf16.f32 {%76,%77,%78,%79}, {a0,a1,a2,a3}, {v6,v7}, {%76,%77,%78,%79};\n" \
    "ld.shared.v4.u32 {v4,v5,v6,v7}, [ca1+128];\n" \
    "mma.sync.aligned.m16n8k8.row.col.f32.bf16.bf16.f32 {z12,z13,z14,z15}, {%167,%168}, {ef}, {fz,fz,fz,fz};\n" \
    "tanh.approx.f32 t4, z12;\n" \
    "mov.b32 {h0,h1}, z6; mov.b32 u1, {h1,h1}; mul.bf16x2 v11, v11, u1;\n" \
    "mov.b32 {h0,h1}, z4; mov.b32 u1, {h1,h1}; mul.bf16x2 v8, v8, u1;\n" \
    "fma.rn.f32 z9, z9, t2, z9;\n" \
    "mov.b32 {h0,h1}, z4; mov.b32 u1, {h1,h1}; mul.bf16x2 v9, v9, u1;\n" \
    "mma.sync.aligned.m16n8k16.row.col.f32.bf16.bf16.f32 {%80,%81,%82,%83}, {a0,a1,a2,a3}, {v8,v9}, {%80,%81,%82,%83};\n" \
    "fma.rn.f32 z11, z11, t3, z11;\n" \
    "mov.b32 {h0,h1}, z6; mov.b32 u1, {h1,h1}; mul.bf16x2 v10, v10, u1;\n" \
    "mma.sync.aligned.m16n8k16.row.col.f32.bf16.bf16.f32 {%84,%85,%86,%87}, {a0,a1,a2,a3}, {v10,v11}, {%84,%85,%86,%87};\n" \
    "ld.shared.v4.u32 {v8,v9,v10,v11}, [ca1+512];\n" \
    "tanh.approx.f32 t5, z14;\n" \
    "mov.b32 {h0,h1}, z5; mov.b32 u1, {h1,h1}; mul.bf16x2 v12, v12, u1;\n" \
    "fma.rn.f32 z12, z12, t4, z12;\n" \
    "tanh.approx.f32 t6, z13;\n" \
    "mov.b32 {h0,h1}, z7; mov.b32 u1, {h1,h1}; mul.bf16x2 v15, v15, u1;\n" \
    "mov.b32 {h0,h1}, z7; mov.b32 u1, {h1,h1}; mul.bf16x2 v14, v14, u1;\n" \
    "tanh.approx.f32 t7, z15;\n" \
    "mma.sync.aligned.m16n8k8.row.col.f32.bf16.bf16.f32 {z0,z1,z2,z3}, {%161,%162}, {rx}, {fz,fz,fz,fz};\n" \
    "mov.b32 {h0,h1}, z5; mov.b32 u1, {h1,h1}; mul.bf16x2 v13, v13, u1;\n" \
    "mma.sync.aligned.m16n8k16.row.col.f32.bf16.bf16.f32 {%88,%89,%90,%91}, {a0,a1,a2,a3}, {v12,v13}, {%88,%89,%90,%91};\n" \
    "mma.sync.aligned.m16n8k16.row.col.f32.bf16.bf16.f32 {%92,%93,%94,%95}, {a0,a1,a2,a3}, {v14,v15}, {%92,%93,%94,%95};\n" \
    "fma.rn.f32 z14, z14, t5, z14;\n" \
    "ld.shared.v4.u32 {v12,v13,v14,v15}, [ca1+640];\n" \
    "tanh.approx.f32 t0, z0;\n" \
    "shr.u32 u2, ex, 16; add.u32 na0, %171, u2;\n" \
    "fma.rn.f32 z15, z15, t7, z15;\n" \
    "fma.rn.f32 z13, z13, t6, z13;\n" \
    "mov.b32 {h0,h1}, z10; mov.b32 u1, {h1,h1}; mul.bf16x2 v3, v3, u1;\n" \
    "mov.b32 {h0,h1}, z8; mov.b32 u1, {h1,h1}; mul.bf16x2 v0, v0, u1;\n" \
    "mov.b32 {h0,h1}, z8; mov.b32 u1, {h1,h1}; mul.bf16x2 v1, v1, u1;\n" \
    "mma.sync.aligned.m16n8k16.row.col.f32.bf16.bf16.f32 {%96,%97,%98,%99}, {a0,a1,a2,a3}, {v0,v1}, {%96,%97,%98,%99};\n" \
    "tanh.approx.f32 t1, z2;\n" \
    "mov.b32 {h0,h1}, z10; mov.b32 u1, {h1,h1}; mul.bf16x2 v2, v2, u1;\n" \
    "mma.sync.aligned.m16n8k16.row.col.f32.bf16.bf16.f32 {%100,%101,%102,%103}, {a0,a1,a2,a3}, {v2,v3}, {%100,%101,%102,%103};\n" \
    "and.b32 u2, ex, 1; mbarrier.try_wait.parity.shared::cta.b64 pr, [e3], u2;\n" \
    "st.volatile.shared.u32 [%177], %160;\n" \
    "@pr ld.shared.v4.u32 {v0,v1,v2,v3}, [na0+0];\n" \
    "fma.rn.f32 z0, z0, t0, z0;\n" \
    "tanh.approx.f32 t3, z3;\n" \
    "tanh.approx.f32 t2, z1;\n" \
    "fma.rn.f32 z2, z2, t1, z2;\n" \
    "mov.b32 {h0,h1}, z9; mov.b32 u1, {h1,h1}; mul.bf16x2 v4, v4, u1;\n" \
    "mov.b32 {h0,h1}, z9; mov.b32 u1, {h1,h1}; mul.bf16x2 v5, v5, u1;\n" \
    "mov.b32 {h0,h1}, z11; mov.b32 u1, {h1,h1}; mul.bf16x2 v6, v6, u1;\n" \
    "mma.sync.aligned.m16n8k16.row.col.f32.bf16.bf16.f32 {%104,%105,%106,%107}, {a0,a1,a2,a3}, {v4,v5}, {%104,%105,%106,%107};\n" \
    "mov.b32 {h0,h1}, z11; mov.b32 u1, {h1,h1}; mul.bf16x2 v7, v7, u1;\n" \
    "mma.sync.aligned.m16n8k16.row.col.f32.bf16.bf16.f32 {%108,%109,%110,%111}, {a0,a1,a2,a3}, {v6,v7}, {%108,%109,%110,%111};\n" \
    "mov.b32 {h0,h1}, z12; mov.b32 u1, {h1,h1}; mul.bf16x2 v8, v8, u1;\n" \
    "fma.rn.f32 z1, z1, t2, z1;\n" \
    "mma.sync.aligned.m16n8k8.row.col.f32.bf16.bf16.f32 {z4,z5,z6,z7}, {%163,%164}, {rx}, {fz,fz,fz,fz};\n" \
    "tanh.approx.f32 t4, z4;\n" \
    "@pr ld.shared.v4.u32 {v4,v5,v6,v7}, [na0+128];\n" \
    "tanh.approx.f32 t5, z6;\n" \
    "mov.b32 {h0,h1}, z12; mov.b32 u1, {h1,h1}; mul.bf16x2 v9, v9, u1;\n" \
    "mma.sync.aligned.m16n8k16.row.col.f32.bf16.bf16.f32 {%112,%113,%114,%115}, {a0,a1,a2,a3}, {v8,v9}, {%112,%113,%114,%115};\n" \
    "mov.b32 {h0,h1}, z14; mov.b32 u1, {h1,h1}; mul.bf16x2 v11, v11, u1;\n" \
    "fma.rn.f32 z3, z3, t3, z3;\n" \
    "mov.b32 {h0,h1}, z14; mov.b32 u1, {h1,h1}; mul.bf16x2 v10, v10, u1;\n" \
    "fma.rn.f32 z4, z4, t4, z4;\n" \
    "mma.sync.aligned.m16n8k16.row.col.f32.bf16.bf16.f32 {%116,%117,%118,%119}, {a0,a1,a2,a3}, {v10,v11}, {%116,%117,%118,%119};\n" \
    "@pr ld.shared.v4.u32 {v8,v9,v10,v11}, [na0+512];\n" \
    "mov.b32 {h0,h1}, z13; mov.b32 u1, {h1,h1}; mul.bf16x2 v12, v12, u1;\n" \
    "tanh.approx.f32 t6, z5;\n" \
    "mov.b32 {h0,h1}, z13; mov.b32 u1, {h1,h1}; mul.bf16x2 v13, v13, u1;\n" \
    "mma.sync.aligned.m16n8k16.row.col.f32.bf16.bf16.f32 {%120,%121,%122,%123}, {a0,a1,a2,a3}, {v12,v13}, {%120,%121,%122,%123};\n" \
    "fma.rn.f32 z6, z6, t5, z6;\n" \
    "mov.b32 {h0,h1}, z15; mov.b32 u1, {h1,h1}; mul.bf16x2 v15, v15, u1;\n" \
    "tanh.approx.f32 t7, z7;\n" \
    "mov.b32 {h0,h1}, z15; mov.b32 u1, {h1,h1}; mul.bf16x2 v14, v14, u1;\n" \
    "mma.sync.aligned.m16n8k16.row.col.f32.bf16.bf16.f32 {%124,%125,%126,%127}, {a0,a1,a2,a3}, {v14,v15}, {%124,%125,%126,%127};\n" \
    "mma.sync.aligned.m16n8k8.row.col.f32.bf16.bf16.f32 {z8,z9,z10,z11}, {%165,%166}, {rx}, {fz,fz,fz,fz};\n" \
    "mma.sync.aligned.m16n8k8.row.col.f32.bf16.bf16.f32 {y0,y1,y2,y3}, {%169,%170}, {ry}, {fz,fz,fz,fz};\n" \
    "and.b32 u2, ex, 14; setp.eq.and.u32 q0, u2, 2, pr; setp.eq.and.u32 q1, u2, 4, pr; setp.eq.and.u32 q2, u2, 8, pr;\n" \
    "ld.shared.v4.u32 {e0,e1,ex,e3}, [%160+16];\n" \
    "cvt.rn.bf16x2.f32 b0, y2, y0; cvt.rn.bf16x2.f32 b1, y3, y1;\n" \
    "selp.b32 a0, b0, 0, p0; selp.b32 a1, b0, 0, p1; selp.b32 a2, b1, 0, p0; selp.b32 a3, b1, 0, p1;\n" \
    "D:\n" \
    "@q0 bra.uni S0;\n" \
    "@q2 bra.uni S2;\n" \
    "@q1 bra.uni S1;\n" \
    "SLOW:\n" \
    "ld.shared.v2.u32 {gx,gy}, [%160+8];\n" \
    "and.b32 u2, gx, 1; and.b32 gx, gx, 14; setp.eq.u32 q0, gx, 2; setp.eq.u32 q1, gx, 4; setp.eq.u32 q2, gx, 8;\n" \
    "setp.eq.u32 pr, gx, 0;\n" \
    "@pr bra.uni DONE;\n" \
    "XW:\n" \
    "mov.u32 cnt, %%globaltimer_hi; ld.shared.u32 gx, [%177+32]; sub.u32 cnt, cnt, gx;\n" \
    "mbarrier.try_wait.parity.shared::cta.b64 pr, [gy], u2;\n" \
    "setp.lt.and.u32 pr, cnt, 2, !pr;\n" \
    "@pr bra.uni XW;\n" \
    "ld.shared.v4.u32 {v0,v1,v2,v3}, [na0+0];\n" \
    "ld.shared.v4.u32 {v4,v5,v6,v7}, [na0+128];\n" \
    "ld.shared.v4.u32 {v8,v9,v10,v11}, [na0+512];\n" \
    "@q0 bra.uni S0;\n" \
    "@q1 bra.uni S1;\n" \
    "bra.uni S2;\n" \
    "DONE:\n" \
    "mov.b32 u2, z0; xor.b32 %160, %160, u2;\n" \
    "mov.b32 u2, z2; xor.b32 %160, %160, u2;\n" \
    "mov.b32 u2, z1; xor.b32 %160, %160, u2;\n" \
    "mov.b32 u2, z3; xor.b32 %160, %160, u2;\n" \
    "mov.b32 u2, z4; xor.b32 %160, %160, u2;\n" \
    "mov.b32 u2, z6; xor.b32 %160, %160, u2;\n" \
    "}\n" \
    ""
#define MAIN_LOOP_ACC(A) \
    "+f"(A[0][0]), "+f"(A[0][1]), "+f"(A[0][2]), "+f"(A[0][3]), "+f"(A[1][0]), "+f"(A[1][1]), "+f"(A[1][2]), "+f"(A[1][3]), \
    "+f"(A[2][0]), "+f"(A[2][1]), "+f"(A[2][2]), "+f"(A[2][3]), "+f"(A[3][0]), "+f"(A[3][1]), "+f"(A[3][2]), "+f"(A[3][3]), \
    "+f"(A[4][0]), "+f"(A[4][1]), "+f"(A[4][2]), "+f"(A[4][3]), "+f"(A[5][0]), "+f"(A[5][1]), "+f"(A[5][2]), "+f"(A[5][3]), \
    "+f"(A[6][0]), "+f"(A[6][1]), "+f"(A[6][2]), "+f"(A[6][3]), "+f"(A[7][0]), "+f"(A[7][1]), "+f"(A[7][2]), "+f"(A[7][3]), \
    "+f"(A[8][0]), "+f"(A[8][1]), "+f"(A[8][2]), "+f"(A[8][3]), "+f"(A[9][0]), "+f"(A[9][1]), "+f"(A[9][2]), "+f"(A[9][3]), \
    "+f"(A[10][0]), "+f"(A[10][1]), "+f"(A[10][2]), "+f"(A[10][3]), "+f"(A[11][0]), "+f"(A[11][1]), "+f"(A[11][2]), "+f"(A[11][3]), \
    "+f"(A[12][0]), "+f"(A[12][1]), "+f"(A[12][2]), "+f"(A[12][3]), "+f"(A[13][0]), "+f"(A[13][1]), "+f"(A[13][2]), "+f"(A[13][3]), \
    "+f"(A[14][0]), "+f"(A[14][1]), "+f"(A[14][2]), "+f"(A[14][3]), "+f"(A[15][0]), "+f"(A[15][1]), "+f"(A[15][2]), "+f"(A[15][3]), \
    "+f"(A[16][0]), "+f"(A[16][1]), "+f"(A[16][2]), "+f"(A[16][3]), "+f"(A[17][0]), "+f"(A[17][1]), "+f"(A[17][2]), "+f"(A[17][3]), \
    "+f"(A[18][0]), "+f"(A[18][1]), "+f"(A[18][2]), "+f"(A[18][3]), "+f"(A[19][0]), "+f"(A[19][1]), "+f"(A[19][2]), "+f"(A[19][3]), \
    "+f"(A[20][0]), "+f"(A[20][1]), "+f"(A[20][2]), "+f"(A[20][3]), "+f"(A[21][0]), "+f"(A[21][1]), "+f"(A[21][2]), "+f"(A[21][3]), \
    "+f"(A[22][0]), "+f"(A[22][1]), "+f"(A[22][2]), "+f"(A[22][3]), "+f"(A[23][0]), "+f"(A[23][1]), "+f"(A[23][2]), "+f"(A[23][3]), \
    "+f"(A[24][0]), "+f"(A[24][1]), "+f"(A[24][2]), "+f"(A[24][3]), "+f"(A[25][0]), "+f"(A[25][1]), "+f"(A[25][2]), "+f"(A[25][3]), \
    "+f"(A[26][0]), "+f"(A[26][1]), "+f"(A[26][2]), "+f"(A[26][3]), "+f"(A[27][0]), "+f"(A[27][1]), "+f"(A[27][2]), "+f"(A[27][3]), \
    "+f"(A[28][0]), "+f"(A[28][1]), "+f"(A[28][2]), "+f"(A[28][3]), "+f"(A[29][0]), "+f"(A[29][1]), "+f"(A[29][2]), "+f"(A[29][3]), \
    "+f"(A[30][0]), "+f"(A[30][1]), "+f"(A[30][2]), "+f"(A[30][3]), "+f"(A[31][0]), "+f"(A[31][1]), "+f"(A[31][2]), "+f"(A[31][3]), \
    "+f"(A[32][0]), "+f"(A[32][1]), "+f"(A[32][2]), "+f"(A[32][3]), "+f"(A[33][0]), "+f"(A[33][1]), "+f"(A[33][2]), "+f"(A[33][3]), \
    "+f"(A[34][0]), "+f"(A[34][1]), "+f"(A[34][2]), "+f"(A[34][3]), "+f"(A[35][0]), "+f"(A[35][1]), "+f"(A[35][2]), "+f"(A[35][3]), \
    "+f"(A[36][0]), "+f"(A[36][1]), "+f"(A[36][2]), "+f"(A[36][3]), "+f"(A[37][0]), "+f"(A[37][1]), "+f"(A[37][2]), "+f"(A[37][3]), \
    "+f"(A[38][0]), "+f"(A[38][1]), "+f"(A[38][2]), "+f"(A[38][3]), "+f"(A[39][0]), "+f"(A[39][1]), "+f"(A[39][2]), "+f"(A[39][3])
#define PRODUCER_PTX \
    "{\n" \
    ".reg .b32 r<4>, d, c, t, w, n, bb, dd, kw, cc; .reg .b64 a; .reg .pred p;\n" \
    "mov.b32 n, 0; mov.b32 r0, 0; mov.u32 cc, %%globaltimer_lo; sub.s32 cc, cc, %11;\n" \
    "bra.uni TURN;\n" \
    "TOP:\n" \
    "ld.shared.v4.u32 {r0,r1,r2,r3}, [%0+%16];\n" \
    "ld.shared.u16 t, [%0+72];\n" \
    "mov.u32 c, %%globaltimer_lo; sub.s32 c, c, %11; sub.s32 c, c, t; setp.ge.s32 p, c, 0;\n" \
    "@p bra.uni G;\n" \
    "T:\n" \
    "nanosleep.u32 64;\n" \
    "mov.u32 c, %%globaltimer_lo; sub.s32 c, c, %11; sub.s32 c, c, t; setp.lt.s32 p, c, 0;\n" \
    "@p bra.uni T;\n" \
    "G:\n" \
    "ld.volatile.shared.u32 w, [%9]; setp.lt.u32 p, w, %0;\n" \
    "@p bra.uni W;\n" \
    "mbarrier.arrive.expect_tx.shared::cta.b64 _, [bb], %12;\n" \
    "add.u32 d, dd, 0*%15;\n" \
    "cp.async.bulk.tensor.2d.shared::cluster.global.tile.mbarrier::complete_tx::bytes [d], [%4, {%5, r0}], [bb];\n" \
    "add.u32 d, dd, 1*%15;\n" \
    "cp.async.bulk.tensor.2d.shared::cluster.global.tile.mbarrier::complete_tx::bytes [d], [%4, {%6, r1}], [bb];\n" \
    "add.u32 d, dd, 2*%15;\n" \
    "cp.async.bulk.tensor.2d.shared::cluster.global.tile.mbarrier::complete_tx::bytes [d], [%4, {%7, r2}], [bb];\n" \
    "add.u32 d, dd, 3*%15;\n" \
    "cp.async.bulk.tensor.2d.shared::cluster.global.tile.mbarrier::complete_tx::bytes [d], [%4, {%8, r3}], [bb];\n" \
    "add.u32 %0, %0, 16; add.u32 bb, bb, 8; add.u32 dd, dd, 1024; setp.ne.u32 p, %0, kw;\n" \
    "@p bra.uni TOP;\n" \
    "TURN:\n" \
    "setp.ge.u32 p, %0, %10;\n" \
    "@p bra.uni END;\n" \
    "mov.b32 bb, %3; mov.b32 dd, %2; add.u32 kw, %0, 80; min.u32 kw, kw, %10;\n" \
    "mul.lo.u32 c, r0, 16; shr.u32 c, c, 5; add.u32 c, c, %17; setp.lt.u32 p, c, %1;\n" \
    "@p bra.uni TOP;\n" \
    "sub.s32 c, %14, %1; min.s32 c, c, %18; setp.gt.s32 p, c, 0; shl.b32 c, c, 10; mad.wide.u32 a, %1, 1024, %13;\n" \
    "@p cp.async.bulk.prefetch.L2.global [a], c;\n" \
    "add.u32 %1, %1, %19;\n" \
    "bra.uni TOP;\n" \
    "W:\n" \
    "add.u32 n, n, 1; setp.lt.u32 p, n, 0x1000000;\n" \
    "@p bra.uni G;\n" \
    "END:\n" \
    "}\n" \
    ""

__device__ __forceinline__ void wgmma_n64(float (&d)[32], const uint32_t (&a)[4], uint64_t desc, int acc) {
    asm volatile("{\n\t.reg .pred p;\n\tsetp.ne.u32 p, %37, 0;\n\t"
        "wgmma.mma_async.sync.aligned.m64n64k16.f32.bf16.bf16 {%0,%1,%2,%3,%4,%5,%6,%7,%8,%9,%10,%11,%12,%13,%14,%15,"
        "%16,%17,%18,%19,%20,%21,%22,%23,%24,%25,%26,%27,%28,%29,%30,%31}, {%32,%33,%34,%35}, %36, p, 1, 1, 1;\n\t}"
        : "+f"(d[0]), "+f"(d[1]), "+f"(d[2]), "+f"(d[3]), "+f"(d[4]), "+f"(d[5]), "+f"(d[6]), "+f"(d[7]),
          "+f"(d[8]), "+f"(d[9]), "+f"(d[10]), "+f"(d[11]), "+f"(d[12]), "+f"(d[13]), "+f"(d[14]), "+f"(d[15]),
          "+f"(d[16]), "+f"(d[17]), "+f"(d[18]), "+f"(d[19]), "+f"(d[20]), "+f"(d[21]), "+f"(d[22]), "+f"(d[23]),
          "+f"(d[24]), "+f"(d[25]), "+f"(d[26]), "+f"(d[27]), "+f"(d[28]), "+f"(d[29]), "+f"(d[30]), "+f"(d[31])
        : "r"(a[0]), "r"(a[1]), "r"(a[2]), "r"(a[3]), "l"(desc), "r"(acc));
}

#define PT1 900
#define PT0 1550
#define PDT 36.2
#define NSLEEP 64
#define PFA 1400
#define PFR 8
template <int ID, int COUNT> __device__ __forceinline__ void bar_sync() { asm volatile("bar.sync %0, %1;" ::"n"(ID), "n"(COUNT) : "memory"); }
template <int ID, int COUNT> __device__ __forceinline__ void bar_arrive() { asm volatile("bar.arrive %0, %1;" ::"n"(ID), "n"(COUNT) : "memory"); }
template <int BYTES>
__device__ __forceinline__ void fill(uint32_t addr, uint4 v, int tid) {
#pragma unroll
    for (int r = 0; r < (BYTES / 16 + NT - 1) / NT; r++)
        sts128_if((r + 1) * NT <= BYTES / 16 || r * NT + tid < BYTES / 16, addr + (r * NT + tid) * 16, v);
}

__device__ __forceinline__ uint32_t group_cap(uint32_t key, int lane) {
    return __reduce_add_sync(0xffffffffu, min(key >> 5, GK)) > KCAP ? KCAP / NG : lane < 16 ? GK : 128 - 2 * GK;
}
template <int NR>
__device__ __forceinline__ void build_list(uint4 lt, uint4 lo, int wl, int lane, int N, uint32_t bin_magic, uint32_t pace) {
    const uint32_t lh = sb + SM_LH + wl * (LBIN * 4);
    uint4 w[NR], r[NR];
    uint32_t p[NR], ba[NR], ez[NR];
#pragma unroll
    for (int j = 0; j < NR; j++) {
        const uint32_t i = j * 32 + lane;
        w[j] = lds128(sb + SM_KSG + i * 16 + (i < lt.x ? lo.x : i < lt.y ? lo.y : lo.z));
        ez[j] = i < lt.x ? 2 : i < lt.y ? 4 : 8;
    }
#pragma unroll
    for (int j = 0; j < NR; j++) {
        r[j] = make_uint4(w[j].x & 0x3fff, w[j].y & 0x3fff, w[j].z & 0x3fff, w[j].w & 0x3fff);
        const uint32_t key = r[j].x + r[j].y + r[j].z + r[j].w;
        ba[j] = j * 32 + lane < lt.z ? lh + (key * bin_magic >> 20) * 4 : sb + SM_DUM + lane * 4;
        ez[j] |= __umulhi(key * 2, pace) & 0xfff0;
    }
#pragma unroll
    for (int j = 0; j < NR; j++) p[j] = atoms_inc(ba[j]);
    __syncwarp();
    const uint4 u = lds128(lh + lane * 16);
    const uint32_t sum = u.x + u.y + u.z + u.w, ex = warp_incl_scan(sum) - sum;
    sts128_if(true, lh + lane * 16, make_uint4(ex, ex + u.x, ex + u.x + u.y, ex + u.x + u.y + u.z));
    __syncwarp();
#pragma unroll
    for (int j = 0; j < NR; j++) p[j] += lds32(ba[j]);
#pragma unroll
    for (int j = 0; j < NR; j++) {
        const uint32_t turn = (p[j] * SMG) >> 16, slot = p[j] - turn * S;
        sts128_if(p[j] < lt.z, sb + SM_SRC + (lt.w + p[j]) * 16, make_uint4(r[j].x * 8, r[j].y * 8, r[j].z * 8, r[j].w * 8));
        sts128_if(p[j] < lt.z, sb + SM_LIST + (lt.w + p[j]) * 16,
                  make_uint4(__byte_perm(w[j].x * 4, w[j].y * 4, 0x7632), __byte_perm(w[j].z * 4, w[j].w * 4, 0x7632),
                             (ez[j] | (turn & 1)) + slot * (1u << 26), sb + SM_BAR + wl * (S * 8) + slot * 8));
    }
}
__device__ __forceinline__ bool next_excess(const Scratch* scr, const __nv_bfloat16* x, uint32_t va0) {
    uint32_t tid, cta;
    asm volatile("mov.u32 %0, %tid.x;" : "=r"(tid));
    asm volatile("mov.u32 %0, %ctaid.x;" : "=r"(cta));
    const int lane = tid & 31, wl = tid >> 5;
    const uint32_t bar_rec = sb + SM_BAR + NW * S * 8 + 16, own = sb + SM_SRC + wl * 96, st = sb + SM_STATE + wl * 16;
    const uint32_t grp = lds32(sb + SM_MISC + 64 + wl * 4);
    uint4 c = lds128(st);
    __syncwarp();
    for (; c.x <= NCTA; c.x++, c.y = 0) {
        if (c.y == 0 && c.z == 0)
            c.x += __reduce_min_sync(0xffffffffu, c.x + lane >= NCTA || (lds32(sb + SM_SEG + min(c.x + lane, NCTA - 1) * 4) >> 12) > MBE ? lane : 31);
        const uint32_t loc = lds32(sb + SM_SEG + min(c.x, NCTA - 1) * 4);
        const int n = c.x < NCTA ? (int)(loc >> 12) - MBE : lds32(sb + SM_MISC + 12);
        for (; (int)c.y < n; c.y += 32, c.z = 0) {
            uint2 u = make_uint2(0xffffffffu, c.x * SLICE + (loc & 0xfff) + MBE + c.y + lane);
            if ((int)c.y + lane < n) {
                if (c.x < NCTA) u.x = __ldcg(scr->ss + u.y);
                else u = __ldcg(scr->exc + cta * MBW + c.y + lane);
            }
            const uint32_t gw = (u.x >> 25 & 31) - 1, ja = gw == (grp & 31) ? 1 : gw == (grp >> 5 & 31) ? 2 : gw == (grp >> 10 & 31) ? 3 : 0;
            const unsigned todo = __ballot_sync(0xffffffffu, ja) & ~c.z;
            if (!todo) continue;
            const uint32_t jf = __shfl_sync(0xffffffffu, ja, __ffs(todo) - 1);
            const unsigned m = todo & __ballot_sync(0xffffffffu, ja == jf);
            const uint32_t from = __fns(m, 0, (lane & 3) + 1);
            const bool pad = from > 31;
            c.z |= __reduce_or_sync(0xffffffffu, pad ? 0 : 1u << from);
            if (!(todo & ~c.z)) { c.y += 32; c.z = 0; }
            u.x = __shfl_sync(0xffffffffu, u.x, pad ? __ffs(m) - 1 : from);
            u.y = __shfl_sync(0xffffffffu, u.y, from);
            const uint32_t slot = ((grp >> 16) + S - 1) % S;
#pragma unroll 1
            for (int k = 0; k < 8; k++)
                cp16((va0 ^ (k & 4) * 8) + slot * 1024 + (k & 1) * 128 + (k & 2) * 256,
                     reinterpret_cast<const uint4*>(x) + (size_t)(u.x & 0x3fff) * 64 + chunk_of(k, lane >> 2));
            mbar_wait(bar_rec - 16, 0);
            if (lane < 4) {
                if (!pad) cp16(own + 32 + lane * 16, scr->rec + u.y);
                asm volatile("st.shared.u16 [%0], %1;" ::"r"(own + lane * 2),
                             "h"((uint16_t)(((pad ? sb + SM_ZERO : own + 32 + lane * 16) - sb - SM_REC) | (u.x >> 14 & 15))) : "memory");
                sts32_if(lane == 0, own + 8, 1u << jf | slot << 26);
                sts32_if(lane == 0, own + 12, bar_rec);
                sts128_if(lane == 0, own + 16, make_uint4(0, 0, 0, bar_rec));
                sts128_if(lane == 0, st, c);
            }
            asm volatile("cp.async.wait_all;" ::: "memory");
            __syncwarp();
            return true;
        }
    }
    return false;
}

template <int MODE>
__global__ void __launch_bounds__(NT, 1)
tfn_kernel(const int* __restrict__ dst, const int* __restrict__ src, Scratch* scr, int E, int slice,
           int N, int npc, uint32_t npc_magic, uint32_t bin_magic, const uint2* __restrict__ Y, const uint2* __restrict__ ef,
           const __nv_bfloat16* __restrict__ w_rad, const __nv_bfloat16* __restrict__ cg, const __nv_bfloat16* __restrict__ x,
           const __nv_bfloat16* __restrict__ w_mix, __nv_bfloat16* __restrict__ out, uint32_t pace,
           const __grid_constant__ CUtensorMap xmap, const __grid_constant__ CUtensorMap wmap) {
    extern __shared__ __align__(1024) uint8_t smem[];
    const int tid = threadIdx.x, lane = tid & 31, warp = __shfl_sync(0xffffffffu, tid >> 5, 0);
    const int cta = blockIdx.x;
    const uint32_t bar_w = sb + SM_BAR + NW * S * 8, bar_raw = bar_w + 8, bar_rec = bar_w + 16, bar_mb = bar_w + 24;
    auto prefetch_x = [&](int chunk) {
        const int row = (chunk * NCTA + cta) * PFR;
        if (row < N)
            asm volatile("cp.async.bulk.prefetch.L2.global [%0], %1;" ::"l"(x + (size_t)row * 512), "r"(min(PFR, N - row) * 1024));
    };
    const int g = lane >> 2, t = lane & 3;
    uint32_t wz[4][2], wt[2];
    uint32_t cgr[4];
    auto load_weights = [&]() {
        const uint32_t* wr = reinterpret_cast<const uint32_t*>(w_rad) + (t & 1) * 128;
        const uint16_t* cp = reinterpret_cast<const uint16_t*>(cg) + (t >> 1) * 32 + (t & 1) * 8 + (g & 3);
#pragma unroll
        for (int j = 0; j < 4; j++) {
            asm volatile("ld.global.u32 %0, [%1];" : "=r"(wz[j][0]) : "l"(wr + chunk_of(2 * j + (t >> 1), g)) : "memory");
            asm volatile("ld.global.u32 %0, [%1];" : "=r"(wz[j][1]) : "l"(wr + chunk_of(2 * j + (t >> 1), g) + 64) : "memory");
            asm volatile("ld.global.u16 %0, [%1];" : "=r"(cgr[j]) : "l"(cp + (j >> 1) * 16 + (j & 1) * 4) : "memory");
        }
    };
    auto weights = [&]() {
        const uint32_t z = lds32(sb + SM_ZERO), hh = 0x3f003f00u + z;
        const __nv_bfloat162 half = *reinterpret_cast<const __nv_bfloat162*>(&hh);
#pragma unroll
        for (int j = 0; j < 4; j++) {
            const __nv_bfloat162 h0 = __hmul2(*reinterpret_cast<__nv_bfloat162*>(&wz[j][0]), half);
            const __nv_bfloat162 h1 = __hmul2(*reinterpret_cast<__nv_bfloat162*>(&wz[j][1]), half);
            const uint32_t u0 = *reinterpret_cast<const uint32_t*>(&h0), u1 = *reinterpret_cast<const uint32_t*>(&h1);
            wz[j][0] = __byte_perm(u0, u1, 0x5410);
            wz[j][1] = __byte_perm(u0, u1, 0x7632);
        }
        wt[0] = __byte_perm(cgr[0], cgr[1], 0x5410 + z);
        wt[1] = __byte_perm(cgr[2], cgr[3], 0x5410 + z);
        sts32_if((wz[0][0] ^ wz[0][1] ^ wz[1][0] ^ wz[1][1] ^ wz[2][0] ^ wz[2][1] ^ wz[3][0] ^ wz[3][1] ^ wt[0] ^ wt[1]) == 1,
                 sb + SM_ZERO + 96, 0);
    };

    const int e0 = cta * slice, ne = min(E - e0, slice);
    uint32_t a_d[RA], a_s[RA];
    uint32_t tag = 0;
    if (MODE & 1) {
        const int q = min(e0 / 4 + tid, (E - 1) >> 2), e = min(e0 + 4 * NT + tid, E - 1);
        const int4 d4 = __ldcs(reinterpret_cast<const int4*>(dst) + q);
        a_d[4] = __ldcs(dst + e);
        const int4 s4 = __ldcs(reinterpret_cast<const int4*>(src) + q);
        a_s[4] = __ldcs(src + e);
        a_d[0] = d4.x; a_d[1] = d4.y; a_d[2] = d4.z; a_d[3] = d4.w;
        a_s[0] = s4.x; a_s[1] = s4.y; a_s[2] = s4.z; a_s[3] = s4.w;
    }
    if (MODE == 3) asm volatile("ld.relaxed.gpu.global.u32 %0, [%1];" : "=r"(tag) : "l"(&scr->epoch) : "memory");
    auto load_raw = [&](int which) {
        const int bytes = max((ne + 1) >> 1, 0) * 16;
        asm volatile("mbarrier.arrive.expect_tx.shared::cta.b64 _, [%0], %1;" ::"r"(bar_raw), "r"(bytes) : "memory");
        if (bytes > 0)
            asm volatile("cp.async.bulk.shared::cluster.global.mbarrier::complete_tx::bytes [%0], [%1], %2, [%3];"
                         ::"r"(sb + SM_RAWY + which * SLICE * 8), "l"((which ? ef : Y) + e0), "r"(bytes), "r"(bar_raw) : "memory");
    };
    auto send = [&](bool p, uint32_t* gp, uint4 v) {
        asm volatile("{\n\t.reg .pred p;\n\tsetp.ne.u32 p, %5, 0;\n\t@p st.relaxed.gpu.global.v4.u32 [%0], {%1,%2,%3,%4};\n\t}"
                     ::"l"(gp), "r"(v.x), "r"(v.y), "r"(v.z), "r"(v.w), "r"((uint32_t)p) : "memory");
    };
    uint32_t mc[3];
    auto prewrite = [&](uint4 empty) {
#pragma unroll
        for (int r = 0; r < 3; r++) {
            const uint32_t i = r * NT + tid, c = i < 4 * NCTA ? i >> 2 : ((i - 4 * NCTA) * 10923) >> 16, j = i < 4 * NCTA ? (i & 3) + 2 : i - 4 * NCTA - c * 6 + 6;
            mc[r] = c << 8 | j;
            if (r > 0) send(c < NCTA && j >= 6, scr->mb + c * MBW + cta * MBC + j * 4, empty);
        }
    };
    if ((uint32_t)__cvta_generic_to_shared(smem) != sb) __trap();
    if (elect_one()) {
#pragma unroll
        for (int i = 0; i < S; i++)
            if (warp >= NW) mbar_init(sb + SM_BAR + ((warp - NW) * S + i) * 8, 1);
        if (warp == 0) {
            mbar_init(bar_w, NW);
            mbar_init(bar_raw, 2);
            mbar_init(bar_rec, NW);
            mbar_init(bar_mb, 1);
        }
        asm volatile("fence.mbarrier_init.release.cluster;" ::: "memory");
    }
    fill<SM_KSG - SM_BIN>(sb + SM_BIN, make_uint4(0, 0, 0, 0), tid);
    if (MODE & 1) {
        const uint32_t em = lane << (BSH + 2);
        const uint4 empty = make_uint4(em, em + (1 << BSH), em + (2 << BSH), em + (3 << BSH));
        prewrite(empty);
        fill<NCTA * ASTR * 4>(sb + SM_AMB, empty, tid);
    }
    sts32_if(tid < 32, sb + SM_AOFF + (NCTA + tid) * 4, SLICE);
    sts32_if(tid < 128, sb + SM_DUM + tid * 4, 0x10000);
    if (MODE & 2) {
        const uint32_t pad = RCAP << 18 | N;
        fill<SM_BAR - SM_ZERO>(sb + SM_ZERO, make_uint4(0, 0, 0, 0), tid);
        fill<NG * GK * 16>(sb + SM_KSG, make_uint4(pad, pad, pad, pad), tid);
    }
    __syncthreads();
    if (warp == 13 && (MODE & 2) && elect_one()) {
        asm volatile("cp.async.bulk.prefetch.L2.global [%0], 1024;" ::"l"(w_rad));
        asm volatile("cp.async.bulk.prefetch.L2.global [%0], 128;" ::"l"(cg));
        asm volatile("prefetch.tensormap [%0];" ::"l"(&xmap) : "memory");
        asm volatile("prefetch.tensormap [%0];" ::"l"(&wmap) : "memory");
        asm volatile("st.shared.u64 [%0], %1;" ::"r"(sb + SM_MISC + 24), "l"(&xmap) : "memory");
    }
    if (MODE & 1) {
        if (warp >= 14 && elect_one()) load_raw(warp & 1);
        const uint32_t z = lds32(sb + SM_KEY + lane * 4);
        tag = ((tag + z) & 1) + 1;
        const uint32_t tg = tag << 30;
        uint32_t cc[RA], rk[RA];
#pragma unroll
        for (int r = 0; r < RA; r++) {
            cc[r] = (r < 4 ? 4 * tid + r : 4 * NT + tid) < ne ? __umulhi(a_d[r], npc_magic + z) : NCTA + lane;
            rk[r] = atoms_inc(sb + SM_HIST + cc[r] * 4);
        }
#pragma unroll
        for (int r = 0; r < RA; r++) {
            const uint32_t l = a_d[r] - cc[r] * npc;
            a_s[r] = (tg + ((l < 64 ? (l >> 2) + 1 : (l >> 1) - 15) << 25)) | ((a_s[r] * (bin_magic + z)) & ((NBIN - 1) << BSH)) | a_s[r] | 0x4000u << (l & (l < 64 ? 3 : 1));
            sts32_if(true, sb + SM_AMB + (cc[r] * ASTR + min(rk[r], MBE) + 1) * 4, a_s[r]);
        }
        __syncthreads();
        uint32_t hh[3];
#pragma unroll
        for (int r = 1; r < 3; r++) hh[r] = lds32(sb + SM_HIST + min(mc[r] >> 8, NCTA + 33) * 4);
#pragma unroll
        for (int r = 0; r < 3; r++) {
            const uint32_t c = mc[r] >> 8, j = mc[r] & 15;
            const bool used = r == 0 || j < 6 || (c < NCTA && hh[r] >= (j & 14) * 4);
            if (r == 0 || __any_sync(0xffffffffu, used))
                send(used, scr->mb + c * MBW + cta * MBC + j * 4, lds128(sb + SM_AMB + min(c, NCTA) * (ASTR * 4) + j * 16));
        }
        if (warp >= 7) {
            const uint32_t c = (tid - 7 * 32) >> 1, h = !(tid & 1) && c < NCTA ? lds32(sb + SM_HIST + c * 4) : 0;
            uint4 v = lds128(sb + SM_AMB + c * (ASTR * 4) + (tid & 1) * 16);
            const uint32_t h2 = (h + 1) & ~1, inc = warp_incl_scan(h2);
            const uint32_t off = __shfl_sync(0xffffffffu, atoms_add(sb + SM_HIST + 135 * 4 + lane * 4, lane == 31 ? inc : 0), 31) + inc - h2;
            if (!(tid & 1)) v.x = tg | h << 12 | off;
            send(c < NCTA, scr->mb + c * MBW + cta * MBC + (tid & 1) * 4, v);
            sts32_if(!(tid & 1) && c < NCTA, sb + SM_AOFF + c * 4, off);
        }
        __syncthreads();
        if (MODE == 3 && tid == NT - 1) asm volatile("red.relaxed.gpu.global.add.u32 [%0], 1;" ::"l"(scr->sent + (tag & 1)) : "memory");
        uint32_t ap[2 * RA];
#pragma unroll
        for (int r = 0; r < RA; r++) ap[r] = rk[r] + lds32(sb + SM_AOFF + cc[r] * 4);
        if (__builtin_expect(max(max(max(rk[0], rk[1]), max(rk[2], rk[3])), rk[4]) >= MBE, 0)) {
#pragma unroll
            for (int r = 0; r < RA; r++)
                if (rk[r] >= MBE && cc[r] < NCTA) __stcg(scr->ss + cta * SLICE + ap[r], a_s[r]);
            __threadfence();
        }
        if (warp >= NW) {
            asm volatile("st.shared.v2.u32 [%0], {%1, %2};" ::"r"(sb + SM_AP + (tid - NH) * 8), "r"(ap[0] | ap[1] << 16), "r"(ap[2] | ap[3] << 16) : "memory");
            sts32_if(true, sb + SM_AP + NH * 8 + (tid - NH) * 4, ap[4]);
            bar_arrive<1, NT>();
        } else {
            bar_sync<1, NT>();
            const uint2 u = lds64(sb + SM_AP + tid * 8);
            ap[5] = u.x & 0xffff; ap[6] = u.x >> 16; ap[7] = u.y & 0xffff; ap[8] = u.y >> 16;
            ap[9] = lds32(sb + SM_AP + NH * 8 + tid * 4);
            const bool sw = lane & 4;
            const uint32_t nst = lds32(sb + SM_HIST + 166 * 4) * 16;
            if (MODE == 3) load_weights();
            mbar_wait(bar_raw, 0);
#pragma unroll
            for (int hh = 0; hh < 2; hh++) {
                const uint32_t a = sb + SM_RAWY + (hh * NH + tid) * 32 + (lane & 4) * 4, b = sb + SM_RAWY + (4 * NT + hh * NH + tid) * 8;
                const uint4 y0 = lds128(a), f0 = lds128(a + SLICE * 8), y1 = lds128(a ^ 16), f1 = lds128((a ^ 16) + SLICE * 8);
                const uint2 y2 = lds64(b), f2 = lds64(b + SLICE * 8);
                const uint32_t* q = ap + hh * RA;
                sts128_if(true, sb + SM_AREC + (sw ? q[2] : q[0]) * 16, make_uint4(f0.x, y0.x, f0.y, y0.y));
                sts128_if(true, sb + SM_AREC + (sw ? q[3] : q[1]) * 16, make_uint4(f0.z, y0.z, f0.w, y0.w));
                sts128_if(true, sb + SM_AREC + (sw ? q[0] : q[2]) * 16, make_uint4(f1.x, y1.x, f1.y, y1.y));
                sts128_if(true, sb + SM_AREC + (sw ? q[1] : q[3]) * 16, make_uint4(f1.z, y1.z, f1.w, y1.w));
                sts128_if(true, sb + SM_AREC + q[4] * 16, make_uint4(f2.x, y2.x, f2.y, y2.y));
            }
            asm volatile("fence.proxy.async.shared::cta;" ::: "memory");
            bar_sync<7, NH>();
            if (MODE == 3 && warp == NW - 1) bar_sync<9, 64>();
            if (warp == NW - 1 && lane == 0 && ne > 0)
                asm volatile("cp.async.bulk.global.shared::cta.bulk_group [%0], [%1], %2;"
                             ::"l"(scr->rec + cta * SLICE), "r"(sb + SM_AREC), "r"(nst) : "memory");
            if (MODE == 3) weights();
            if (warp == NW - 1) {
                asm volatile("cp.async.bulk.commit_group;" ::: "memory");
                asm volatile("cp.async.bulk.wait_group 0;" ::: "memory");
                if (MODE == 3) {
                    mbar_wait(bar_mb, 0);
                    if (lane == 0) {
                        const uint32_t now = timer32(), tm = lds32v(sb + SM_MISC + 20);
                        asm volatile("red.relaxed.gpu.global.max.u32 [%0], %1;" ::"l"(scr->sent2[tag & 1] + 8), "r"(max((tm ? tm : now) + PT0, now + PT1)) : "memory");
                        asm volatile("red.relaxed.gpu.global.or.b32 [%0], %1;" ::"l"(scr->sent2[tag & 1] + cta % 6), "r"(1u << cta / 6) : "memory");
                    }
                    uint32_t v;
                    int guard = 0;
                    do {
                        asm volatile("ld.relaxed.gpu.global.u32 %0, [%1];" : "=r"(v) : "l"(scr->sent2[tag & 1] + (lane & 15)) : "memory");
                        sts32_if(lane < NW, sb + SM_MISC + 96 + lane * 4, v);
                    } while (__any_sync(0xffffffffu, lane < 6 && v != (1u << NCTA / 6) - 1) && ++guard < (1 << 20));
                    sts32_if(lane == NW, sb + SM_MISC + 4, v);
                }
            }
        }
    } else {
        tag = 1;
    }
    if (!(MODE & 2)) return;
    const int wl = warp & (NW - 1);
    const uint32_t ring = sb + SM_RING + wl * (S * 1024);
    const uint32_t bars = sb + SM_BAR + wl * (S * 8);
    const uint32_t pos = bar_w + 32 + wl * 4;

    if (warp >= NW) {
        uint32_t ss[RL + 1], rk[RL + 1];
        const uint32_t sl = wl + 8 * lane, empty = lane << BSH;
        if (wl == 0) {
            if (elect_one()) {
                asm volatile("mbarrier.arrive.expect_tx.shared::cta.b64 _, [%0], %1;" ::"r"(bar_mb), "n"(MBW * 4) : "memory");
                asm volatile("{\n\t.reg .pred p;\n\t.reg .b32 n, v;\n\tmov.b32 n, 0;\n"
                             "AGAIN:\n\tld.relaxed.gpu.global.u32 v, [%4];\n\tadd.u32 n, n, 1;\n\tsetp.lt.u32 p, n, 1048576;\n\t"
                             "setp.lt.and.u32 p, v, %5, p;\n\t@p bra.uni AGAIN;\n\t"
                             "cp.async.bulk.shared::cluster.global.mbarrier::complete_tx::bytes [%0], [%1], %2, [%3];\n\t}"
                             ::"r"(sb + SM_AMB), "l"(scr->mb + cta * MBW + lds32v(sb + SM_ZERO)), "n"(MBW * 4), "r"(bar_mb),
                               "l"(scr->sent + (tag & 1)), "n"(MODE == 3 ? NCTA : 0) : "memory");
            }
            __syncwarp();
            if (MODE == 3) bar_arrive<9, 64>();
            if (MODE != 3) sts32_if(true, sb + SM_MISC + 4, timer32() + PT0);
        }
        uint32_t loc, cnt, from, big;
        for (int guard = 0;; guard++) {
            mbar_wait(bar_mb, 0);
            loc = lds32(sb + SM_AMB + min(sl, NCTA - 1) * (MBC * 4));
#pragma unroll
            for (int r = 0; r < RL; r++) ss[r] = lds32(sb + SM_AMB + ((wl + 8 * r) * MBC + lane + 1) * 4);
            if (MODE == 3) sts32_if(wl == NW - 1, sb + SM_MISC + 20, timer32());
            if (wl + 8 * (RL - 1) >= NCTA) ss[RL - 1] = empty;
            cnt = sl < NCTA ? loc >> 12 & 0xfff : 0;
            big = __ballot_sync(0xffffffffu, cnt > 32);
            from = __ffs((lane < 16 ? big : big & (big - 1)) | 1 << RL) - 1;
            cnt = min(cnt, __popc(big & ((1u << lane) - 1)) < 2 ? MBE : 32);
            ss[RL] = lds32(sb + SM_AMB + ((wl + 8 * from) * MBC + 33 + (lane & 15)) * 4);
            if (32 + (lane & 15) >= __shfl_sync(0xffffffffu, cnt, from)) ss[RL] = empty;
            uint32_t any = ~loc >> 30 & tag ? 0xffffffffu : 0, got[2] = {-cnt * tag, 0};
#pragma unroll
            for (int r = 0; r <= RL; r++) { any |= ss[r]; got[r & 1] += ss[r] >> 30; }
            if (!__reduce_add_sync(0xffffffffu, got[0] + got[1] + (any >> 30 & (3 - tag) ? 0x10000 : 0)) || guard == 1 << 20) break;
#pragma unroll 1
            for (int r = wl; r < NCTA; r += 8)
                if (lane < MBC / 4)
                    sts128_if(true, sb + SM_AMB + (r * MBC + lane * 4) * 4, ldg128_relaxed(reinterpret_cast<const uint4*>(scr->mb + cta * MBW + r * MBC) + lane));
            __syncwarp();
        }
        auto bin_of = [&](uint32_t w) { return sb + SM_DUM + (w >> (BSH - 2) & (NBIN * 128 - 4)); };
#pragma unroll
        for (int r = 0; r <= RL; r++) rk[r] = atoms_add(bin_of(ss[r]), 4);
        bar_sync<3, NH>();
        uint32_t dof;
        {
            const uint32_t a = sb + SM_BIN + wl * (NBIN * 12) + lane * 16;
            uint4 u[3];
            uint32_t sum[3];
#pragma unroll
            for (int j = 0; j < 3; j++) {
                u[j] = lds128(a + j * (NBIN * 4));
                sum[j] = u[j].x + u[j].y + u[j].z + u[j].w;
            }
            uint32_t i01 = sum[0] | sum[1] << 16, i2 = sum[2] | ((cnt + 1) & ~1) << 16;
#pragma unroll
            for (int o = 1; o < 32; o <<= 1) {
                scan_step(i01, o);
                scan_step(i2, o);
            }
            dof = atoms_add(sb + SM_MISC - 124 + lane * 4, lane == 31 ? i2 >> 16 : 0);
            const uint32_t inc[3] = {i01 & 0xffff, i01 >> 16, i2 & 0xffff};
#pragma unroll
            for (int j = 0; j < 3; j++) {
                const uint32_t p = (3 * wl + j) * (GK * 16) + inc[j] - sum[j];
                sts128_if(true, a + j * (NBIN * 4), make_uint4(p, p + u[j].x, p + u[j].x + u[j].y, p + u[j].x + u[j].y + u[j].z));
                sts32_if(lane == 31, sb + SM_KEY + (3 * wl + j) * 4, (inc[j] + 12) >> 4 << 5 | (3 * wl + j));
            }
            dof = __shfl_sync(0xffffffffu, dof, 31) + (i2 >> 16) - ((cnt + 1) & ~1);
            sts32_if(sl < NCTA, sb + SM_SEG + sl * 4, loc & 0xffffff);
            sts32_if((loc >> 12 & 0xfff) > MBE, sb + SM_MISC + 8, 1);
            sts32_if(true, sb + SM_DOFF + (tid - NH) * 4, dof << 18);
            const uint64_t from = reinterpret_cast<uint64_t>(scr->rec + sl * SLICE + (loc & 0xfff));
            sts128_if(sl < NCTA, sb + SM_CPY + sl * 16,
                      make_uint4((uint32_t)from, (uint32_t)(from >> 32), sb + SM_REC + dof * 16, min(cnt, RCAP - min(dof, RCAP)) * 16));
        }
        bar_arrive<4, NT - 32>();
        bar_sync<3, NH>();
        const uint32_t key = lds32(sb + SM_KEY + lane * 4), nrec = lds32(sb + SM_MISC);
        uint32_t d20[RL + 3];
#pragma unroll
        for (int r = 0; r < RL; r += 4) {
            const uint4 v = lds128(sb + SM_DOFF + wl * 128 + r * 4);
            d20[r] = v.x; d20[r + 1] = v.y; d20[r + 2] = v.z; d20[r + 3] = v.w;
        }
#pragma unroll
        for (int r = 0; r <= RL; r++) {
            uint32_t v;
            asm volatile("{\n\t.reg .pred p;\n\tsetp.lt.u32 p, %2, 0x10000;\n\tmov.b32 %0, %2;\n\t@p ld.shared.u32 %0, [%1];\n\t}"
                         : "=&r"(v) : "r"(bin_of(ss[r])), "r"(rk[r]) : "memory");
            rk[r] += v;
        }
        d20[RL] = (__shfl_sync(0xffffffffu, dof, from) + 32 - (lane & 16)) << 18;
        const uint32_t cap = group_cap(key, lane);
        const uint32_t lim = __any_sync(0xffffffffu, (key >> 5) > cap || nrec > RCAP) ? 0 : 0x20000;
#pragma unroll
        for (int r = 0; r <= RL; r++) {
            uint32_t v;
            asm("lop3.b32 %0, %1, 0x3ffff, %2, 0xea;" : "=r"(v) : "r"(ss[r]), "r"(lane << 18));
            sts32_if(rk[r] < lim, sb + SM_KSG + rk[r], v + d20[r]);
        }
        if (__builtin_expect(lim == 0 || __popc(big) > 2, 0)) {
            auto excess = [&](uint32_t w, uint32_t gi) { __stcg(scr->exc + cta * MBW + atoms_inc(sb + SM_MISC + 12), make_uint2(w, gi)); };
            big &= big - 1;
#pragma unroll 1
            for (big &= big - 1; big; big &= big - 1) {
                const uint32_t r = __ffs(big) - 1, l = __shfl_sync(0xffffffffu, loc, r);
                if (32 + lane < min(l >> 12 & 0xfff, MBE)) {
                    uint32_t w;
                    int guard = 0;
                    do asm volatile("ld.relaxed.gpu.global.u32 %0, [%1];" : "=r"(w) : "l"(scr->mb + cta * MBW + (wl + 8 * r) * MBC + 33 + lane) : "memory");
                    while (w >> 30 != tag && ++guard < (1 << 20));
                    excess(w, (wl + 8 * r) * SLICE + (l & 0xfff) + 32 + lane);
                }
            }
            const uint32_t tmp = sb + SM_AMB + (wl * MBC + lane) * 4;
#pragma unroll 1
            for (int part = 0; part < (lim ? 0 : 3); part++) {
#pragma unroll
                for (int r = 0; r <= RL; r++)
                    if (r / 8 == part) {
                        sts32_if(true, tmp + (r & 7) * (16 * MBC * 4), ss[r]);
                        sts32_if(true, tmp + ((r & 7) * 2 + 1) * (8 * MBC * 4), rk[r]);
                    }
#pragma unroll 1
                for (int r = part * 8; r < min(part * 8 + 8, RL + 1); r++) {
                    const uint32_t w = lds32(tmp + (r & 7) * (16 * MBC * 4)), p = lds32(tmp + ((r & 7) * 2 + 1) * (8 * MBC * 4));
                    const uint32_t rnk = r < RL ? lane : 32 + (lane & 15), fr = r < RL ? r : from, gw = (w >> 25 & 31) - 1;
                    const uint32_t ri = __shfl_sync(0xffffffffu, dof, fr) + rnk, gi = __shfl_sync(0xffffffffu, loc & 0xfff, fr) + rnk;
                    const bool fits = p - gw * (GK * 16) < __shfl_sync(0xffffffffu, cap, gw) * 16;
                    if (p < 0x20000) {
                        sts32_if(fits, sb + SM_KSG + p, min(ri, RCAP) << 18 | (w & 0x3ffffu));
                        if (!fits || ri >= RCAP) excess(w, (wl + 8 * fr) * SLICE + gi);
                    }
                }
            }
        }
        bar_sync<8, NH + 32>();
        const uint4 lt = lds128(sb + SM_LT + 128 + wl * 16), lo = lds128(sb + SM_LT + 256 + wl * 16);
        const uint32_t lb = lt.w, len = lt.z, le = lb + len;
        if (__builtin_expect(len <= 96, 1)) build_list<3>(lt, lo, wl, lane, N, bin_magic, pace);
        else build_list<4>(lt, lo, wl, lane, N, bin_magic, pace);
        bar_arrive<2, NT>();
        const uint32_t z = lds32(sb + SM_ZERO + (lane & 3) * 4);
        const uint32_t bytes = opaque(4096 + z);
        const uint4 z0 = lds128v(sb + SM_ZERO);
        const uint2 tm = lds64(sb + SM_MISC + 24);
        bar_sync<5, NT>();
        asm volatile("setmaxnreg.dec.sync.aligned.u32 24;");
        if (elect_one()) {
            uint32_t ka = sb + SM_LIST + lb * 16 - 16 * (S - 1);
            int row = ((1 + wl) * NCTA + cta) * PFR;
            asm volatile(PRODUCER_PTX : "+r"(ka), "+r"(row)
                : "r"(ring), "r"(bars), "l"((uint64_t)tm.y << 32 | tm.x),
                  "r"(z0.x), "r"(z0.y), "r"(z0.z), "r"(z0.w), "r"(pos), "r"(ka + len * 16), "r"(lds32v(sb + SM_MISC + 4)), "r"(bytes),
                  "l"(x), "r"(N), "n"(RSTR), "n"(SM_SRC - SM_LIST + 16 * (S - 1)), "n"(PFA), "n"(PFR), "n"(NW * NCTA * PFR) : "memory");
            for (int guard = 0; lds32v(pos) + 16 * (S - 1) < sb + SM_LIST + le * 16 && guard < (1 << 20); guard++) __nanosleep(NSLEEP);
            const uint32_t d = ring + (len - ((len * SMG) >> 16) * S) * 1024;
            sts32_if(true, sb + SM_MISC + 32 + wl * 4, (d - (sb + SM_RING)) >> 4);
            asm volatile("mbarrier.arrive.expect_tx.shared::cta.b64 _, [%0], 4096;" ::"r"(bar_w) : "memory");
#pragma unroll
            for (uint32_t r = 0; r < 8; r++)
                asm volatile("cp.async.bulk.tensor.5d.shared::cluster.global.tile.mbarrier::complete_tx::bytes [%0], [%1, {%2, %3, %4, %5, %6}], [%7];"
                             ::"r"(d + (r >> 1) * RSTR + (r & 1) * 512), "l"(((uint64_t)tm.y << 32 | tm.x) + sizeof(CUtensorMap)), "r"((r >> 2) * 64), "r"((r >> 1) & 1),
                               "r"((wl >> 1) & 2), "r"(((r ^ (wl >> 1)) & 1) + (wl & 1) * 2), "r"(wl & 2), "r"(bar_w) : "memory");
        }
        return;
    }

    {
        if (MODE == 2) { load_weights(); weights(); }
        if (warp < NW - 1) bar_sync<4, NT - 32>();
        if (warp == 0) {
            const uint32_t key = lds32(sb + SM_KEY + lane * 4);
            int rank = 0;
#pragma unroll
            for (int j = 0; j < 4; j++) {
                const uint4 o = lds128(sb + SM_KEY + (lane & 16) * 4 + j * 16);
                rank += ((key - o.x) >> 31) + ((key - o.y) >> 31) + ((key - o.z) >> 31) + ((key - o.w) >> 31);
            }
            const int n2 = 2 * __popc(__ballot_sync(0xffffffffu, key < 32) & 0xff0000);
            const int other = (rank < n2 ? n2 - 1 : 15 + n2) - rank;
            const int li = lane >= 16 ? 7 - rank : min(rank, other) - (rank < n2 ? 0 : n2 / 2);
            sts32_if(lane < NG, sb + SM_LT + (li < 4 ? li : 11 - li) * 16 + (lane >= 16 ? 8 : rank < other ? 0 : 4), min(key >> 5, group_cap(key, lane)) << 5 | lane);
            __syncwarp();
            const uint4 lt = lds128(sb + SM_LT + (lane & 7) * 16);
            const uint32_t len = (lt.x >> 5) + (lt.y >> 5) + (lt.z >> 5);
            uint32_t le = len + 1;
#pragma unroll
            for (int o = 1; o < 8; o <<= 1) scan_step(le, o);
            le -= 1;
            const uint32_t n0 = lt.x >> 5, n01 = n0 + (lt.y >> 5);
            sts128_if(lane < 2 * NW, sb + SM_LT + 128 + lane * 16, lane < NW ? make_uint4(n0, n01, len, le - len) :
                      make_uint4((lt.x & 31) * (GK * 16), ((lt.y & 31) * GK - n0) * 16, ((lt.z & 31) * GK - n01) * 16, 0));
            bar_arrive<8, NH + 32>();
            if (lane < NW) {
                sts32_if(true, sb + SM_LIST + le * 16 + 12, bar_rec);
                sts32_if(true, bar_w + 32 + lane * 4, sb + SM_LIST + (le - len) * 16);
                sts32_if(true, sb + SM_MISC + 64 + lane * 4, (lt.x & 31) | (lt.y & 31) << 5 | (lt.z & 31) << 10 | len << 16);
            }
        }
        uint4 cp = make_uint4(0, 0, 0, 0);
        if (warp > 0 && warp < NW - 1 && lane < NCTA / 6) cp = lds128(sb + SM_CPY + (warp - 1 + 6 * lane) * 16);
        const uint32_t total = __reduce_add_sync(0xffffffffu, cp.w);
        bar_arrive<5, NT>();
        if (lane == 0) asm volatile("mbarrier.arrive.expect_tx.shared::cta.b64 _, [%0], %1;" ::"r"(bar_rec), "r"(total) : "memory");
        unsigned todo = __ballot_sync(0xffffffffu, cp.w);
        for (int guard = 0; todo && guard < (1 << 22); guard++) {
            const unsigned go = MODE == 3 ? todo & lds32v(sb + SM_MISC + 92 + warp * 4) : todo;
            if (go) {
                asm volatile("fence.proxy.async.global;" ::: "memory");
                if (go >> lane & 1)
                    asm volatile("cp.async.bulk.shared::cluster.global.mbarrier::complete_tx::bytes [%0], [%1], %2, [%3];"
                                 ::"r"(cp.z), "l"((uint64_t)cp.y << 32 | cp.x), "r"(cp.w), "r"(bar_rec) : "memory");
                todo ^= go;
            } else {
                __nanosleep(20);
            }
        }
        if (tid == 0) prefetch_x(0);
        if (MODE == 3 && cta == 0 && tid == 0) {
            scr->epoch = tag;
            scr->sent[~tag & 1] = 0;
            for (int i = 0; i < 9; i++) scr->sent2[~tag & 1][i] = 0;
        }
        if (tid == 0 && cta < 128) asm volatile("cp.async.bulk.prefetch.L2.global [%0], 256;" ::"l"(w_mix + cta * 128));
        bar_sync<2, NT>();
        asm volatile("setmaxnreg.inc.sync.aligned.u32 232;" ::: "memory");
    }

    float acc[40][4];
    const uint32_t z = lds32(sb + SM_ZERO + t * 4);
#pragma unroll
    for (int j = 0; j < 40; j++) acc[j][0] = acc[j][1] = acc[j][2] = acc[j][3] = 0.f;
    const bool bact = (g & 1) == (t >> 1);
    mbar_wait(bar_rec, 0);
    {
        auto keep = [&](uint32_t v) { return __shfl_sync(0xffffffffu, v + z, lane); };
        const uint32_t va0 = keep(ring + t * RSTR + (g & 2) * 128 + (g & 1) * 16 + ((((g >> 1) & 2) ^ ((((g >> 1) & 1) + t) & 3)) << 5));
        const uint32_t hm0 = keep(HM0(g >> 2)), hm1 = keep(0x40000u << (g >> 2)), sel = keep(0x1010u + (g >> 1) * 0x22 + t * 0x2200);
        const uint32_t rl = keep(bact ? (t & 1) * 8 : SM_ZERO - SM_REC), rm = keep(bact ? 0xfff0u : 0u);
        uint32_t lp = keep(lds32(pos));
        for (;;) {
        asm volatile(MAIN_LOOP_PTX : MAIN_LOOP_ACC(acc), "+r"(lp)
            : "r"(wz[0][0]), "r"(wz[0][1]), "r"(wz[1][0]), "r"(wz[1][1]), "r"(wz[2][0]), "r"(wz[2][1]), "r"(wz[3][0]), "r"(wz[3][1]),
              "r"(wt[0]), "r"(wt[1]), "r"(va0), "r"(hm0), "r"(hm1), "r"(rl), "r"(rm), "r"(sel), "r"(pos), "n"(sb + SM_REC)
            : "memory");
            sts32_if(true, sb + SM_ZERO + 96, lp);
            const uint2 left = lds64(sb + SM_MISC + 8);
            if (__builtin_expect(!(left.x | left.y), 1)) break;
            if (!next_excess(scr, x, va0)) break;
            lp = sb + SM_SRC + wl * 96 + (sel & 1);
        }
    }
    const uint32_t grp = lds32(sb + SM_MISC + 64 + wl * 4);

    uint32_t aq[3][8][4];
    auto pack = [&](int j) {
#pragma unroll
        for (int m = 0; m < 8; m++) {
            if (j < 2) {
#pragma unroll
                for (int q = 0; q < 4; q++) {
                    const float* a = acc[16 * j + 2 * m + (q >> 1)] + (q & 1) * 2;
                    asm volatile("cvt.rn.bf16x2.f32 %0, %1, %2;" : "=r"(aq[j][m][q]) : "f"(a[~m & 1]), "f"(a[m & 1]));
                }
            } else {
                aq[2][m][0] = movm(pack_bf16(acc[32 + m][0], acc[32 + m][1]));
                aq[2][m][2] = movm(pack_bf16(acc[32 + m][2], acc[32 + m][3]));
                if (m & 1) {
                    aq[2][m][0] = __byte_perm(aq[2][m][0], 0, 0x1032);
                    aq[2][m][2] = __byte_perm(aq[2][m][2], 0, 0x1032);
                }
                aq[2][m][1] = aq[2][m][3] = 0;
#pragma unroll
                for (int q = 0; q < 4; q++) asm volatile("" : "+r"(aq[2][m][q]));
            }
        }
    };
    pack(0);
    mbar_wait(bar_w, 0);
    const uint4 ws0 = lds128(sb + SM_MISC + 32), ws1 = lds128(sb + SM_MISC + 48);
    const uint32_t ws[8] = {ws0.x, ws0.y, ws0.z, ws0.w, ws1.x, ws1.y, ws1.z, ws1.w};
    const uint64_t wdesc = ((sb + SM_RING) >> 4) | ((uint64_t)(2 * RSTR >> 4) << 16) | ((uint64_t)(RSTR >> 4) << 32) | (1ull << 62);
    const int nloc = min(npc, N - cta * npc);
    uint32_t ln;
    asm volatile("mov.u32 %0, %laneid;" : "=r"(ln));
    const bool odd = ln & 1;
    const int hi = ln >> 1 & 1;
    uint2* op = reinterpret_cast<uint2*>(out) + (size_t)(cta * npc) * 128 + (ln >> 2) + (ln & 1) * 8;
    float d[2][32];
    auto mix = [&](int job) {
        asm volatile("wgmma.fence.sync.aligned;" ::: "memory");
#pragma unroll
        for (int m = 0; m < 8; m++) wgmma_n64(d[job & 1], aq[job >> 1][m], wdesc + ws[m] + (job & 1) * (2 * RSTR >> 4), m);
        asm volatile("wgmma.commit_group.sync.aligned;" ::: "memory");
    };
    mix(0);
    if (nloc > NCTA) __trap();
    pack(1);
    pack(2);
#pragma unroll
    for (int job = 0; job < 6; job++) {
        if (nloc + 2 * job + 1 > NCTA) __trap();
        asm volatile("wgmma.wait_group.sync.aligned 0;" ::: "memory");
        float (&dd)[32] = d[job & 1];
#pragma unroll
        for (int k = 0; k < 32; k++) asm volatile("" : "+f"(dd[k]));
        if (job < 5) mix(job + 1);
        if (job > 0 && nloc + 2 * job + 2 > NCTA) __trap();
#pragma unroll
        for (int h = 0; h < (job < 4 ? 2 : 1); h++) {
            const int gj = grp >> (5 * (job >> 1)) & 31;
            const int l = job < 4 ? gj * 4 + 2 * h + hi : gj * 2 + 32 + hi;
            const bool ok = l < nloc;
#pragma unroll
            for (int j = 0; j < 8; j += 2) {
                const uint32_t p0 = movm(pack_bf16(dd[4 * j + 2 * h], dd[4 * j + 2 * h + 1])), p1 = movm(pack_bf16(dd[4 * j + 4 + 2 * h], dd[4 * j + 5 + 2 * h]));
                const uint32_t rv = __shfl_xor_sync(0xffffffffu, odd ? p0 : p1, 1);
                if (ok) op[l * 128 + (job & 1) * 64 + j * 8] = odd ? make_uint2(rv, p1) : make_uint2(p0, rv);
            }
        }
    }
    __syncwarp();
}

}

extern "C" void kernel_launch(void* const* d_in, const int* in_sizes, int n_in, void* d_out, int out_size) {
    const __nv_bfloat16* x     = (const __nv_bfloat16*)d_in[0];
    const int*           src   = (const int*)d_in[1];
    const int*           dst   = (const int*)d_in[2];
    const uint2*         Y     = (const uint2*)d_in[3];
    const uint2*         ef    = (const uint2*)d_in[4];
    const __nv_bfloat16* w_rad = (const __nv_bfloat16*)d_in[5];
    const __nv_bfloat16* cg    = (const __nv_bfloat16*)d_in[6];
    const __nv_bfloat16* w_mix = (const __nv_bfloat16*)d_in[7];
    __nv_bfloat16*       out   = (__nv_bfloat16*)d_out;
    const int N = in_sizes[0] / 512;
    const int E = in_sizes[1];

    static int n_sm = 0;
    static Scratch* scr = nullptr;
    static decltype(&cuTensorMapEncodeTiled) encode = nullptr;
    if (n_sm == 0) {
        cudaDriverEntryPointQueryResult qr;
        cudaGetDriverEntryPoint("cuTensorMapEncodeTiled", (void**)&encode, cudaEnableDefault, &qr);
        cudaGetSymbolAddress((void**)&scr, g_scr);
        int dev = 0;
        cudaGetDevice(&dev);
        cudaDeviceGetAttribute(&n_sm, cudaDevAttrMultiProcessorCount, dev);
        cudaFuncSetAttribute(tfn_kernel<1>, cudaFuncAttributeMaxDynamicSharedMemorySize, SM_TOTAL);
        cudaFuncSetAttribute(tfn_kernel<2>, cudaFuncAttributeMaxDynamicSharedMemorySize, SM_TOTAL);
        cudaFuncSetAttribute(tfn_kernel<3>, cudaFuncAttributeMaxDynamicSharedMemorySize, SM_TOTAL);
    }
    CUtensorMap xmap;
    {
        const cuuint64_t dims[2] = {64, (cuuint64_t)N * 8}, strides[1] = {128};
        const cuuint32_t box[2] = {64, 8}, es[2] = {1, 1};
        encode(&xmap, CU_TENSOR_MAP_DATA_TYPE_BFLOAT16, 2, (void*)x, dims, strides, box, es, CU_TENSOR_MAP_INTERLEAVE_NONE,
               CU_TENSOR_MAP_SWIZZLE_128B, CU_TENSOR_MAP_L2_PROMOTION_NONE, CU_TENSOR_MAP_FLOAT_OOB_FILL_NONE);
    }
    CUtensorMap wmap;
    {
        const cuuint64_t dims[5] = {128, 2, 4, 4, 4}, strides[4] = {256, 512, 2048, 8192};
        const cuuint32_t box[5] = {64, 1, 2, 1, 2}, es[5] = {1, 1, 1, 1, 1};
        encode(&wmap, CU_TENSOR_MAP_DATA_TYPE_BFLOAT16, 5, (void*)w_mix, dims, strides, box, es, CU_TENSOR_MAP_INTERLEAVE_NONE,
               CU_TENSOR_MAP_SWIZZLE_128B, CU_TENSOR_MAP_L2_PROMOTION_NONE, CU_TENSOR_MAP_FLOAT_OOB_FILL_NONE);
    }
    const int slice = ((E + NCTA - 1) / NCTA + 3) / 4 * 4;
    const int npc   = (N + NCTA - 1) / NCTA;
    const uint32_t npc_magic = (uint32_t)((0x100000000ull + npc - 1) / npc);
    const uint32_t bin_magic = (uint32_t)((1ull << 25) / N);
    const double want = PDT * (double)E / (32.0 * N);
    const uint32_t pace = (uint32_t)((want < 1 ? 1 : want > 94 ? 94 : want) * (1 << 25));
    cudaStream_t st = cudaStreamPerThread;
    if (n_sm >= NCTA) {
        tfn_kernel<3><<<NCTA, NT, SM_TOTAL, st>>>(dst, src, scr, E, slice, N, npc, npc_magic, bin_magic, Y, ef, w_rad, cg, x, w_mix, out, pace, xmap, wmap);
    } else {
        tfn_kernel<1><<<NCTA, NT, SM_TOTAL, st>>>(dst, src, scr, E, slice, N, npc, npc_magic, bin_magic, Y, ef, w_rad, cg, x, w_mix, out, pace, xmap, wmap);
        tfn_kernel<2><<<NCTA, NT, SM_TOTAL, st>>>(dst, src, scr, E, slice, N, npc, npc_magic, bin_magic, Y, ef, w_rad, cg, x, w_mix, out, pace, xmap, wmap);
    }
}
```
